```python
import torch

def _softmax(x, axis=-1):
    return torch.softmax(x, dim=axis)
def _gelu(x):
    return torch.nn.functional.gelu(x, approximate="tanh")
def _silu(x):
    return torch.nn.functional.silu(x)
def _sigmoid(x):
    return torch.sigmoid(x)
def _layernorm(x, axis=-1, eps=1e-5):
    m = x.mean(dim=axis, keepdim=True)
    v = x.var(dim=axis, keepdim=True, unbiased=False)
    return (x - m) / torch.sqrt(v + eps)
def _scatter_add(tgt, idx, src, axis=0):
    return tgt.clone().index_add_(axis, idx, src)
def _segment_sum(src, seg, n):
    out = torch.zeros((n,) + src.shape[1:], dtype=src.dtype)
    return out.index_add_(0, seg, src)
def _pad(x, pw):
    flat = tuple(v for pair in reversed(pw) for v in pair)
    return torch.nn.functional.pad(x, flat)

kernel_name = 'parallel_sum__sliding_local_dilated__moe_arch_mod__prompt'

def setup_inputs():

    _w = (lambda a: (lambda t: t.to(torch.bfloat16) if t.is_floating_point() else t)(torch.as_tensor(a)))
    def _A_setup():
        B, S, D = 1, 2048, 1024
        return {
            "x": _w((lambda *s: torch.randn(*s, dtype=torch.bfloat16) * 0.05)(B, S, D)),
            "wqkv": _w((lambda *s: torch.randn(*s, dtype=torch.bfloat16) * 0.05)(D, 3 * D)),
            "wo": _w((lambda *s: torch.randn(*s, dtype=torch.bfloat16) * 0.05)(D, D)),
        }
    _A_in = _A_setup()

    def _B_setup():
        B, S, D, F, C = 1, 2048, 1024, 3584, 8
        return {
            "x": _w((lambda *s: torch.randn(*s, dtype=torch.bfloat16) * 0.05)(B, S, D)),
            "w_r": _w((lambda *s: torch.randn(*s, dtype=torch.bfloat16) * 0.05)(D)),
            "w_gate": _w((lambda *s: torch.randn(*s, dtype=torch.bfloat16) * 0.05)(D, F)),
            "w_up": _w((lambda *s: torch.randn(*s, dtype=torch.bfloat16) * 0.05)(D, F)),
            "w_down": _w((lambda *s: torch.randn(*s, dtype=torch.bfloat16) * 0.05)(F, D)),
        }
    _B_in = _B_setup()

    return {
        "A_x": _A_in["x"],
        "A_wqkv": _A_in["wqkv"],
        "A_wo": _A_in["wo"],
        "B_x": _B_in["x"],
        "B_w_r": _B_in["w_r"],
        "B_w_gate": _B_in["w_gate"],
        "B_w_up": _B_in["w_up"],
        "B_w_down": _B_in["w_down"],
    }

def reference(A_x, A_wqkv, A_wo, B_x, B_w_r, B_w_gate, B_w_up, B_w_down):
    def _A_ref(x, wqkv, wo):
        B, S, D = x.shape
        H = 32; Dh = D // H
        W, dil = 8, 2
        qkv = (lambda x, *d: x.permute(*d))((x @ wqkv).reshape(B, S, 3, H, Dh), 2, 0, 3, 1, 4)
        q, k, v = qkv[0], qkv[1], qkv[2]
        scale = Dh ** -0.5
        pos = torch.arange(S)
        off = torch.arange(W) * dil
        idx = pos[:, None] - off[None, :]
        mask = idx >= 0
        idx_c = torch.where(mask, idx, 0).reshape(-1)
        kg = k[:, :, idx_c, :].reshape(B, H, S, W, Dh)
        vg = v[:, :, idx_c, :].reshape(B, H, S, W, Dh)
        logits = torch.einsum("bhsd,bhswd->bhsw", q, kg) * scale
        logits = torch.where(mask[None, None, :, :], logits, -1e9)
        attn = _softmax(logits, axis=-1)
        o = torch.einsum("bhsw,bhswd->bhsd", attn, vg)
        return (lambda x, *d: x.permute(*d))(o, 0, 2, 1, 3).reshape(B, S, D) @ wo

    def _B_ref(x, w_r, w_gate, w_up, w_down):
        B, S, D = x.shape
        C = 8
        r = x @ w_r
        idx = torch.argsort(-r, axis=-1)[:, :C]
        idx_e = (lambda x, n, axis: torch.repeat_interleave(x, n, dim=axis))(idx.reshape(B, C, 1), D, axis=2)
        x_sel = (lambda x, i, axis: torch.take_along_dim(x, i, dim=axis))(x, idx_e, axis=1)
        g = _silu(x_sel @ w_gate)
        u = x_sel @ w_up
        y = (g * u) @ w_down
        r_sel = _sigmoid((lambda x, i, axis: torch.take_along_dim(x, i, dim=axis))(r, idx, axis=1))
        y = y * r_sel.reshape(B, C, 1)
        b_off = (torch.arange(B) * S).reshape(B, 1)
        flat_idx = (idx + b_off).reshape(B * C)
        zero = (x * 0.0).reshape(B * S, D)
        upd = _scatter_add(zero, flat_idx, y.reshape(B * C, D), axis=0)
        return x + upd.reshape(B, S, D)

    x = A_x
    xn = _layernorm(x, axis=-1)
    return x + _A_ref(xn, A_wqkv, A_wo) + _B_ref(xn, B_w_r, B_w_gate, B_w_up, B_w_down)
```

```cpp
#include <cuda_runtime.h>
#include <cuda.h>
#include <cuda_bf16.h>
#include <stdint.h>

namespace {

constexpr int STAGE = 57344;
constexpr int OFF_FW = 3 * STAGE;
constexpr int OFF_FA = OFF_FW + 49152;
constexpr int OFF_CS = OFF_FA + 6144;
constexpr int OFF_STAT = OFF_CS + 1232;
constexpr int OFF_ROWMAP = OFF_STAT + 2112;
constexpr int OFF_TAG = OFF_ROWMAP + 128;
constexpr int OFF_BAR = OFF_TAG + 8;
constexpr int OFF_F2X = 16384, OFF_HALO = 24576, OFF_O1 = 24576, OFF_O0 = 73728, OFF_WO = 106496, NWO = 7, OFF_MEAN = 2 * STAGE;
static_assert(OFF_WO + NWO * 16384 == OFF_FA && OFF_O0 + 32768 == OFF_WO && OFF_O1 + 32768 == STAGE, "alias");
constexpr int B_FULLA = 0, B_FULLB = 3, B_ROW = 6, B_FFULL = 11, B_FEMPTY = 14, B_F2DONE = 17, B_WOFULL = 18, B_OFULL = B_WOFULL + 16,
              B_DONE = B_OFULL + 32;
constexpr int B_EMPTY = B_DONE + 28, B_G1DONE = B_EMPTY + 3;
constexpr int B_UPD = B_G1DONE + 1, B_F2FULL = B_UPD + 1;
constexpr int B_AUX = B_F2FULL + 1, B_PART = B_AUX + 1, B_ATT = B_PART + 1, B_CSDONE = B_ATT + 1, NBAR = B_CSDONE + 1;
constexpr int SMEM_BYTES = OFF_BAR + NBAR * 8;
static_assert(SMEM_BYTES <= 232448 && OFF_BAR % 8 == 0, "smem");
#define LEAD 3
#define F1_MASK 0x6a005600u
#define N_PF 0
#define PF_START 4
#define EARLY_FILL 2
#define N_S1 2
#define T_X 500
#define D_X 350
#define T_ROW 1000
#define D_R 400
#define T_W 1500
#define D_W 500
#define T_CS 2400
#define W_LAG (nt & 3)
#define POLL_NS 100
#define STATS_UNROLL 4
constexpr int kStatsUnroll = STATS_UNROLL;
constexpr int SPIN_LIMIT = 1 << 18;

struct Scratch {
    uint8_t o[2048 * 1024 * 2];
    uint2 rec[2048];
    float cs[8][3072];
    uint32_t halo[128][512];
    uint32_t h[14336];
    float ypart[8][8][1024];
    uint2 sel[16];
    uint32_t epoch;
};
__device__ __align__(1024) Scratch g_scr;

#define TS(i) do {} while (0)
#define TS_END() do {} while (0)
#define NRETRY() do {} while (0)
constexpr int SMEM_LAUNCH = SMEM_BYTES;
#define TSC(c, i) do {} while (0)
__device__ __forceinline__ uint32_t smem_u32(const void* p) { return (uint32_t)__cvta_generic_to_shared(p); }
__device__ __forceinline__ void mbar_init(uint32_t bar, uint32_t cnt) { asm volatile("mbarrier.init.shared::cta.b64 [%0], %1;" ::"r"(bar), "r"(cnt) : "memory"); }
__device__ __forceinline__ void mbar_expect_tx(uint32_t bar, uint32_t bytes) { asm volatile("mbarrier.arrive.expect_tx.shared::cta.b64 _, [%0], %1;" ::"r"(bar), "r"(bytes) : "memory"); }
__device__ __forceinline__ void mbar_arrive(uint32_t bar) { asm volatile("mbarrier.arrive.shared::cta.b64 _, [%0];" ::"r"(bar) : "memory"); }
__device__ __forceinline__ void mbar_wait(uint32_t bar, uint32_t parity) {
    asm volatile("{\n.reg .pred P1;\nLAB_WAIT:\nmbarrier.try_wait.parity.shared::cta.b64 P1, [%0], %1;\n@!P1 bra LAB_WAIT;\n}" ::"r"(bar), "r"(parity) : "memory");
}
__device__ __forceinline__ bool mbar_test(uint32_t bar, uint32_t parity) {
    uint32_t ok;
    asm volatile("{\n.reg .pred p;\nmbarrier.test_wait.parity.shared::cta.b64 p, [%1], %2;\nselp.u32 %0, 1, 0, p;\n}" : "=r"(ok) : "r"(bar), "r"(parity) : "memory");
    return ok;
}
__device__ __forceinline__ void tma_2d(uint32_t dst, const CUtensorMap* m, uint32_t bar, int c0, int c1) {
    asm volatile("cp.async.bulk.tensor.2d.shared::cluster.global.mbarrier::complete_tx::bytes [%0], [%1, {%3, %4}], [%2];" ::"r"(dst), "l"(m), "r"(bar), "r"(c0), "r"(c1) : "memory");
}
__device__ __forceinline__ void tma_3d(uint32_t dst, const CUtensorMap* m, uint32_t bar, int c0, int c1, int c2) {
    asm volatile("cp.async.bulk.tensor.3d.shared::cluster.global.mbarrier::complete_tx::bytes [%0], [%1, {%3, %4, %5}], [%2];" ::"r"(dst), "l"(m), "r"(bar), "r"(c0), "r"(c1), "r"(c2) : "memory");
}
__device__ __forceinline__ void tma_4d(uint32_t dst, const CUtensorMap* m, uint32_t bar, int c0, int c1, int c2, int c3) {
    asm volatile("cp.async.bulk.tensor.4d.shared::cluster.global.mbarrier::complete_tx::bytes [%0], [%1, {%3, %4, %5, %6}], [%2];" ::"r"(dst), "l"(m), "r"(bar), "r"(c0), "r"(c1), "r"(c2), "r"(c3) : "memory");
}
__device__ __forceinline__ void tma_store_2d(const CUtensorMap* m, uint32_t src, int c0, int c1) {
    asm volatile("cp.async.bulk.tensor.2d.global.shared::cta.bulk_group [%0, {%2, %3}], [%1];" ::"l"(m), "r"(src), "r"(c0), "r"(c1) : "memory");
}
__device__ __forceinline__ void bulk_g2s(uint32_t dst, const void* src, uint32_t bytes, uint32_t bar) {
    asm volatile("cp.async.bulk.shared::cluster.global.mbarrier::complete_tx::bytes [%0], [%1], %2, [%3];" ::"r"(dst), "l"(src), "r"(bytes), "r"(bar) : "memory");
}
__device__ __forceinline__ void bulk_prefetch(const void* p, uint32_t bytes) { asm volatile("cp.async.bulk.prefetch.L2.global [%0], %1;" ::"l"(p), "r"(bytes) : "memory"); }
__device__ __forceinline__ void fence_async_smem() { asm volatile("fence.proxy.async.shared::cta;" ::: "memory"); }
__device__ __forceinline__ void wg_fence() { asm volatile("wgmma.fence.sync.aligned;" ::: "memory"); }
__device__ __forceinline__ void wg_commit() { asm volatile("wgmma.commit_group.sync.aligned;" ::: "memory"); }
template <int N> __device__ __forceinline__ void wg_wait() { asm volatile("wgmma.wait_group.sync.aligned %0;" ::"n"(N) : "memory"); }
__device__ __forceinline__ uint64_t mkdesc(uint32_t lo, uint32_t hi) { return ((uint64_t)hi << 32) | lo; }
__host__ __device__ constexpr uint32_t dhi(uint32_t sbo, uint32_t mode) { return (sbo >> 4) | (mode << 30); }
__host__ __device__ constexpr uint32_t dlo(uint32_t off, uint32_t lbo) { return (off >> 4) + ((lbo >> 4) << 16); }
__device__ __forceinline__ bool elect_one() {
    uint32_t e;
    asm volatile("{\n.reg .pred p;\nelect.sync _|p, 0xffffffff;\nselp.u32 %0, 1, 0, p;\n}" : "=r"(e));
    return e;
}
template <int R> __device__ __forceinline__ void reg_inc() { asm volatile("setmaxnreg.inc.sync.aligned.u32 %0;" ::"n"(R)); }
template <int R> __device__ __forceinline__ void reg_dec() { asm volatile("setmaxnreg.dec.sync.aligned.u32 %0;" ::"n"(R)); }
__device__ __forceinline__ void bar_sync(int id, int n) { asm volatile("bar.sync %0, %1;" ::"r"(id), "r"(n) : "memory"); }
__device__ __forceinline__ void bar_arrive(int id, int n) { asm volatile("bar.arrive %0, %1;" ::"r"(id), "r"(n) : "memory"); }
__device__ __forceinline__ uint32_t pack_bf16(float lo, float hi) { uint32_t r; asm("cvt.rn.bf16x2.f32 %0, %1, %2;" : "=r"(r) : "f"(hi), "f"(lo)); return r; }
__device__ __forceinline__ float bf_lo(uint32_t u) { return __uint_as_float(u << 16); }
__device__ __forceinline__ float bf_hi(uint32_t u) { return __uint_as_float(u & 0xffff0000u); }
__device__ __forceinline__ float bf16r(float v) { return bf_lo(pack_bf16(v, 0.f)); }
__device__ __forceinline__ uint32_t tagw(uint32_t w, uint32_t m, uint32_t tag) { uint32_t r; asm("lop3.b32 %0, %1, %2, %3, 0xb8;" : "=r"(r) : "r"(w), "r"(m), "r"(tag)); return r; }
__device__ __forceinline__ uint32_t tagf(float f, uint32_t tag) { return tagw(__float_as_uint(f), 1u, tag); }
__device__ __forceinline__ uint32_t movm(uint32_t a) { uint32_t d; asm volatile("movmatrix.sync.aligned.m8n8.trans.b16 %0, %1;" : "=r"(d) : "r"(a)); return d; }
__device__ __forceinline__ void mma16816(float (&c)[4], uint32_t a0, uint32_t a1, uint32_t a2, uint32_t a3, uint32_t b0, uint32_t b1) {
    asm volatile("mma.sync.aligned.m16n8k16.row.col.f32.bf16.bf16.f32 {%0,%1,%2,%3}, {%4,%5,%6,%7}, {%8,%9}, {%0,%1,%2,%3};"
                 : "+f"(c[0]), "+f"(c[1]), "+f"(c[2]), "+f"(c[3]) : "r"(a0), "r"(a1), "r"(a2), "r"(a3), "r"(b0), "r"(b1));
}
__device__ __forceinline__ void mma1688(float (&c)[4], uint32_t a0, uint32_t a1, uint32_t b0) {
    asm volatile("mma.sync.aligned.m16n8k8.row.col.f32.bf16.bf16.f32 {%0,%1,%2,%3}, {%4,%5}, {%6}, {%0,%1,%2,%3};"
                 : "+f"(c[0]), "+f"(c[1]), "+f"(c[2]), "+f"(c[3]) : "r"(a0), "r"(a1), "r"(b0));
}
__device__ __forceinline__ uint32_t ld_rlx(const void* p) { uint32_t v; asm volatile("ld.relaxed.gpu.global.u32 %0, [%1];" : "=r"(v) : "l"(p) : "memory"); return v; }
__device__ __forceinline__ uint2 ld_rlx2(const void* p) { uint2 v; asm volatile("ld.relaxed.gpu.global.v2.u32 {%0,%1}, [%2];" : "=r"(v.x), "=r"(v.y) : "l"(p) : "memory"); return v; }
__device__ __forceinline__ uint4 ld_rlx4(const void* p) { uint4 v; asm volatile("ld.relaxed.gpu.global.v4.u32 {%0,%1,%2,%3}, [%4];" : "=r"(v.x), "=r"(v.y), "=r"(v.z), "=r"(v.w) : "l"(p) : "memory"); return v; }
__device__ __forceinline__ uint32_t ld_acq(const void* p) { uint32_t v; asm volatile("ld.acquire.gpu.global.u32 %0, [%1];" : "=r"(v) : "l"(p) : "memory"); return v; }
__device__ __forceinline__ void st_rlx(void* p, uint32_t v) { asm volatile("st.relaxed.gpu.global.u32 [%0], %1;" ::"l"(p), "r"(v) : "memory"); }
__device__ __forceinline__ void st_rlx2(void* p, uint32_t a, uint32_t b) { asm volatile("st.relaxed.gpu.global.v2.u32 [%0], {%1,%2};" ::"l"(p), "r"(a), "r"(b) : "memory"); }
__device__ __forceinline__ void st_rlx4(void* p, uint32_t a, uint32_t b, uint32_t c, uint32_t d) { asm volatile("st.relaxed.gpu.global.v4.u32 [%0], {%1,%2,%3,%4};" ::"l"(p), "r"(a), "r"(b), "r"(c), "r"(d) : "memory"); }
__device__ __forceinline__ uint4 ldg_nc(const void* p) { uint4 v; asm volatile("ld.global.nc.v4.u32 {%0,%1,%2,%3}, [%4];" : "=r"(v.x), "=r"(v.y), "=r"(v.z), "=r"(v.w) : "l"(p)); return v; }
__device__ __forceinline__ uint32_t mism(uint32_t a, uint32_t b, uint32_t tag) { uint32_t r; asm("lop3.b32 %0, %1, %2, %3, 0x7e;" : "=r"(r) : "r"(a), "r"(b), "r"(tag)); return r; }
__device__ __forceinline__ uint32_t mism(const uint4& v, uint32_t tag) { return mism(v.x, v.y, tag) | mism(v.z, v.w, tag); }
__device__ __forceinline__ void prefetch_l2(const void* p) { asm volatile("prefetch.global.L2 [%0];" ::"l"(p)); }
__device__ __forceinline__ void touch256(uint32_t dst, const void* p) { asm volatile("cp.async.ca.shared.global.L2::256B [%0], [%1], 4;" ::"r"(dst), "l"(p) : "memory"); }
__device__ __forceinline__ void nap(int n) {
#pragma unroll 1
    for (int i = 0; i < n; i++) __nanosleep(100);
}
__device__ __forceinline__ uint32_t now() { uint32_t t; asm volatile("mov.u32 %0, %%globaltimer_lo;" : "=r"(t)); return t; }
__device__ __forceinline__ void until(uint32_t t) {
#pragma unroll 1
    for (int i = 0; i < 256 && (int)(now() - t) < 0; i++) __nanosleep(50);
}
__device__ __forceinline__ uint32_t opaque(uint32_t v) { return __shfl_xor_sync(0xffffffffu, v, 0); }
__device__ __forceinline__ void sts4(uint32_t a, uint32_t x, uint32_t y, uint32_t z, uint32_t w) { asm volatile("st.shared.v4.u32 [%0], {%1,%2,%3,%4};" ::"r"(a), "r"(x), "r"(y), "r"(z), "r"(w) : "memory"); }
__device__ __forceinline__ void sts2(uint32_t a, uint32_t x, uint32_t y) { asm volatile("st.shared.v2.u32 [%0], {%1,%2};" ::"r"(a), "r"(x), "r"(y) : "memory"); }
__device__ __forceinline__ uint4 lds4(uint32_t a) { uint4 v; asm volatile("ld.shared.v4.u32 {%0,%1,%2,%3}, [%4];" : "=r"(v.x), "=r"(v.y), "=r"(v.z), "=r"(v.w) : "r"(a) : "memory"); return v; }
__device__ __forceinline__ float4 lds4f(uint32_t a) { float4 v; asm volatile("ld.shared.v4.f32 {%0,%1,%2,%3}, [%4];" : "=f"(v.x), "=f"(v.y), "=f"(v.z), "=f"(v.w) : "r"(a) : "memory"); return v; }
__device__ __forceinline__ uint2 lds2(uint32_t a) { uint2 v; asm volatile("ld.shared.v2.u32 {%0,%1}, [%2];" : "=r"(v.x), "=r"(v.y) : "r"(a) : "memory"); return v; }
__device__ __forceinline__ float2 lds2f(uint32_t a) { float2 v; asm volatile("ld.shared.v2.f32 {%0,%1}, [%2];" : "=f"(v.x), "=f"(v.y) : "r"(a) : "memory"); return v; }
__device__ __forceinline__ uint32_t lds1(uint32_t a) { uint32_t v; asm volatile("ld.shared.u32 %0, [%1];" : "=r"(v) : "r"(a) : "memory"); return v; }
__device__ __forceinline__ float lds1f(uint32_t a) { return __uint_as_float(lds1(a)); }
__device__ __forceinline__ void sts1(uint32_t a, uint32_t v) { asm volatile("st.shared.u32 [%0], %1;" ::"r"(a), "r"(v) : "memory"); }
__device__ __forceinline__ uint32_t redux_max(uint32_t v) { uint32_t r; asm volatile("redux.sync.max.u32 %0, %1, 0xffffffff;" : "=r"(r) : "r"(v)); return r; }
__device__ __forceinline__ float ex2(float x) { float r; asm("ex2.approx.ftz.f32 %0, %1;" : "=f"(r) : "f"(x)); return r; }
__device__ __forceinline__ float rcp(float x) { float r; asm("rcp.approx.ftz.f32 %0, %1;" : "=f"(r) : "f"(x)); return r; }
__device__ __forceinline__ float sigmoidf(float v) { return rcp(1.f + ex2(v * -1.4426950408889634f)); }

template <int TA, int TB>
__device__ __forceinline__ void wgmma_n192(float (&d)[96], uint64_t da, uint64_t db, int acc = 1) {
    asm volatile("{\n.reg .pred p;\nsetp.ne.b32 p, %100, 0;\n"
        "wgmma.mma_async.sync.aligned.m64n192k16.f32.bf16.bf16 "
        "{%0, %1, %2, %3, %4, %5, %6, %7, %8, %9, %10, %11, %12, %13, %14, %15, "
        "%16, %17, %18, %19, %20, %21, %22, %23, %24, %25, %26, %27, %28, %29, %30, %31, "
        "%32, %33, %34, %35, %36, %37, %38, %39, %40, %41, %42, %43, %44, %45, %46, %47, "
        "%48, %49, %50, %51, %52, %53, %54, %55, %56, %57, %58, %59, %60, %61, %62, %63, "
        "%64, %65, %66, %67, %68, %69, %70, %71, %72, %73, %74, %75, %76, %77, %78, %79, "
        "%80, %81, %82, %83, %84, %85, %86, %87, %88, %89, %90, %91, %92, %93, %94, %95}, "
        "%96, %97, p, 1, 1, %98, %99;\n}\n"
        : "+f"(d[0]), "+f"(d[1]), "+f"(d[2]), "+f"(d[3]), "+f"(d[4]), "+f"(d[5]), "+f"(d[6]), "+f"(d[7]),
          "+f"(d[8]), "+f"(d[9]), "+f"(d[10]), "+f"(d[11]), "+f"(d[12]), "+f"(d[13]), "+f"(d[14]), "+f"(d[15]),
          "+f"(d[16]), "+f"(d[17]), "+f"(d[18]), "+f"(d[19]), "+f"(d[20]), "+f"(d[21]), "+f"(d[22]), "+f"(d[23]),
          "+f"(d[24]), "+f"(d[25]), "+f"(d[26]), "+f"(d[27]), "+f"(d[28]), "+f"(d[29]), "+f"(d[30]), "+f"(d[31]),
          "+f"(d[32]), "+f"(d[33]), "+f"(d[34]), "+f"(d[35]), "+f"(d[36]), "+f"(d[37]), "+f"(d[38]), "+f"(d[39]),
          "+f"(d[40]), "+f"(d[41]), "+f"(d[42]), "+f"(d[43]), "+f"(d[44]), "+f"(d[45]), "+f"(d[46]), "+f"(d[47]),
          "+f"(d[48]), "+f"(d[49]), "+f"(d[50]), "+f"(d[51]), "+f"(d[52]), "+f"(d[53]), "+f"(d[54]), "+f"(d[55]),
          "+f"(d[56]), "+f"(d[57]), "+f"(d[58]), "+f"(d[59]), "+f"(d[60]), "+f"(d[61]), "+f"(d[62]), "+f"(d[63]),
          "+f"(d[64]), "+f"(d[65]), "+f"(d[66]), "+f"(d[67]), "+f"(d[68]), "+f"(d[69]), "+f"(d[70]), "+f"(d[71]),
          "+f"(d[72]), "+f"(d[73]), "+f"(d[74]), "+f"(d[75]), "+f"(d[76]), "+f"(d[77]), "+f"(d[78]), "+f"(d[79]),
          "+f"(d[80]), "+f"(d[81]), "+f"(d[82]), "+f"(d[83]), "+f"(d[84]), "+f"(d[85]), "+f"(d[86]), "+f"(d[87]),
          "+f"(d[88]), "+f"(d[89]), "+f"(d[90]), "+f"(d[91]), "+f"(d[92]), "+f"(d[93]), "+f"(d[94]), "+f"(d[95])
        : "l"(da), "l"(db), "n"(TA), "n"(TB), "r"(acc));
}
template <int TA, int TB>
__device__ __forceinline__ void wgmma_n128(float (&d)[64], uint64_t da, uint64_t db, int acc = 1) {
    asm volatile("{\n.reg .pred p;\nsetp.ne.b32 p, %68, 0;\n"
        "wgmma.mma_async.sync.aligned.m64n128k16.f32.bf16.bf16 "
        "{%0, %1, %2, %3, %4, %5, %6, %7, %8, %9, %10, %11, %12, %13, %14, %15, "
        "%16, %17, %18, %19, %20, %21, %22, %23, %24, %25, %26, %27, %28, %29, %30, %31, "
        "%32, %33, %34, %35, %36, %37, %38, %39, %40, %41, %42, %43, %44, %45, %46, %47, "
        "%48, %49, %50, %51, %52, %53, %54, %55, %56, %57, %58, %59, %60, %61, %62, %63}, "
        "%64, %65, p, 1, 1, %66, %67;\n}\n"
        : "+f"(d[0]), "+f"(d[1]), "+f"(d[2]), "+f"(d[3]), "+f"(d[4]), "+f"(d[5]), "+f"(d[6]), "+f"(d[7]),
          "+f"(d[8]), "+f"(d[9]), "+f"(d[10]), "+f"(d[11]), "+f"(d[12]), "+f"(d[13]), "+f"(d[14]), "+f"(d[15]),
          "+f"(d[16]), "+f"(d[17]), "+f"(d[18]), "+f"(d[19]), "+f"(d[20]), "+f"(d[21]), "+f"(d[22]), "+f"(d[23]),
          "+f"(d[24]), "+f"(d[25]), "+f"(d[26]), "+f"(d[27]), "+f"(d[28]), "+f"(d[29]), "+f"(d[30]), "+f"(d[31]),
          "+f"(d[32]), "+f"(d[33]), "+f"(d[34]), "+f"(d[35]), "+f"(d[36]), "+f"(d[37]), "+f"(d[38]), "+f"(d[39]),
          "+f"(d[40]), "+f"(d[41]), "+f"(d[42]), "+f"(d[43]), "+f"(d[44]), "+f"(d[45]), "+f"(d[46]), "+f"(d[47]),
          "+f"(d[48]), "+f"(d[49]), "+f"(d[50]), "+f"(d[51]), "+f"(d[52]), "+f"(d[53]), "+f"(d[54]), "+f"(d[55]),
          "+f"(d[56]), "+f"(d[57]), "+f"(d[58]), "+f"(d[59]), "+f"(d[60]), "+f"(d[61]), "+f"(d[62]), "+f"(d[63])
        : "l"(da), "l"(db), "n"(TA), "n"(TB), "r"(acc));
}
template <int TB>
__device__ __forceinline__ void wgmma_rs_n128(float (&d)[64], uint32_t a0, uint32_t a1, uint32_t a2, uint32_t a3, uint64_t db) {
    asm volatile("{\n.reg .pred p;\nsetp.ne.b32 p, 1, 0;\n"
        "wgmma.mma_async.sync.aligned.m64n128k16.f32.bf16.bf16 "
        "{%0, %1, %2, %3, %4, %5, %6, %7, %8, %9, %10, %11, %12, %13, %14, %15, "
        "%16, %17, %18, %19, %20, %21, %22, %23, %24, %25, %26, %27, %28, %29, %30, %31, "
        "%32, %33, %34, %35, %36, %37, %38, %39, %40, %41, %42, %43, %44, %45, %46, %47, "
        "%48, %49, %50, %51, %52, %53, %54, %55, %56, %57, %58, %59, %60, %61, %62, %63}, "
        "{%64, %65, %66, %67}, %68, p, 1, 1, %69;\n}\n"
        : "+f"(d[0]), "+f"(d[1]), "+f"(d[2]), "+f"(d[3]), "+f"(d[4]), "+f"(d[5]), "+f"(d[6]), "+f"(d[7]),
          "+f"(d[8]), "+f"(d[9]), "+f"(d[10]), "+f"(d[11]), "+f"(d[12]), "+f"(d[13]), "+f"(d[14]), "+f"(d[15]),
          "+f"(d[16]), "+f"(d[17]), "+f"(d[18]), "+f"(d[19]), "+f"(d[20]), "+f"(d[21]), "+f"(d[22]), "+f"(d[23]),
          "+f"(d[24]), "+f"(d[25]), "+f"(d[26]), "+f"(d[27]), "+f"(d[28]), "+f"(d[29]), "+f"(d[30]), "+f"(d[31]),
          "+f"(d[32]), "+f"(d[33]), "+f"(d[34]), "+f"(d[35]), "+f"(d[36]), "+f"(d[37]), "+f"(d[38]), "+f"(d[39]),
          "+f"(d[40]), "+f"(d[41]), "+f"(d[42]), "+f"(d[43]), "+f"(d[44]), "+f"(d[45]), "+f"(d[46]), "+f"(d[47]),
          "+f"(d[48]), "+f"(d[49]), "+f"(d[50]), "+f"(d[51]), "+f"(d[52]), "+f"(d[53]), "+f"(d[54]), "+f"(d[55]),
          "+f"(d[56]), "+f"(d[57]), "+f"(d[58]), "+f"(d[59]), "+f"(d[60]), "+f"(d[61]), "+f"(d[62]), "+f"(d[63])
        : "r"(a0), "r"(a1), "r"(a2), "r"(a3), "l"(db), "n"(TB));
}
template <int TA, int TB>
__device__ __forceinline__ void wgmma_n8(float (&d)[4], uint64_t da, uint64_t db, int acc = 1) {
    asm volatile("{\n.reg .pred p;\nsetp.ne.b32 p, %8, 0;\n"
        "wgmma.mma_async.sync.aligned.m64n8k16.f32.bf16.bf16 "
        "{%0, %1, %2, %3}, "
        "%4, %5, p, 1, 1, %6, %7;\n}\n"
        : "+f"(d[0]), "+f"(d[1]), "+f"(d[2]), "+f"(d[3])
        : "l"(da), "l"(db), "n"(TA), "n"(TB), "r"(acc));
}

__device__ __forceinline__ uint32_t norm_pair(uint32_t u, float m, float rinv) {
    uint32_t d = pack_bf16(bf_lo(u) - m, bf_hi(u) - m);
    return pack_bf16(bf_lo(d) * rinv, bf_hi(d) * rinv);
}

__global__ void __launch_bounds__(512, 1)
fused_kernel(int by_sm, const __nv_bfloat16* __restrict__ x, const __nv_bfloat16* __restrict__ wqkv, const __nv_bfloat16* __restrict__ wr,
             Scratch* const S, const char* __restrict__ wg, const char* __restrict__ wu, const char* __restrict__ wd, const char* __restrict__ wo,
             const __grid_constant__ CUtensorMap mw, const __grid_constant__ CUtensorMap mx, const __grid_constant__ CUtensorMap mwo,
             const __grid_constant__ CUtensorMap mxs, const __grid_constant__ CUtensorMap mout, const __grid_constant__ CUtensorMap mgu, const __grid_constant__ CUtensorMap mwd) {
    extern __shared__ __align__(1024) uint8_t smem[];
    constexpr uint32_t sb = 1024, bars = sb + OFF_BAR, sd = sb >> 4;
    const int tid = threadIdx.x, lane = tid & 31, warp = __shfl_sync(0xffffffffu, tid >> 5, 0);
    uint32_t smid;
    asm("mov.u32 %0, %%smid;" : "=r"(smid));
    const int T = smid >> 1, T8 = T < 32 ? T : T + 1 + (((T - 32) * 37) >> 8), pr = T < 60 ? (~T8 & 7) * 8 + (T8 >> 3) : T < 62 ? T + 4 : T - 2;
    const int b = by_sm ? pr * 2 + (smid & 1) : blockIdx.x;
    const int mt = b >> 4, nt = b & 15, hp = b & 1, cb = nt >> 1;
    const int par = mt >> 2, j0 = (mt & 3) * 256;
    uint8_t* const g_o = S->o;

    TSC(TIMING == 5 && tid == 0, 32);
    if (b >= 128) {
        if (b > 128) { nap(16); TS_END(); return; }
        const uint32_t tag = (ld_rlx(&S->epoch) & 1) - 1;
        if (tid < 8) st_rlx2(&S->sel[tid], ~tag, ~tag);
        uint4 ra, rb;
#pragma unroll 1
        for (int it = 0; it < SPIN_LIMIT; it++) {
            ra = ld_rlx4(&S->rec[tid * 2]); rb = ld_rlx4(&S->rec[1024 + tid * 2]);
            if (!((mism(ra.x, ra.z, tag) | mism(rb.x, rb.z, tag)) & 0x8000u)) break;
        }
        __syncwarp();
        TSC(tid == 0, 31);
        TSC(TIMING == 7 && lane == 0, 32 + warp);
        sts4(sb + 1024 + tid * 16, ra.y, rb.y, ra.w, rb.w);
        uint4 k = make_uint4(ra.x, ra.z, rb.x, rb.z);
        uint32_t cand;
#pragma unroll 1
        for (int pass = 0; pass < 2; pass++) {
            const uint32_t a0 = max(k.x, k.y), a1 = min(k.x, k.y), a2 = max(k.z, k.w), a3 = min(k.z, k.w), c1 = min(a0, a2), c2 = max(a1, a3);
            k = make_uint4(max(a0, a2), max(c1, c2), min(c1, c2), min(a1, a3));
#pragma unroll
            for (int r = 0; r < 8; r++) {
                const uint32_t m = redux_max(k.x);
                if (lane == r) cand = m;
                if (k.x == m) k = make_uint4(k.y, k.z, k.w, 0);
            }
            if (pass) break;
            if (lane < 8) sts1(sb + (warp * 8 + lane) * 4, cand);
            __syncthreads();
            if (warp) { TS_END(); return; }
            k = lds4(sb + lane * 16);
            TSC(TIMING == 7 && tid == 0 && k.x != 0x12345, 49);
        }
        if (lane < 8) st_rlx2(&S->sel[lane], cand, lds1(sb + 1024 + (~cand & 0x7ffu) * 4));
        TSC(tid == 0, 20);
        TS_END();
        return;
    }
    auto kblock = [&](int p) { return p < 14 ? (p < 2 * cb ? p : p + 2) : 2 * cb + p - 14; };
    auto load_stage = [&](int p, uint32_t so, int bi, int lag) {
        const int kc0 = kblock(p) * 64;
        const uint32_t fa = bars + 8 * (B_FULLA + bi), fb = bars + 8 * (B_FULLB + bi);
        mbar_expect_tx(fa, 40960);
        if (lag < 0) tma_3d(sb + so + 16384, &mw, fa, nt * 64, kc0, 0);
        tma_4d(sb + so + (hp ? 0 : 40960), &mx, fa, par * 1024 + kc0, 0, (j0 >> 5) + 4, 0);
        mbar_expect_tx(fb, 16384);
        tma_4d(sb + so + (hp ? 40960 : 0), &mx, fb, par * 1024 + kc0, 0, j0 >> 5, 0);
        if (lag >= 0) { nap(lag); tma_3d(sb + so + 16384, &mw, fa, nt * 64, kc0, 0); }
    };
    auto prefetch_w = [&](int part, int p0) { prefetch_l2(wqkv + (size_t)(kblock(p0 + (lane >> 3)) * 64 + mt * 8 + (lane & 7)) * 3072 + part * 1024 + nt * 64); };
    auto prefetch_x = [&](int c) { prefetch_l2(x + (size_t)((j0 + nt * 16 + (lane >> 1)) * 2 + par) * 1024 + c * 128 + (lane & 1) * 64); };
    if (warp == 12) {
        if (elect_one()) {
#pragma unroll
            for (int i = 0; i < B_ROW; i++) mbar_init(bars + 8 * i, 1);
            asm volatile("fence.mbarrier_init.release.cluster;" ::: "memory");
            TSC(TIMING == 5, 33);
            load_stage(0, STAGE, 0, -1);
            TSC(TIMING == 5, 34);
        }
    } else {
        if (warp > 12) {
            if (lane < 8) prefetch_w(warp - 13, 0);
        } else if (warp >= 10) prefetch_x(warp - 10);
        if (warp == 0 && elect_one()) {
#pragma unroll
            for (int i = B_ROW; i < B_WOFULL; i++) mbar_init(bars + 8 * i, i >= B_FFULL && i < B_FEMPTY ? 5 : 1);
            mbar_expect_tx(bars + 8 * (B_ROW + 4), 2048);
            bulk_g2s(sb + OFF_FA, wr, 2048, bars + 8 * (B_ROW + 4));
        }
        if (warp == 1 && elect_one()) {
#pragma unroll
            for (int i = B_EMPTY; i < NBAR; i++) mbar_init(bars + 8 * i, i < B_UPD ? 2 : i < B_AUX ? 4 : i == B_AUX ? 7 : i == B_CSDONE ? 3 : 8);
        }
    }
    TSC(TIMING == 5 && lane == 0, 40 + warp);
    __syncthreads();
    TSC(TIMING >= 4 && tid == 0, 35);
    if (warp == 12 && elect_one()) {
#pragma unroll 1
        for (int p = 1; p < 3; p++) { nap(N_S1); load_stage(p, p == 2 ? 0 : 2 * STAGE, p, -1); }
    }

    if (warp >= 12) {
        reg_dec<24>();
        if (warp > 12) {
            const int p = warp - 13;
            const uint32_t t0 = now();
#pragma unroll 1
            for (int i = 0; i < 4; i++) {
                until(t0 + (p == 0 ? T_X + i * D_X : p == 1 ? T_W + i * D_W : T_ROW + i * D_R));
                if (p == 0) { if (i < 3) { prefetch_x(2 + 2 * i); prefetch_x(3 + 2 * i); } }
                else if (p == 1) {
#pragma unroll 1
                    for (int c = 0; c < 3; c++) prefetch_w(c, min(3 + i * 4, 12));
                } else if (elect_one()) {
                    mbar_expect_tx(bars + 8 * (B_ROW + i), 8192);
                    tma_3d(sb + OFF_FW + i * 8192, &mxs, bars + 8 * (B_ROW + i), 0, j0 + nt * 16, par * 16 + i * 4);
                }
            }
            until(t0 + T_CS);
            const char* wp = (const char*)(wqkv + (size_t)(mt * 8 + (lane >> 3)) * 3072 + p * 1024 + nt * 64 + (lane & 7) * 8);
            const uint32_t stg = sb + OFF_FW + 32768 + p * 4096 + lane * 16;
            float c[8];
#pragma unroll
            for (int i = 0; i < 8; i++) c[i] = 0.f;
#pragma unroll 1
            for (int n = 0; n < 10; n++) {
                const uint32_t buf = stg + (n & 1) * 2048;
                if (n >= 2) {
                    asm volatile("cp.async.wait_group 1;" ::: "memory");
#pragma unroll 2
                    for (int i = 0; i < 4; i++) {
                        const uint4 v = lds4(buf + i * 512);
                        c[0] += bf_lo(v.x); c[1] += bf_hi(v.x); c[2] += bf_lo(v.y); c[3] += bf_hi(v.y);
                        c[4] += bf_lo(v.z); c[5] += bf_hi(v.z); c[6] += bf_lo(v.w); c[7] += bf_hi(v.w);
                    }
                }
                if (n < 8) {
                    const char* src = wp + (size_t)kblock(2 * n) * 64 * 6144;
#pragma unroll
                    for (int i = 0; i < 4; i++) asm volatile("cp.async.ca.shared.global [%0], [%1], 16;" ::"r"(buf + i * 512), "l"(src + ((i >> 1) * 64 + (i & 1) * 4) * 6144) : "memory");
                }
                asm volatile("cp.async.commit_group;" ::: "memory");
            }
            sts4(stg + lane * 16, __float_as_uint(c[0]), __float_as_uint(c[1]), __float_as_uint(c[2]), __float_as_uint(c[3]));
            sts4(stg + lane * 16 + 16, __float_as_uint(c[4]), __float_as_uint(c[5]), __float_as_uint(c[6]), __float_as_uint(c[7]));
            bar_sync(13, 128);
            const uint32_t tag = lds1(sb + OFF_TAG);
            float* gcs = &S->cs[0][p * 1024 + nt * 64];
            {
                const float2 a0 = lds2f(stg - lane * 8), a1 = lds2f(stg - lane * 8 + 256), a2 = lds2f(stg - lane * 8 + 512), a3 = lds2f(stg - lane * 8 + 768);
                st_rlx2(gcs + mt * 3072 + lane * 2, tagf((a0.x + a1.x) + (a2.x + a3.x), tag), __float_as_uint((a0.y + a1.y) + (a2.y + a3.y)));
            }
            __syncwarp();
            if (lane == 0) mbar_arrive(bars + 8 * B_CSDONE);
            TSC(warp == 13 && lane == 0, 19);
            {
                uint4 v[4];
                const float* src = gcs + (lane >> 4) * 4 * 3072 + (lane & 15) * 4;
#pragma unroll 1
                for (int it = 0; it < SPIN_LIMIT; it++) {
#pragma unroll
                    for (int m = 0; m < 4; m++) v[m] = ld_rlx4(src + m * 3072);
                    if (!((mism(v[0].x, v[1].x, tag) | mism(v[2].x, v[3].x, tag)) & 1)) break;
                }
                __syncwarp();
#pragma unroll
                for (int c = 0; c < 4; c++) {
                    const float a = (__uint_as_float((&v[0].x)[c]) + __uint_as_float((&v[1].x)[c])) + (__uint_as_float((&v[2].x)[c]) + __uint_as_float((&v[3].x)[c]));
                    (&v[0].x)[c] = __float_as_uint(a + __shfl_xor_sync(0xffffffffu, a, 16));
                }
                const uint32_t ca = sb + OFF_CS + p * 384 + ((lane & 15) >> 1) * 48 + (lane & 1) * 8;
#pragma unroll 1
                for (int r = 0; r < 3; r++) {
                    const uint32_t u0 = pack_bf16(__uint_as_float(v[0].x), __uint_as_float(v[0].y)), u1 = pack_bf16(__uint_as_float(v[0].z), __uint_as_float(v[0].w));
                    sts2(ca + r * 16, u0, u1);
                    v[0].x = __float_as_uint(__uint_as_float(v[0].x) - bf_lo(u0)); v[0].y = __float_as_uint(__uint_as_float(v[0].y) - bf_hi(u0));
                    v[0].z = __float_as_uint(__uint_as_float(v[0].z) - bf_lo(u1)); v[0].w = __float_as_uint(__uint_as_float(v[0].w) - bf_hi(u1));
                }
                if (lane < 20) sts1(sb + OFF_CS + 1152 + lane * 4, 0);
                fence_async_smem();
            }
            __syncwarp();
            if (lane == 0) mbar_arrive(bars + 8 * B_AUX);
            TSC(warp == 13 && lane == 0, 21);
            if (p == 0) {
                uint32_t* hdst = &S->halo[b][lane * 4];
#pragma unroll 1
                for (int c = 0; c < 4; c++) st_rlx4(hdst + c * 128, ~tag, ~tag, ~tag, ~tag);
                bar_sync(11, 64);
#pragma unroll
                for (int c = 0; c < 4; c++) {
                    const uint4 v = lds4(sb + OFF_HALO + 16384 + c * 512 + lane * 16);
                    st_rlx4(hdst + c * 128, tagw(v.x, 1u, tag), v.y, v.z, v.w);
                }
            } else {
                if (p == 1) {
                    uint4 v[4];
#pragma unroll
                    for (int c = 0; c < 4; c++) v[c] = make_uint4(0, 0, 0, 0);
                    mbar_wait(bars + 8 * B_PART, 0);
#pragma unroll 1
                    for (int it = 0; it < SPIN_LIMIT && j0; it++) {
#pragma unroll
                        for (int c = 0; c < 4; c++) v[c] = ld_rlx4(&S->halo[b - 16][c * 128 + lane * 4]);
                        if (!((mism(v[0].x, v[1].x, tag) | mism(v[2].x, v[3].x, tag)) & 1)) break;
                    }
#pragma unroll
                    for (int c = 0; c < 4; c++) sts4(sb + OFF_HALO + c * 512 + lane * 16, v[c].x, v[c].y, v[c].z, v[c].w);
                    __syncwarp();
                    bar_arrive(3, 64);
                }
                const int w = p - 1;
                const uint8_t* osrc = g_o + (size_t)((mt * 2 + hp) * 2 + w) * 131072;
                mbar_wait(bars + 8 * (w ? B_ATT : B_G1DONE), 0);
#pragma unroll 1
                for (int it = 0; it < SPIN_LIMIT; it++)
                    if (!__any_sync(0xffffffffu, (ld_rlx(osrc + lane * 512 + 96 + (lane & 6) * 4) ^ tag) & 1)) break;
                TSC(lane == 0, 28 + w);
                if (elect_one()) {
#pragma unroll 1
                    for (int st = 0; st < 16; st++) {
                        const uint32_t full = bars + 8 * (B_OFULL + 16 * w + st);
                        if (st >= 4) mbar_wait(full + 8 * (B_DONE - B_OFULL - 4), 0);
                        mbar_expect_tx(full, 8192);
                        bulk_g2s(sb + (w ? OFF_O1 : OFF_O0) + (st & 3) * 8192, osrc + st * 8192, 8192, full);
                    }
                }
            }
            TS_END();
            return;
        }
        if (elect_one()) {
            auto load_wo = [&](int s, int ws) {
                mbar_expect_tx(bars + 8 * (B_WOFULL + s), 16384);
                tma_4d(sb + OFF_WO + ws * 16384, &mwo, bars + 8 * (B_WOFULL + s), 0, (s >> 1) * 8, (s & 1) * 8, cb * 2);
            };
            uint32_t so = STAGE, ph = 0;
            int bi = 0;
            if (smem_u32(smem) != sb) __trap();
#pragma unroll 1
            for (int i = B_WOFULL; i < B_OFULL; i++) mbar_init(bars + 8 * i, 1);
            const char* pf = (b < 64 ? wg : wu) + (b & 63) * 7168;
            int q = 0;
#pragma unroll 1
            for (int p = 3; p < 16; p++) {
                mbar_wait(bars + 8 * (B_EMPTY + bi), ph);
                load_stage(p, so, bi, W_LAG);
#pragma unroll 1
                for (; q < ((p - PF_START + 1) * 26 + 15 - PF_START) / (16 - PF_START); q++) {
                    if (q == 16) pf = wd + b * 7168;
                    if (q == 24) pf = wo + b * 8192;
                    const uint32_t n = q >= 24 ? 8192 : 7168;
                    bulk_prefetch(pf, n); nap(N_PF);
                    pf += q < 16 ? 64 * 7168 : 128 * n;
                }
                so = so == 2 * STAGE ? 0 : so + STAGE;
                if (++bi == 3) { bi = 0; ph ^= 1; }
            }
            TS(27);
            int ws = 1;
#pragma unroll 1
            for (int i = 0; i < 16; i++) {
                const int s = i < 3 ? i + 1 : i == 3 ? 0 : i;
                if (i == 3) {
                    mbar_wait(bars + 8 * (B_EMPTY + 2), 0);
                    mbar_expect_tx(bars + 8 * B_F2FULL, 8192);
                    tma_2d(sb + OFF_F2X, &mwd, bars + 8 * B_F2FULL, nt * 64, mt * 448);
                }
                mbar_wait(bars + 8 * (i < 3 ? B_EMPTY + 1 : i == 3 ? B_G1DONE : i < NWO ? B_F2DONE : B_DONE - NWO + i), 0);
                if (i >= NWO) mbar_wait(bars + 8 * (B_DONE + 16 - NWO + i), 0);
                load_wo(s, i == 3 ? 0 : ws);
                if (i != 3 && ++ws == NWO) ws = 0;
            }
        }
        TS_END();
    } else if (warp >= 8) {
        reg_dec<40>();
        const int p = warp - 8;
        const bool f1 = b < 112;
        auto ffn_w = [&](int n, int s) {
            const uint32_t dst = sb + OFF_FW + s * 16384;
            if (n < 8) {
                mbar_expect_tx(bars + 8 * (B_FFULL + s), 16384);
                tma_3d(dst, &mgu, bars + 8 * (B_FFULL + s), b * 32, n * 128, 0);
            } else {
                mbar_expect_tx(bars + 8 * B_F2FULL, 16384);
                tma_2d(dst, &mwd, bars + 8 * B_F2FULL, nt * 64, mt * 448 + 64 + s * 128);
                tma_2d(dst + 8192, &mwd, bars + 8 * B_F2FULL, nt * 64, mt * 448 + 128 + s * 128);
            }
        };
        const uint32_t epoch = __shfl_sync(0xffffffffu, ld_rlx(&S->epoch), 0), tag = (epoch & 1) - 1;
        float s1 = 0.f, s2 = 0.f, sr = 0.f, sw = 0.f, sh = 0.f;
        {
            const uint32_t xa = sb + OFF_FW + p * 512 + lane * 16, wa = sb + OFF_FA + (((p * 4 + (lane >> 3)) ^ lane) & 7) * 16;
            mbar_wait(bars + 8 * (B_ROW + 4), 0);
#pragma unroll 1
            for (int i = 0; i < 4; i++) {
                const uint4 q = lds4(sb + OFF_FA + i * 512 + lane * 16);
                sw += ((bf_lo(q.x) + bf_hi(q.x)) + (bf_lo(q.y) + bf_hi(q.y))) + ((bf_lo(q.z) + bf_hi(q.z)) + (bf_lo(q.w) + bf_hi(q.w)));
            }
#pragma unroll 1
            for (int o = 1; o < 32; o <<= 1) sw += __shfl_xor_sync(0xffffffffu, sw, o);
            {
                float c1 = 0.f, c2 = 0.f, cr = 0.f;
#pragma unroll 1
                for (int q = 0; q < 4; q++) {
                mbar_wait(bars + 8 * (B_ROW + q), 0);
                TSC(tid == 256 && q == 3, 17);
                TSC(TIMING == 4 && tid == 256, 36 + q);
#pragma unroll
                for (int i = 0; i < 4; i++) {
                    const uint4 u = lds4(xa + q * 8192 + i * 2048), w4 = lds4(wa + q * 512 + i * 128);
                    const float a0 = bf_lo(u.x), a1 = bf_hi(u.x), a2 = bf_lo(u.y), a3 = bf_hi(u.y), a4 = bf_lo(u.z), a5 = bf_hi(u.z), a6 = bf_lo(u.w), a7 = bf_hi(u.w);
                    s1 += a0 + a1; c1 += a4 + a5; s1 += a2 + a3; c1 += a6 + a7;
                    s2 = fmaf(a0, a0, s2); c2 = fmaf(a4, a4, c2); sr = fmaf(a0, bf_lo(w4.x), sr); cr = fmaf(a4, bf_lo(w4.z), cr);
                    s2 = fmaf(a1, a1, s2); c2 = fmaf(a5, a5, c2); sr = fmaf(a1, bf_hi(w4.x), sr); cr = fmaf(a5, bf_hi(w4.z), cr);
                    s2 = fmaf(a2, a2, s2); c2 = fmaf(a6, a6, c2); sr = fmaf(a2, bf_lo(w4.y), sr); cr = fmaf(a6, bf_lo(w4.w), cr);
                    s2 = fmaf(a3, a3, s2); c2 = fmaf(a7, a7, c2); sr = fmaf(a3, bf_hi(w4.y), sr); cr = fmaf(a7, bf_hi(w4.w), cr);
                }
                }
                s1 += c1; s2 += c2; sr += cr;
                TSC(TIMING == 4 && lane == 0 && s1 + s2 + sr != 123.456f, 40 + p);
            }
#pragma unroll 1
            for (int pass = 0;; pass++) {
#pragma unroll
                for (int o = 1; o < 8; o <<= 1) {
                    s1 += __shfl_xor_sync(0xffffffffu, s1, o); s2 += __shfl_xor_sync(0xffffffffu, s2, o); sr += __shfl_xor_sync(0xffffffffu, sr, o);
                }
                s1 *= 1.f / 1024.f;
                s2 = fmaf(-s1, s1, s2 * (1.f / 1024.f));
                if (!__any_sync(0xffffffffu, !pass && s1 * s1 > 256.f * s2)) break;
                sh = bf16r(s1); s1 = 0.f; s2 = 0.f; sr = 0.f;
#pragma unroll 1
                for (uint32_t o = 0; o < 2048; o = opaque(o + ((o & 12) == 12 ? 116 : 4))) {
                    const uint32_t u = lds1(xa + (o >> 7) * 2048 + (o & 12)), q = lds1(wa + o);
                    const float a0 = bf_lo(u) - sh, a1 = bf_hi(u) - sh;
                    s1 += a0 + a1; s2 = fmaf(a0, a0, fmaf(a1, a1, s2)); sr = fmaf(a0, bf_lo(q), fmaf(a1, bf_hi(q), sr));
                }
            }
        }
        const int ta = opaque(tid) - 256, lane = ta & 31, g = lane >> 2, t = lane & 3;
        {
            if ((lane & 7) == 0) {
                const int s = b * 16 + p * 4 + (lane >> 3);
                const float mb = bf16r(sh + s1);
                float den;
                asm("sqrt.approx.f32 %0, %1;" : "=f"(den) : "f"(bf16r(bf16r(s2) + 1e-5f)));
                den = bf16r(den);
                uint32_t rb = pack_bf16(fmaf(sh - mb, sw, sr) * rcp(den), 0.f);
                if (rb == 0x8000u) rb = 0;
                uint32_t ord = (rb & 0x8000u) ? (~rb & 0xffffu) : (rb | 0x8000u);
                if ((rb & 0x7fffu) > 0x7f80u) ord = 0;
                st_rlx2(&S->rec[s], (ord << 16) | (tag & 0x8000u) | (0x47ffu - (s & 1023) * 2 - par), pack_bf16(mb, den));
            }
            TSC(TIMING == 4 && lane == 0, 44 + p);
            TSC(TIMING == 7 && lane == 0, 52 + p);
            if (ta < 48) st_rlx4(&S->cs[mt][(ta >> 4) * 1024 + nt * 64 + (ta & 15) * 4], ~tag, ~tag, ~tag, ~tag);
            if (elect_one()) {
#pragma unroll 1
                for (int i = B_OFULL + p; i < B_EMPTY; i += 4) mbar_init(bars + 8 * i, 1);
            }
            bar_sync(12, 128);
            if (p == 1) sts1(sb + OFF_ROWMAP + lane * 4, 0xffffffffu);
            if (p == 0) {
                if (lane == 0) {
                    sts1(sb + OFF_TAG, tag);
                    if (f1 && EARLY_FILL > 0) ffn_w(0, 0);
                }
                __syncwarp();
                bar_arrive(13, 128);
            }
            TSC(ta == 0, 18);
        }
        {
            uint2 r[3];
            const uint2* src = &S->rec[mt * 256 + ta];
            const int l2 = ta < 8 && j0 ? -8 : 0;
#pragma unroll 1
            for (int it = 0; it < SPIN_LIMIT; it++) {
                r[0] = ld_rlx2(src + l2); r[1] = ld_rlx2(src); r[2] = ld_rlx2(src + 128);
                if (!((mism(r[0].x, r[1].x, tag) | (r[2].x ^ tag)) & 0x8000u)) break;
            }
#pragma unroll
            for (int n = 0; n < 3; n++)
                if (n || ta < 8) sts2(sb + OFF_STAT + (n ? n * 1024 - 960 : 0) + ta * 8, (r[n].y << 16) ^ 0x80000000u, __float_as_uint(rcp(bf_hi(r[n].y))));
        }
        __syncwarp();
        if (lane == 0) mbar_arrive(bars + 8 * B_AUX);
        TSC(ta == 0, 30);
        if (EARLY_FILL > 1 && f1 && p == 0 && elect_one()) ffn_w(1, 1);
        uint2 sel;
#pragma unroll 1
        for (int it = 0; it < SPIN_LIMIT; it++) {
            sel = ld_rlx2(&S->sel[lane & 7]);
            if (!__any_sync(0xffffffffu, (sel.x ^ tag) & 0x8000u)) break;
            __nanosleep(POLL_NS);
        }
        TSC(ta == 0, 26);
        if (b == 0 && ta == 0) st_rlx(&S->epoch, epoch + 1);
        {
            const __nv_bfloat16* xp = x + (~sel.x & 0x7ffu) * 1024 + (ta >> 3) * 8;
            const float mb = bf_lo(sel.y), rinv = rcp(bf_hi(sel.y));
            uint4 v = ldg_nc(xp);
            int s = f1 ? 0 : 2;
#pragma unroll 1
            for (int n = f1 ? 0 : 8; n < (p ? 8 : 11); n++) {
                mbar_wait(bars + 8 * (f1 ? B_FEMPTY + s : B_PART), f1 && (n < 3 || (n >= 6 && n < 9)));
                if (p == 0 && s == 2) mbar_wait(bars + 8 * B_CSDONE, 0);
                if (p == 0 && n >= EARLY_FILL && elect_one()) ffn_w(n, s);
                if (n < 8) {
                    sts4(sb + OFF_FA + s * 2048 + ta * 16, norm_pair(v.x, mb, rinv), norm_pair(v.y, mb, rinv), norm_pair(v.z, mb, rinv), norm_pair(v.w, mb, rinv));
                    fence_async_smem();
                    __syncwarp();
                    if (lane == 0) mbar_arrive(bars + 8 * (B_FFULL + s));
                    v = ldg_nc(xp + ((n + 1) & 7) * 128);
                }
                if (++s == 3) s = 0;
            }
        }
        mbar_wait(bars + 8 * B_PART, 0);
        if (f1 && p >= 2) {
            const uint32_t pa = sb + OFF_FA + (ta - 64) * 16, go = wu < wg ? 1024 : 0;
            const float4 g0 = lds4f(pa + go), g1 = lds4f(pa + 2048 + go), u0 = lds4f(pa + (go ^ 1024)), u1 = lds4f(pa + 2048 + (go ^ 1024));
            float hv[4];
#pragma unroll
            for (int c = 0; c < 4; c++) {
                const float ga = bf16r((&g0.x)[c] + (&g1.x)[c]), up = bf16r((&u0.x)[c] + (&u1.x)[c]);
                hv[c] = bf16r(ga * sigmoidf(ga)) * up;
            }
#pragma unroll
            for (int hh = 0; hh < 2; hh++) {
                const float o = __shfl_xor_sync(0xffffffffu, (g & 1) ? hv[2 * hh] : hv[2 * hh + 1], 4);
                st_rlx(&S->h[(b * 4 + (p & 1) * 2 + hh) * 32 + (2 * t + (g & 1)) * 4 + (g >> 1)],
                       tagw((g & 1) ? pack_bf16(o, hv[2 * hh + 1]) : pack_bf16(hv[2 * hh], o), g < 2, tag));
            }
            TSC(ta == 64, 22);
        }
        {
            uint4 hq[4];
            const uint32_t* hp4 = S->h + mt * 1792 + ta * 4;
#pragma unroll 1
            for (int it = 0; it < SPIN_LIMIT; it++) {
#pragma unroll
                for (int n = 0; n < 4; n++) hq[n] = ld_rlx4(hp4 + (n < 3 ? n * 512 : p < 2 ? 1536 : 0));
                if (!((mism(hq[0].x, hq[1].x, tag) | mism(hq[2].x, hq[3].x, tag)) & 1)) break;
            }
            mbar_wait(bars + 8 * B_G1DONE, 0);
            bar_sync(12, 128);
#pragma unroll
            for (int n = 0; n < 4; n++) sts4(sb + OFF_FA + ta * 16 + (n < 3 ? n * 2048 : p < 2 ? 6144 : 0), hq[n].x, hq[n].y, hq[n].z, hq[n].w);
            fence_async_smem();
            bar_sync(12, 128);
            TSC(ta == 0, 25);
            mbar_wait(bars + 8 * B_F2FULL, 0);
            mbar_wait(bars + 8 * B_ATT, 0);
            float acc[4] = {0.f, 0.f, 0.f, 0.f};
            uint32_t da = sd + dlo(OFF_F2X, 8192), db = sd + dlo(OFF_FA, 128);
#pragma unroll 1
            for (int q = 0; q < 7; q++) {
                wg_fence();
#pragma unroll
                for (int j = 0; j < 4; j++) wgmma_n8<1, 0>(acc, mkdesc(da + j * 128, dhi(1024, 1)), mkdesc(db + j * 16, dhi(128, 0)));
                wg_commit();
                da = sd + dlo(OFF_FW, 8192) + q * 512; db += 64;
            }
            wg_wait<0>();
            if (ta == 0) mbar_arrive(bars + 8 * B_F2DONE);
#pragma unroll
            for (int c = 0; c < 4; c++) st_rlx(&S->ypart[mt][2 * t + (c & 1)][nt * 64 + p * 16 + (c >> 1) * 8 + g], tagf(acc[c], tag));
            TSC(ta == 0, 23);
            bar_sync(12, 128);
        }
#pragma unroll 1
        for (int j = 2 * p; j < 2 * p + 2; j++) {
            const uint32_t kj = __shfl_sync(0xffffffffu, sel.x, j);
            const int row = 0x7ff - (kj & 0x7ffu), jj = (row >> 1) - j0 - hp * 128;
            float a0 = 0.f, a1 = 0.f, a2 = 0.f, a3 = 0.f, sig = 0.f;
            if ((row & 1) == par && jj >= 0 && jj < 128) {
                sig = bf16r(sigmoidf(__uint_as_float(((int)kj < 0 ? kj ^ 0x80000000u : ~kj) & 0xffff0000u)));
#pragma unroll 1
                for (int hh = 0; hh < 8; hh += 4) {
                    uint4 v[4];
#pragma unroll 1
                    for (int it = 0; it < SPIN_LIMIT; it++) {
#pragma unroll
                        for (int m = 0; m < 4; m++) v[m] = ld_rlx4(&S->ypart[hh + m][j][cb * 128 + lane * 4]);
                        if (!((mism(v[0], tag) | mism(v[1], tag) | mism(v[2], tag) | mism(v[3], tag)) & 1)) break;
                    }
#pragma unroll
                    for (int m = 0; m < 4; m++) { a0 += __uint_as_float(v[m].x); a1 += __uint_as_float(v[m].y); a2 += __uint_as_float(v[m].z); a3 += __uint_as_float(v[m].w); }
                }
                asm volatile("st.shared.u8 [%0], %1;" ::"r"(sb + OFF_ROWMAP + jj), "r"(j) : "memory");
            }
            sts2(sb + OFF_FA + (lane >> 1) * 128 + j * 16 + (lane & 1) * 8, pack_bf16(bf16r(a0) * sig, bf16r(a1) * sig), pack_bf16(bf16r(a2) * sig, bf16r(a3) * sig));
        }
        fence_async_smem();
        __syncwarp();
        if (lane == 0) mbar_arrive(bars + 8 * B_UPD);
        TSC(ta == 0, 24);
        TS_END();
    } else {
        reg_inc<224>();
        TSC(TIMING == 5 && tid == 0, 36);
        const int w = warp >> 2, wi = warp & 3, tw = (1 - w) * 4 + wi;
        const bool elect = (tid & 127) == 0;
        const uint32_t ln = opaque(lane), g = ln >> 2, t = ln & 3;
        uint32_t tag;
        {
            float acc[2][96];
            const uint32_t sta = opaque(sb + OFF_STAT + tw * 256 + 64 + g * 8);
            {
                float fa[4] = {0.f, 0.f, 0.f, 0.f};
                uint32_t so = STAGE >> 4, bo = bars, ph = 0;
                const uint32_t dx0 = sd + dlo(w == hp ? 40960 : 0, 16), dw0 = sd + dlo(16384, 8192);
                int p = 0;
                auto step = [&](bool ffn, int fs, uint32_t fph, bool last) {
                    mbar_wait(bo + 8 * B_FULLA, ph);
                    if (w) mbar_wait(bo + 8 * B_FULLB, ph);
                    TSC(TIMING == 9 && elect && p >= 11, 32 + (p - 11) * 6 + w * 3);
                    if (ffn) mbar_wait(bars + 8 * (B_FFULL + fs), fph);
                    TSC(TIMING == 9 && elect && p >= 11, 33 + (p - 11) * 6 + w * 3);
                    TSC(elect && p == 0, 1 + 8 * w);
                    bar_sync(1 + w, 256);
                    TSC(TIMING == 1 && tid == 0, 32 + p);
                    wg_fence();
                    if (last) {
                        wgmma_n192<0, 1>(acc[0], mkdesc(sd + dlo(OFF_MEAN, 0) + w * 128, dhi(128, 0)), mkdesc(sd + dlo(OFF_CS, 0), dhi(48, 0)));
                        wgmma_n192<0, 1>(acc[1], mkdesc(sd + dlo(OFF_MEAN + 1024, 0) + w * 128, dhi(128, 0)), mkdesc(sd + dlo(OFF_CS, 0), dhi(48, 0)));
                    }
#pragma unroll
                    for (int k = 0; k < 4; k++) {
                        wgmma_n192<0, 1>(acc[0], mkdesc(dx0 + so + k * 2, dhi(1024, 1)), mkdesc(dw0 + so + k * 128, dhi(1024, 1)), k || ffn || last ? 1 : p);
                        wgmma_n192<0, 1>(acc[1], mkdesc(dx0 + so + 512 + k * 2, dhi(1024, 1)), mkdesc(dw0 + so + k * 128, dhi(1024, 1)), k || ffn || last ? 1 : p);
                        if (ffn && k == 2) {
#pragma unroll
                            for (int j = 0; j < 8; j++)
                                wgmma_n8<1, 0>(fa, mkdesc(sd + dlo(OFF_FW, 8192) + fs * 1024 + j * 64, dhi(512, 2)), mkdesc(sd + dlo(OFF_FA, 128) + fs * 128 + j * 16, dhi(128, 0)));
                        }
                    }
                    wg_commit();
                    bar_arrive(2 - w, 256);
                    wg_wait<0>();
                    TSC(TIMING == 9 && elect && p >= 11, 34 + (p - 11) * 6 + w * 3);
                    if (wi == 0 && elect_one()) { mbar_arrive(bo + 8 * B_EMPTY); if (ffn) mbar_arrive(bars + 8 * (B_FEMPTY + fs)); }
                    so = so == 2 * (STAGE >> 4) ? 0 : so + (STAGE >> 4);
                    bo += 8;
                    if (bo == bars + 24) { bo = bars; ph ^= 1; }
                };
                if (w) bar_arrive(1, 256);
                uint32_t fm = opaque((b < 112 ? (F1_MASK >> (16 * w)) & 0xffff : 0u) | 0x80000000u), fph = 0;
                int fs = w;
#pragma unroll 1
                for (; p < 16; p++) {
                    if (fm & 1) { step(true, fs, fph, false); fs += 2; if (fs >= 3) { fs -= 3; fph ^= 1; } }
                    else if (fm & 0x10000) step(false, 0, 0, true);
                    else step(false, 0, 0, false);
                    fm >>= 1;
                    if (p != 14) continue;
                    if (b < 112) sts4(sb + OFF_FA + tid * 16, __float_as_uint(fa[0]), __float_as_uint(fa[1]), __float_as_uint(fa[2]), __float_as_uint(fa[3]));
                    __syncwarp();
                    if (lane == 0) mbar_arrive(bars + 8 * B_PART);
                    mbar_wait(bars + 8 * B_AUX, 0);
                    mbar_wait(bars + 8 * (B_EMPTY + 1), 0);
                    const uint32_t hm = __float_as_uint(0.5f * lds1f(sb + OFF_STAT + 64 + tw * 256 + ln * 8)) >> 16;
                    sts4(sb + OFF_MEAN + w * 2048 + wi * 256 + (ln >> 4) * 1024 + (ln & 15) * 16, hm * 0x10001u, hm, 0, 0);
                    fence_async_smem();
                }
                if (elect) mbar_arrive(bars + 8 * B_G1DONE);
            }
            TSC(elect, 2 + 8 * w);

            mbar_wait(bars + 8 * (B_EMPTY + 2), 0);
            uint32_t pk[4][24];
            auto np = [&](int i, int j) {
                const float* a = &acc[i >> 1][4 * j + 2 * (i & 1)];
                pk[i][j] = pack_bf16(a[0], a[1]);
                if (j >= 16) pk[i][j] = movm(pk[i][j]);
            };
            const uint32_t ha = sb + OFF_HALO + tw * 2048 + ln * 8;
#pragma unroll
            for (int j = 8; j < 24; j += 2) { np(3, j); np(3, j + 1); sts2(ha + 2048 + (j - 8) * 128, pk[3][j], pk[3][j + 1]); }
            bar_arrive(4 + tw, 64);
            TSC(TIMING == 8 && ln == 0 && wi == 1, 32 + 8 * w);
            tag = lds1(sb + OFF_TAG);
            const bool u0 = 2 * t > g, u1 = 2 * t + 1 > g;
            const uint32_t mU = (u0 ? 0xffffu : 0u) | (u1 ? 0xffff0000u : 0u);
            uint8_t* ob = g_o + (size_t)((mt * 2 + 1 - w) * 2 + 1 - (wi >> 1)) * 131072 + nt * 1024 + (wi & 1) * 512 + ln * 4;
            uint2 hl[8];
            float rk[4][2], fq[4][2];
            const float mask = tw == 0 && j0 == 0 ? -INFINITY : 0.f;
#pragma unroll
            for (int hd = 0; hd < 2; hd++) {
#pragma unroll
                for (int jj = 0; jj < 12; jj++) {
                    const int j = (jj >> 2) * 8 + hd * 4 + (jj & 3);
                    np(0, j); np(1, j); np(2, j);
                    if (j < 8) np(3, j);
                }
                float s[2][3][4];
#pragma unroll
                for (int h = 1; h >= 0; h--)
#pragma unroll
                    for (int n = 2; n >= 0; n--) {
                        if (h == 0 && n == 0 && hd == 0) {
                            const uint32_t ka = sb + OFF_STAT + tw * 256 + 4 + t * 16, k0 = opaque(ka + (u0 ? 0 : 64)), k1 = opaque(ka + (u1 ? 8 : 72));
#pragma unroll
                            for (int i = 0; i < 4; i++) {
                                const float rq = lds1f(sta + i * 64 + 4) * (0.17677669529663687f * 1.4426950408889634f);
                                rk[i][0] = lds1f(k0 + i * 64); rk[i][1] = lds1f(k1 + i * 64);
                                fq[i][0] = rq * rk[i][0]; fq[i][1] = rq * rk[i][1];
                            }
                            TSC(TIMING == 8 && ln == 0 && wi == 1 && s[1][0][0] + s[0][1][0] != 123.456f, 33 + 8 * w);
                            bar_sync(3 + tw, 64);
#pragma unroll
                            for (int c = 0; c < 8; c++) hl[c] = lds2(ha + c * 256);
                        }
                        const int kg = 2 * h - 1 + n;
                        s[h][n][0] = s[h][n][1] = kg < 0 ? mask : 0.f; s[h][n][2] = s[h][n][3] = 0.f;
#pragma unroll
                        for (int ks = 0; ks < 2; ks++) {
                            const int q = hd * 4 + 2 * ks;
                            const uint32_t* k = kg < 0 ? &hl[hd * 2 + ks].x : &pk[kg < 0 ? 0 : kg][8 + q];
                            mma16816(s[h][n], pk[2 * h][q], pk[2 * h + 1][q], pk[2 * h][q + 1], pk[2 * h + 1][q + 1], k[0], k[1]);
                        }
                    }
                uint32_t pp[4], pc[4];
#pragma unroll
                for (int i = 0; i < 4; i++) {
                    const float* sp = &s[i >> 1][i & 1][2 * (i & 1)];
                    const float* sc = &s[i >> 1][(i & 1) + 1][2 * (i & 1)];
                    float a0 = (u0 ? sp[0] : sc[0]) * fq[i][0], a1 = (u1 ? sp[1] : sc[1]) * fq[i][1];
                    float m = fmaxf(a0, a1);
                    m = fmaxf(m, __shfl_xor_sync(0xffffffffu, m, 1));
                    m = fmaxf(m, __shfl_xor_sync(0xffffffffu, m, 2));
                    a0 = ex2(a0 - m); a1 = ex2(a1 - m);
                    float sum = a0 + a1;
                    sum += __shfl_xor_sync(0xffffffffu, sum, 1);
                    sum += __shfl_xor_sync(0xffffffffu, sum, 2);
                    const float inv = rcp(sum);
                    const uint32_t pw = pack_bf16(a0 * rk[i][0] * inv, a1 * rk[i][1] * inv);
                    pp[i] = pw & mU; pc[i] = pw & ~mU;
                }
                TSC(TIMING == 8 && ln == 0 && wi == 1 && pp[0] + pp[3] != 0x12345, 34 + 2 * hd + 8 * w);
                uint32_t ow[4][4];
#pragma unroll
                for (int fh = 0; fh < 2; fh++)
#pragma unroll
                    for (int i = 0; i < 4; i++) {
                        const int v = 16 + hd * 4 + 2 * fh;
                        const uint32_t* vp = i ? &pk[i ? i - 1 : 0][v] : &hl[4 + hd * 2 + fh].x;
                        float o[4] = {0.f, 0.f, 0.f, 0.f};
                        if (i & 1) mma16816(o, vp[0], vp[1], pk[i][v], pk[i][v + 1], pp[i], pc[i]);
                        else { mma1688(o, pk[i][v], pk[i][v + 1], pc[i]); mma1688(o, vp[0], vp[1], pp[i]); }
                        const uint32_t tm = (ln & 7) == (nt & 3) * 2 + (i & 1);
                        ow[2 * fh][i] = tagw(pack_bf16(o[0], o[1]), tm, tag); ow[2 * fh + 1][i] = tagw(pack_bf16(o[2], o[3]), tm, tag);
                    }
                if (hd && ln == 0) mbar_arrive(bars + 8 * B_ATT);
#pragma unroll
                for (int f = 0; f < 4; f++)
#pragma unroll
                    for (int i = 3; i >= 0; i--) st_rlx(ob + (hd * 4 + f) * 16384 + i * 128, ow[f][i]);
                TSC(elect && hd == 0, 3 + 8 * w);
                TSC(TIMING == 8 && ln == 0 && wi == 1, 35 + 2 * hd + 8 * w);
            }
        }
        TSC(elect, 4 + 8 * w);
        if (!w) bar_sync(1, 256);
        float acc2[64];
        const uint32_t xs = sb + (wi & 1) * 8192 + (tw >> 1) * 2048, mad = xs + (ln & 15) * 128;
        {
            const uint32_t sta = sb + OFF_STAT + (8 + hp * 128 + tw * 16 + g) * 8;
            const float2 s0 = lds2f(sta), s1 = lds2f(sta + 64);
            const float m0 = s0.x * s0.y, r0 = 1.f + s0.y, m1 = s1.x * s1.y, r1 = 1.f + s1.y;
#pragma unroll
            for (int j = 0; j < 16; j += 2) {
                uint32_t a0, a1, a2, a3;
                const int ch = (j & 7) + (ln >> 4);
                asm volatile("ldmatrix.sync.aligned.m8n8.x4.shared.b16 {%0,%1,%2,%3}, [%4];" : "=r"(a0), "=r"(a1), "=r"(a2), "=r"(a3)
                             : "r"(mad + (j >> 3) * STAGE + ((ch ^ (ln & 7)) << 4)) : "memory");
                acc2[4 * j + 0] = fmaf(bf_lo(a0), r0, m0); acc2[4 * j + 1] = fmaf(bf_hi(a0), r0, m0);
                acc2[4 * j + 2] = fmaf(bf_lo(a1), r1, m1); acc2[4 * j + 3] = fmaf(bf_hi(a1), r1, m1);
                acc2[4 * j + 4] = fmaf(bf_lo(a2), r0, m0); acc2[4 * j + 5] = fmaf(bf_hi(a2), r0, m0);
                acc2[4 * j + 6] = fmaf(bf_lo(a3), r1, m1); acc2[4 * j + 7] = fmaf(bf_hi(a3), r1, m1);
            }
        }
        TSC(elect, 5 + 8 * w);
        {
            if (w) bar_sync(14, 256); else mbar_wait(bars + 8 * B_ATT, 0);
            const uint32_t ring = sb + (w ? OFF_O1 : OFF_O0), da0 = (ring >> 4) + dlo(0, 1024);
            const uint32_t chk = ring + wi * 256 + (ln >> 3) * 1032 + (g & 1) * 132 + t * 32;
            uint32_t db = sd + dlo(OFF_WO, 8192), wb = bars + 8 * B_WOFULL, ro = 0;
            const int s0 = w ? 1 : LEAD;
#pragma unroll 1
            for (int s = 0; s < 16; s++) {
                mbar_wait(wb, 0);
                mbar_wait(wb + 128 + 128 * w, 0);
                uint32_t v0 = lds1(chk + ro), v1 = lds1(chk + ro + 4096);
                if (s >= s0 && s < 13) wg_wait<0>();
                wg_wait<1>();
                if (elect && s > 1 && s <= s0) mbar_arrive(wb + 8 * (B_DONE - B_WOFULL - 2) + 128 * w);
                if (elect && s >= s0 && s < 13) mbar_arrive(wb + 8 * (B_DONE - B_WOFULL - 1) + 128 * w);
#pragma unroll 1
                for (int it = 0; __any_sync(0xffffffffu, mism(v0, v1, tag) & 1) && it < SPIN_LIMIT; it++) {
                    NRETRY();
                    const uint32_t fo = wi * 256 + (ln >> 4) * 1024 + (ln & 15) * 16;
#pragma unroll 1
                    for (int c = 0; c < 8192; c += 2048) {
                        const uint4 v = ld_rlx4(g_o + (size_t)(((mt * 2 + hp) * 2 + w) * 16 + s) * 8192 + fo + c);
                        sts4(ring + ro + fo + c, v.x, v.y, v.z, v.w);
                    }
                    fence_async_smem();
                    __syncwarp();
                    v0 = lds1(chk + ro); v1 = lds1(chk + ro + 4096);
                }
                TSC(elect && s == 0, 6 + 8 * w);
                TSC(TIMING == 1 && tid == 0, 48 + s);
                TSC(TIMING == 2 && elect, 32 + 16 * w + s);
                wg_fence();
#pragma unroll
                for (int k = 0; k < 4; k++)
                    wgmma_n128<1, 1>(acc2, mkdesc(da0 + (ro >> 4) + k * 128, dhi(128, 0)), mkdesc(db + k * 128, dhi(1024, 1)));
                wg_commit();
                if (w == 0 && s == LEAD - 1) bar_arrive(14, 256);
                db = db == sd + dlo(OFF_WO + (NWO - 1) * 16384, 8192) ? sd + dlo(OFF_WO, 8192) : db + 1024;
                wb += 8;
                ro = (ro + 8192) & 24576;
            }
            mbar_wait(bars + 8 * B_UPD, 0);
            int sl0, sl1;
            asm volatile("ld.shared.s8 %0, [%1];" : "=r"(sl0) : "r"(sb + OFF_ROWMAP + tw * 16 + g) : "memory");
            asm volatile("ld.shared.s8 %0, [%1];" : "=r"(sl1) : "r"(sb + OFF_ROWMAP + tw * 16 + 8 + g) : "memory");
            const uint32_t e0 = (sl0 >> 1) == (int)t ? 0x3f80u << ((sl0 & 1) * 16) : 0u, e1 = (sl1 >> 1) == (int)t ? 0x3f80u << ((sl1 & 1) * 16) : 0u;
            wg_fence();
            wgmma_rs_n128<1>(acc2, e0, e1, 0u, 0u, mkdesc(sd + dlo(OFF_FA, 0), dhi(128, 0)));
            wg_commit();
            wg_wait<0>();
#pragma unroll
            for (int i = 0; i < 64; i++) asm volatile("" : "+f"(acc2[i]) :: "memory");
            TSC(elect, 7 + 8 * w);
#pragma unroll
            for (int j = 0; j < 16; j += 2) {
                const int ch = (j & 7) + (ln >> 4);
                asm volatile("stmatrix.sync.aligned.m8n8.x4.shared.b16 [%0], {%1,%2,%3,%4};" ::"r"(mad + (j >> 3) * STAGE + ((ch ^ (ln & 7)) << 4)),
                             "r"(pack_bf16(acc2[4 * j], acc2[4 * j + 1])), "r"(pack_bf16(acc2[4 * j + 2], acc2[4 * j + 3])),
                             "r"(pack_bf16(acc2[4 * j + 4], acc2[4 * j + 5])), "r"(pack_bf16(acc2[4 * j + 6], acc2[4 * j + 7])) : "memory");
                if ((j & 7) == 6) {
                    fence_async_smem();
                    __syncwarp();
                    if (ln == 0) tma_store_2d(&mout, xs + (j >> 3) * STAGE, par * 1024 + cb * 128 + (j >> 3) * 64, j0 + hp * 128 + tw * 16);
                }
            }
            if (ln == 0) asm volatile("cp.async.bulk.commit_group;\ncp.async.bulk.wait_group.read 0;" ::: "memory");
            TSC(elect, 8 + 8 * w);
            TS_END();
        }
    }
}

typedef CUresult (*EncodeFn)(CUtensorMap*, CUtensorMapDataType, cuuint32_t, void*, const cuuint64_t*, const cuuint64_t*, const cuuint32_t*,
                             const cuuint32_t*, CUtensorMapInterleave, CUtensorMapSwizzle, CUtensorMapL2promotion, CUtensorMapFloatOOBfill);

CUtensorMap make_map(EncodeFn fn, const void* base, int rank, const cuuint64_t* dims, const cuuint64_t* strides, const cuuint32_t* box,
                     CUtensorMapSwizzle swz = CU_TENSOR_MAP_SWIZZLE_128B, CUtensorMapL2promotion pro = CU_TENSOR_MAP_L2_PROMOTION_L2_256B) {
    CUtensorMap m;
    cuuint32_t es[5] = {1, 1, 1, 1, 1};
    fn(&m, CU_TENSOR_MAP_DATA_TYPE_BFLOAT16, rank, (void*)base, dims, strides, box, es, CU_TENSOR_MAP_INTERLEAVE_NONE,
       swz, pro, CU_TENSOR_MAP_FLOAT_OOB_FILL_NONE);
    return m;
}

}

extern "C" void kernel_launch(void* const* d_in, const int* in_sizes, int n_in, void* d_out, int out_size) {
    (void)in_sizes; (void)n_in; (void)out_size;
    const __nv_bfloat16* x = (const __nv_bfloat16*)d_in[0];
    const __nv_bfloat16* wqkv = (const __nv_bfloat16*)d_in[1];
    const char* wo = (const char*)d_in[2];
    const __nv_bfloat16* wr = (const __nv_bfloat16*)d_in[4];
    const char* wg = (const char*)d_in[5];
    const char* wu = (const char*)d_in[6];
    const char* wd = (const char*)d_in[7];
    static EncodeFn fn = nullptr;
    static int by_sm = 0;
    static Scratch* scr = nullptr;
    if (!fn) {
        void* p = nullptr; cudaDriverEntryPointQueryResult q;
        cudaGetDriverEntryPoint("cuTensorMapEncodeTiled", &p, cudaEnableDefault, &q);
        fn = (EncodeFn)p;
        cudaFuncSetAttribute(fused_kernel, cudaFuncAttributeMaxDynamicSharedMemorySize, SMEM_LAUNCH);
        cudaGetSymbolAddress((void**)&scr, g_scr);
        int dev = 0, sms = 0;
        cudaGetDevice(&dev);
        cudaDeviceGetAttribute(&sms, cudaDevAttrMultiProcessorCount, dev);
        by_sm = sms == 132;
    }
    const cuuint64_t xd[4] = {2048, 16, 32, 2}, xs[3] = {4096, 131072, 65536};
    const cuuint32_t xb[4] = {64, 16, 4, 2};
    const cuuint64_t wdm[3] = {1024, 1024, 3}, wst[2] = {6144, 2048};
    const cuuint32_t wb[3] = {64, 64, 3};
    const cuuint64_t od[4] = {64, 64, 16, 16}, ost[3] = {2048, 131072, 128};
    const cuuint32_t ob[4] = {64, 8, 8, 2};
    const cuuint64_t yd[2] = {2048, 1024}, yst[1] = {4096};
    const cuuint32_t yb[2] = {64, 16};
    const cuuint64_t sd[3] = {64, 1024, 32}, sst[2] = {4096, 128};
    const cuuint32_t sbx[3] = {64, 16, 4};
    CUtensorMap mxs = make_map(fn, x, 3, sd, sst, sbx);
    CUtensorMap mx = make_map(fn, x, 4, xd, xs, xb), mw = make_map(fn, wqkv, 3, wdm, wst, wb);
    CUtensorMap mwo = make_map(fn, wo, 4, od, ost, ob), mout = make_map(fn, d_out, 2, yd, yst, yb);
    const cuuint64_t gd[3] = {3584, 1024, 2}, gst[2] = {7168, (cuuint64_t)(wu < wg ? wg - wu : wu - wg)};
    const cuuint32_t gb[3] = {32, 128, 2};
    const cuuint64_t dd[2] = {1024, 3584}, dst[1] = {2048};
    const cuuint32_t db[2] = {64, 64};
    CUtensorMap mgu = make_map(fn, wu < wg ? wu : wg, 3, gd, gst, gb, CU_TENSOR_MAP_SWIZZLE_64B, CU_TENSOR_MAP_L2_PROMOTION_L2_128B);
    CUtensorMap mwd = make_map(fn, wd, 2, dd, dst, db, CU_TENSOR_MAP_SWIZZLE_128B, CU_TENSOR_MAP_L2_PROMOTION_L2_128B);
    fused_kernel<<<132, 512, SMEM_LAUNCH, cudaStreamPerThread>>>(by_sm, x, wqkv, wr, scr, wg, wu, wd, wo, mw, mx, mwo, mxs, mout, mgu, mwd);
}
```

```cpp
#include <cuda_runtime.h>
#include <cuda.h>
#include <cuda_bf16.h>
#include <stdint.h>

namespace {

constexpr int STAGE = 57344;
constexpr int OFF_FW = 3 * STAGE;
constexpr int OFF_FA = OFF_FW + 49152;
constexpr int OFF_CS = OFF_FA + 6144;
constexpr int OFF_STAT = OFF_CS + 1232;
constexpr int OFF_ROWMAP = OFF_STAT + 2112;
constexpr int OFF_TAG = OFF_ROWMAP + 128;
constexpr int OFF_BAR = OFF_TAG + 8;
constexpr int OFF_F2X = 16384, OFF_HALO = 24576, OFF_O1 = 24576, OFF_O0 = 73728, OFF_WO = 106496, NWO = 3, OFF_MEAN = 2 * STAGE;
static_assert(OFF_WO + NWO * 32768 <= OFF_FA && OFF_O0 + 32768 == OFF_WO && OFF_O1 + 32768 == STAGE, "alias");
constexpr int B_FULLA = 0, B_FULLB = 3, B_ROW = 6, B_FFULL = 11, B_FEMPTY = 14, B_F2DONE = 17, B_GO = 18, B_WOFULL = 19, B_OFULL = B_WOFULL + 8,
              B_DONE = B_OFULL + 16;
constexpr int B_EMPTY = B_DONE + 16, B_XR = B_EMPTY + 3, B_G1DONE = B_XR + 1;
constexpr int B_UPD = B_G1DONE + 1, B_F2FULL = B_UPD + 1;
constexpr int B_AUX = B_F2FULL + 1, B_PART = B_AUX + 1, B_ATT = B_PART + 1, B_CSDONE = B_ATT + 1, B_AST = B_CSDONE + 1, NBAR = B_AST + 1;
constexpr int SMEM_BYTES = OFF_BAR + NBAR * 8;
static_assert(SMEM_BYTES <= 232448 && OFF_BAR % 8 == 0, "smem");
#define P_PART 13
#define F1_MASK (0x6a005a00u >> (14 - P_PART))
#define PF_CNT 0x2aaaaac
#define EARLY_FILL 2
#define N_S1 2
#define T_X 300
#define D_X 330
#define T_ROW 1000
#define D_R 400
#define T_W 1500
#define D_W 500
#define T_CS 2400
#define W_LAG -1
#define ST_A 2
#define ST_B 2
#define N_X0 1
#define MAP 1
#define DBG_F2 1
#define DBG_F1 1
#define DBG_XR 1
#define T_H 400
#define T_O1 128
#define XR_GATE B_G1DONE
#define ST_C 5
#define T_O 2250
#define T_S1 128
#define T_GO 256
#define T_S2 1200
#define POLL_NS 100
#define STATS_UNROLL 4
constexpr int kStatsUnroll = STATS_UNROLL;
constexpr int SPIN_LIMIT = 1 << 18;

struct Scratch {
    uint8_t o[2048 * 1024 * 2];
    uint2 rec[2048];
    float cs[8][3072];
    uint32_t halo[128][512];
    uint32_t h[14336];
    float ypart[8][8][1024];
    uint2 sel[16];
    uint32_t hint[128][8];
    uint32_t epoch;
};
__device__ __align__(1024) Scratch g_scr;

#define TS(i) do {} while (0)
#define TS_END() do {} while (0)
constexpr int SMEM_LAUNCH = SMEM_BYTES;
#define TSC(c, i) do {} while (0)
#define NRETRY() do {} while (0)
__device__ __forceinline__ uint32_t smem_u32(const void* p) { return (uint32_t)__cvta_generic_to_shared(p); }
__device__ __forceinline__ void mbar_init(uint32_t bar, uint32_t cnt) { asm volatile("mbarrier.init.shared::cta.b64 [%0], %1;" ::"r"(bar), "r"(cnt) : "memory"); }
__device__ __forceinline__ void mbar_expect_tx(uint32_t bar, uint32_t bytes) { asm volatile("mbarrier.arrive.expect_tx.shared::cta.b64 _, [%0], %1;" ::"r"(bar), "r"(bytes) : "memory"); }
__device__ __forceinline__ void mbar_arrive(uint32_t bar) { asm volatile("mbarrier.arrive.shared::cta.b64 _, [%0];" ::"r"(bar) : "memory"); }
__device__ __forceinline__ void mbar_wait(uint32_t bar, uint32_t parity) {
    asm volatile("{\n.reg .pred P1;\nLAB_WAIT:\nmbarrier.try_wait.parity.shared::cta.b64 P1, [%0], %1;\n@!P1 bra LAB_WAIT;\n}" ::"r"(bar), "r"(parity) : "memory");
}
__device__ __forceinline__ bool mbar_test(uint32_t bar, uint32_t parity) {
    uint32_t ok;
    asm volatile("{\n.reg .pred p;\nmbarrier.test_wait.parity.shared::cta.b64 p, [%1], %2;\nselp.u32 %0, 1, 0, p;\n}" : "=r"(ok) : "r"(bar), "r"(parity) : "memory");
    return ok;
}
__device__ __forceinline__ void tma_2d(uint32_t dst, const CUtensorMap* m, uint32_t bar, int c0, int c1) {
    asm volatile("cp.async.bulk.tensor.2d.shared::cluster.global.mbarrier::complete_tx::bytes [%0], [%1, {%3, %4}], [%2];" ::"r"(dst), "l"(m), "r"(bar), "r"(c0), "r"(c1) : "memory");
}
__device__ __forceinline__ void tma_3d(uint32_t dst, const CUtensorMap* m, uint32_t bar, int c0, int c1, int c2) {
    asm volatile("cp.async.bulk.tensor.3d.shared::cluster.global.mbarrier::complete_tx::bytes [%0], [%1, {%3, %4, %5}], [%2];" ::"r"(dst), "l"(m), "r"(bar), "r"(c0), "r"(c1), "r"(c2) : "memory");
}
__device__ __forceinline__ void tma_4d(uint32_t dst, const CUtensorMap* m, uint32_t bar, int c0, int c1, int c2, int c3) {
    asm volatile("cp.async.bulk.tensor.4d.shared::cluster.global.mbarrier::complete_tx::bytes [%0], [%1, {%3, %4, %5, %6}], [%2];" ::"r"(dst), "l"(m), "r"(bar), "r"(c0), "r"(c1), "r"(c2), "r"(c3) : "memory");
}
__device__ __forceinline__ void tma_store_2d(const CUtensorMap* m, uint32_t src, int c0, int c1) {
    asm volatile("cp.async.bulk.tensor.2d.global.shared::cta.bulk_group [%0, {%2, %3}], [%1];" ::"l"(m), "r"(src), "r"(c0), "r"(c1) : "memory");
}
__device__ __forceinline__ void bulk_g2s(uint32_t dst, const void* src, uint32_t bytes, uint32_t bar) {
    asm volatile("cp.async.bulk.shared::cluster.global.mbarrier::complete_tx::bytes [%0], [%1], %2, [%3];" ::"r"(dst), "l"(src), "r"(bytes), "r"(bar) : "memory");
}
__device__ __forceinline__ void bulk_prefetch(const void* p, uint32_t bytes) { asm volatile("cp.async.bulk.prefetch.L2.global [%0], %1;" ::"l"(p), "r"(bytes) : "memory"); }
__device__ __forceinline__ void fence_async_smem() { asm volatile("fence.proxy.async.shared::cta;" ::: "memory"); }
__device__ __forceinline__ void wg_fence() { asm volatile("wgmma.fence.sync.aligned;" ::: "memory"); }
__device__ __forceinline__ void wg_commit() { asm volatile("wgmma.commit_group.sync.aligned;" ::: "memory"); }
template <int N> __device__ __forceinline__ void wg_wait() { asm volatile("wgmma.wait_group.sync.aligned %0;" ::"n"(N) : "memory"); }
__device__ __forceinline__ uint64_t mkdesc(uint32_t lo, uint32_t hi) { return ((uint64_t)hi << 32) | lo; }
__host__ __device__ constexpr uint32_t dhi(uint32_t sbo, uint32_t mode) { return (sbo >> 4) | (mode << 30); }
__host__ __device__ constexpr uint32_t dlo(uint32_t off, uint32_t lbo) { return (off >> 4) + ((lbo >> 4) << 16); }
__device__ __forceinline__ bool elect_one() {
    uint32_t e;
    asm volatile("{\n.reg .pred p;\nelect.sync _|p, 0xffffffff;\nselp.u32 %0, 1, 0, p;\n}" : "=r"(e));
    return e;
}
template <int R> __device__ __forceinline__ void reg_inc() { asm volatile("setmaxnreg.inc.sync.aligned.u32 %0;" ::"n"(R)); }
template <int R> __device__ __forceinline__ void reg_dec() { asm volatile("setmaxnreg.dec.sync.aligned.u32 %0;" ::"n"(R)); }
__device__ __forceinline__ void bar_sync(int id, int n) { asm volatile("bar.sync %0, %1;" ::"r"(id), "r"(n) : "memory"); }
__device__ __forceinline__ void bar_arrive(int id, int n) { asm volatile("bar.arrive %0, %1;" ::"r"(id), "r"(n) : "memory"); }
__device__ __forceinline__ uint32_t pack_bf16(float lo, float hi) { uint32_t r; asm("cvt.rn.bf16x2.f32 %0, %1, %2;" : "=r"(r) : "f"(hi), "f"(lo)); return r; }
__device__ __forceinline__ float bf_lo(uint32_t u) { return __uint_as_float(u << 16); }
__device__ __forceinline__ float bf_hi(uint32_t u) { return __uint_as_float(u & 0xffff0000u); }
__device__ __forceinline__ float bf16r(float v) { return bf_lo(pack_bf16(v, 0.f)); }
__device__ __forceinline__ uint32_t tagw(uint32_t w, uint32_t m, uint32_t tag) { uint32_t r; asm("lop3.b32 %0, %1, %2, %3, 0xb8;" : "=r"(r) : "r"(w), "r"(m), "r"(tag)); return r; }
__device__ __forceinline__ uint32_t tagf(float f, uint32_t tag) { return tagw(__float_as_uint(f), 1u, tag); }
__device__ __forceinline__ uint32_t movm(uint32_t a) { uint32_t d; asm volatile("movmatrix.sync.aligned.m8n8.trans.b16 %0, %1;" : "=r"(d) : "r"(a)); return d; }
__device__ __forceinline__ void mma16816(float (&c)[4], uint32_t a0, uint32_t a1, uint32_t a2, uint32_t a3, uint32_t b0, uint32_t b1) {
    asm volatile("mma.sync.aligned.m16n8k16.row.col.f32.bf16.bf16.f32 {%0,%1,%2,%3}, {%4,%5,%6,%7}, {%8,%9}, {%0,%1,%2,%3};"
                 : "+f"(c[0]), "+f"(c[1]), "+f"(c[2]), "+f"(c[3]) : "r"(a0), "r"(a1), "r"(a2), "r"(a3), "r"(b0), "r"(b1));
}
__device__ __forceinline__ void mma1688(float (&c)[4], uint32_t a0, uint32_t a1, uint32_t b0) {
    asm volatile("mma.sync.aligned.m16n8k8.row.col.f32.bf16.bf16.f32 {%0,%1,%2,%3}, {%4,%5}, {%6}, {%0,%1,%2,%3};"
                 : "+f"(c[0]), "+f"(c[1]), "+f"(c[2]), "+f"(c[3]) : "r"(a0), "r"(a1), "r"(b0));
}
__device__ __forceinline__ uint32_t ld_rlx(const void* p) { uint32_t v; asm volatile("ld.relaxed.gpu.global.u32 %0, [%1];" : "=r"(v) : "l"(p) : "memory"); return v; }
__device__ __forceinline__ uint2 ld_rlx2(const void* p) { uint2 v; asm volatile("ld.relaxed.gpu.global.v2.u32 {%0,%1}, [%2];" : "=r"(v.x), "=r"(v.y) : "l"(p) : "memory"); return v; }
__device__ __forceinline__ uint4 ld_rlx4(const void* p) { uint4 v; asm volatile("ld.relaxed.gpu.global.v4.u32 {%0,%1,%2,%3}, [%4];" : "=r"(v.x), "=r"(v.y), "=r"(v.z), "=r"(v.w) : "l"(p) : "memory"); return v; }
__device__ __forceinline__ uint32_t ld_acq(const void* p) { uint32_t v; asm volatile("ld.acquire.gpu.global.u32 %0, [%1];" : "=r"(v) : "l"(p) : "memory"); return v; }
__device__ __forceinline__ void st_rlx(void* p, uint32_t v) { asm volatile("st.relaxed.gpu.global.u32 [%0], %1;" ::"l"(p), "r"(v) : "memory"); }
__device__ __forceinline__ void st_rlx2(void* p, uint32_t a, uint32_t b) { asm volatile("st.relaxed.gpu.global.v2.u32 [%0], {%1,%2};" ::"l"(p), "r"(a), "r"(b) : "memory"); }
__device__ __forceinline__ void st_rlx4(void* p, uint32_t a, uint32_t b, uint32_t c, uint32_t d) { asm volatile("st.relaxed.gpu.global.v4.u32 [%0], {%1,%2,%3,%4};" ::"l"(p), "r"(a), "r"(b), "r"(c), "r"(d) : "memory"); }
__device__ __forceinline__ uint4 ldg_nc(const void* p) { uint4 v; asm volatile("ld.global.nc.v4.u32 {%0,%1,%2,%3}, [%4];" : "=r"(v.x), "=r"(v.y), "=r"(v.z), "=r"(v.w) : "l"(p)); return v; }
__device__ __forceinline__ uint32_t mism(uint32_t a, uint32_t b, uint32_t tag) { uint32_t r; asm("lop3.b32 %0, %1, %2, %3, 0x7e;" : "=r"(r) : "r"(a), "r"(b), "r"(tag)); return r; }
__device__ __forceinline__ uint32_t mism(const uint4& v, uint32_t tag) { return mism(v.x, v.y, tag) | mism(v.z, v.w, tag); }
__device__ __forceinline__ void prefetch_l2(const void* p) { asm volatile("prefetch.global.L2 [%0];" ::"l"(p)); }
__device__ __forceinline__ void touch256(uint32_t dst, const void* p) { asm volatile("cp.async.ca.shared.global.L2::256B [%0], [%1], 4;" ::"r"(dst), "l"(p) : "memory"); }
__device__ __forceinline__ void nap(int n) {
#pragma unroll 1
    for (int i = 0; i < n; i++) __nanosleep(100);
}
__device__ __forceinline__ uint32_t now() { uint32_t t; asm volatile("mov.u32 %0, %%globaltimer_lo;" : "=r"(t)); return t; }
__device__ __forceinline__ void until(uint32_t t) {
#pragma unroll 1
    for (int i = 0; i < 256 && (int)(now() - t) < 0; i++) __nanosleep(50);
}
__device__ __forceinline__ uint32_t opaque(uint32_t v) { return __shfl_xor_sync(0xffffffffu, v, 0); }
__device__ __forceinline__ void sts4(uint32_t a, uint32_t x, uint32_t y, uint32_t z, uint32_t w) { asm volatile("st.shared.v4.u32 [%0], {%1,%2,%3,%4};" ::"r"(a), "r"(x), "r"(y), "r"(z), "r"(w) : "memory"); }
__device__ __forceinline__ void sts2(uint32_t a, uint32_t x, uint32_t y) { asm volatile("st.shared.v2.u32 [%0], {%1,%2};" ::"r"(a), "r"(x), "r"(y) : "memory"); }
__device__ __forceinline__ uint4 lds4(uint32_t a) { uint4 v; asm volatile("ld.shared.v4.u32 {%0,%1,%2,%3}, [%4];" : "=r"(v.x), "=r"(v.y), "=r"(v.z), "=r"(v.w) : "r"(a) : "memory"); return v; }
__device__ __forceinline__ float4 lds4f(uint32_t a) { float4 v; asm volatile("ld.shared.v4.f32 {%0,%1,%2,%3}, [%4];" : "=f"(v.x), "=f"(v.y), "=f"(v.z), "=f"(v.w) : "r"(a) : "memory"); return v; }
__device__ __forceinline__ uint2 lds2(uint32_t a) { uint2 v; asm volatile("ld.shared.v2.u32 {%0,%1}, [%2];" : "=r"(v.x), "=r"(v.y) : "r"(a) : "memory"); return v; }
__device__ __forceinline__ float2 lds2f(uint32_t a) { float2 v; asm volatile("ld.shared.v2.f32 {%0,%1}, [%2];" : "=f"(v.x), "=f"(v.y) : "r"(a) : "memory"); return v; }
__device__ __forceinline__ uint32_t lds1(uint32_t a) { uint32_t v; asm volatile("ld.shared.u32 %0, [%1];" : "=r"(v) : "r"(a) : "memory"); return v; }
__device__ __forceinline__ float lds1f(uint32_t a) { return __uint_as_float(lds1(a)); }
__device__ __forceinline__ void sts1(uint32_t a, uint32_t v) { asm volatile("st.shared.u32 [%0], %1;" ::"r"(a), "r"(v) : "memory"); }
__device__ __forceinline__ uint32_t redux_max(uint32_t v) { uint32_t r; asm volatile("redux.sync.max.u32 %0, %1, 0xffffffff;" : "=r"(r) : "r"(v)); return r; }
__device__ __forceinline__ float ex2(float x) { float r; asm("ex2.approx.ftz.f32 %0, %1;" : "=f"(r) : "f"(x)); return r; }
__device__ __forceinline__ float rcp(float x) { float r; asm("rcp.approx.ftz.f32 %0, %1;" : "=f"(r) : "f"(x)); return r; }
__device__ __forceinline__ float sigmoidf(float v) { return rcp(1.f + ex2(v * -1.4426950408889634f)); }

template <int TA, int TB>
__device__ __forceinline__ void wgmma_n192(float (&d)[96], uint64_t da, uint64_t db, int acc = 1) {
    asm volatile("{\n.reg .pred p;\nsetp.ne.b32 p, %100, 0;\n"
        "wgmma.mma_async.sync.aligned.m64n192k16.f32.bf16.bf16 "
        "{%0, %1, %2, %3, %4, %5, %6, %7, %8, %9, %10, %11, %12, %13, %14, %15, "
        "%16, %17, %18, %19, %20, %21, %22, %23, %24, %25, %26, %27, %28, %29, %30, %31, "
        "%32, %33, %34, %35, %36, %37, %38, %39, %40, %41, %42, %43, %44, %45, %46, %47, "
        "%48, %49, %50, %51, %52, %53, %54, %55, %56, %57, %58, %59, %60, %61, %62, %63, "
        "%64, %65, %66, %67, %68, %69, %70, %71, %72, %73, %74, %75, %76, %77, %78, %79, "
        "%80, %81, %82, %83, %84, %85, %86, %87, %88, %89, %90, %91, %92, %93, %94, %95}, "
        "%96, %97, p, 1, 1, %98, %99;\n}\n"
        : "+f"(d[0]), "+f"(d[1]), "+f"(d[2]), "+f"(d[3]), "+f"(d[4]), "+f"(d[5]), "+f"(d[6]), "+f"(d[7]),
          "+f"(d[8]), "+f"(d[9]), "+f"(d[10]), "+f"(d[11]), "+f"(d[12]), "+f"(d[13]), "+f"(d[14]), "+f"(d[15]),
          "+f"(d[16]), "+f"(d[17]), "+f"(d[18]), "+f"(d[19]), "+f"(d[20]), "+f"(d[21]), "+f"(d[22]), "+f"(d[23]),
          "+f"(d[24]), "+f"(d[25]), "+f"(d[26]), "+f"(d[27]), "+f"(d[28]), "+f"(d[29]), "+f"(d[30]), "+f"(d[31]),
          "+f"(d[32]), "+f"(d[33]), "+f"(d[34]), "+f"(d[35]), "+f"(d[36]), "+f"(d[37]), "+f"(d[38]), "+f"(d[39]),
          "+f"(d[40]), "+f"(d[41]), "+f"(d[42]), "+f"(d[43]), "+f"(d[44]), "+f"(d[45]), "+f"(d[46]), "+f"(d[47]),
          "+f"(d[48]), "+f"(d[49]), "+f"(d[50]), "+f"(d[51]), "+f"(d[52]), "+f"(d[53]), "+f"(d[54]), "+f"(d[55]),
          "+f"(d[56]), "+f"(d[57]), "+f"(d[58]), "+f"(d[59]), "+f"(d[60]), "+f"(d[61]), "+f"(d[62]), "+f"(d[63]),
          "+f"(d[64]), "+f"(d[65]), "+f"(d[66]), "+f"(d[67]), "+f"(d[68]), "+f"(d[69]), "+f"(d[70]), "+f"(d[71]),
          "+f"(d[72]), "+f"(d[73]), "+f"(d[74]), "+f"(d[75]), "+f"(d[76]), "+f"(d[77]), "+f"(d[78]), "+f"(d[79]),
          "+f"(d[80]), "+f"(d[81]), "+f"(d[82]), "+f"(d[83]), "+f"(d[84]), "+f"(d[85]), "+f"(d[86]), "+f"(d[87]),
          "+f"(d[88]), "+f"(d[89]), "+f"(d[90]), "+f"(d[91]), "+f"(d[92]), "+f"(d[93]), "+f"(d[94]), "+f"(d[95])
        : "l"(da), "l"(db), "n"(TA), "n"(TB), "r"(acc));
}
template <int TA, int TB>
__device__ __forceinline__ void wgmma_n128(float (&d)[64], uint64_t da, uint64_t db, int acc = 1) {
    asm volatile("{\n.reg .pred p;\nsetp.ne.b32 p, %68, 0;\n"
        "wgmma.mma_async.sync.aligned.m64n128k16.f32.bf16.bf16 "
        "{%0, %1, %2, %3, %4, %5, %6, %7, %8, %9, %10, %11, %12, %13, %14, %15, "
        "%16, %17, %18, %19, %20, %21, %22, %23, %24, %25, %26, %27, %28, %29, %30, %31, "
        "%32, %33, %34, %35, %36, %37, %38, %39, %40, %41, %42, %43, %44, %45, %46, %47, "
        "%48, %49, %50, %51, %52, %53, %54, %55, %56, %57, %58, %59, %60, %61, %62, %63}, "
        "%64, %65, p, 1, 1, %66, %67;\n}\n"
        : "+f"(d[0]), "+f"(d[1]), "+f"(d[2]), "+f"(d[3]), "+f"(d[4]), "+f"(d[5]), "+f"(d[6]), "+f"(d[7]),
          "+f"(d[8]), "+f"(d[9]), "+f"(d[10]), "+f"(d[11]), "+f"(d[12]), "+f"(d[13]), "+f"(d[14]), "+f"(d[15]),
          "+f"(d[16]), "+f"(d[17]), "+f"(d[18]), "+f"(d[19]), "+f"(d[20]), "+f"(d[21]), "+f"(d[22]), "+f"(d[23]),
          "+f"(d[24]), "+f"(d[25]), "+f"(d[26]), "+f"(d[27]), "+f"(d[28]), "+f"(d[29]), "+f"(d[30]), "+f"(d[31]),
          "+f"(d[32]), "+f"(d[33]), "+f"(d[34]), "+f"(d[35]), "+f"(d[36]), "+f"(d[37]), "+f"(d[38]), "+f"(d[39]),
          "+f"(d[40]), "+f"(d[41]), "+f"(d[42]), "+f"(d[43]), "+f"(d[44]), "+f"(d[45]), "+f"(d[46]), "+f"(d[47]),
          "+f"(d[48]), "+f"(d[49]), "+f"(d[50]), "+f"(d[51]), "+f"(d[52]), "+f"(d[53]), "+f"(d[54]), "+f"(d[55]),
          "+f"(d[56]), "+f"(d[57]), "+f"(d[58]), "+f"(d[59]), "+f"(d[60]), "+f"(d[61]), "+f"(d[62]), "+f"(d[63])
        : "l"(da), "l"(db), "n"(TA), "n"(TB), "r"(acc));
}
template <int TB>
__device__ __forceinline__ void wgmma_rs_n128(float (&d)[64], uint32_t a0, uint32_t a1, uint32_t a2, uint32_t a3, uint64_t db) {
    asm volatile("{\n.reg .pred p;\nsetp.ne.b32 p, 1, 0;\n"
        "wgmma.mma_async.sync.aligned.m64n128k16.f32.bf16.bf16 "
        "{%0, %1, %2, %3, %4, %5, %6, %7, %8, %9, %10, %11, %12, %13, %14, %15, "
        "%16, %17, %18, %19, %20, %21, %22, %23, %24, %25, %26, %27, %28, %29, %30, %31, "
        "%32, %33, %34, %35, %36, %37, %38, %39, %40, %41, %42, %43, %44, %45, %46, %47, "
        "%48, %49, %50, %51, %52, %53, %54, %55, %56, %57, %58, %59, %60, %61, %62, %63}, "
        "{%64, %65, %66, %67}, %68, p, 1, 1, %69;\n}\n"
        : "+f"(d[0]), "+f"(d[1]), "+f"(d[2]), "+f"(d[3]), "+f"(d[4]), "+f"(d[5]), "+f"(d[6]), "+f"(d[7]),
          "+f"(d[8]), "+f"(d[9]), "+f"(d[10]), "+f"(d[11]), "+f"(d[12]), "+f"(d[13]), "+f"(d[14]), "+f"(d[15]),
          "+f"(d[16]), "+f"(d[17]), "+f"(d[18]), "+f"(d[19]), "+f"(d[20]), "+f"(d[21]), "+f"(d[22]), "+f"(d[23]),
          "+f"(d[24]), "+f"(d[25]), "+f"(d[26]), "+f"(d[27]), "+f"(d[28]), "+f"(d[29]), "+f"(d[30]), "+f"(d[31]),
          "+f"(d[32]), "+f"(d[33]), "+f"(d[34]), "+f"(d[35]), "+f"(d[36]), "+f"(d[37]), "+f"(d[38]), "+f"(d[39]),
          "+f"(d[40]), "+f"(d[41]), "+f"(d[42]), "+f"(d[43]), "+f"(d[44]), "+f"(d[45]), "+f"(d[46]), "+f"(d[47]),
          "+f"(d[48]), "+f"(d[49]), "+f"(d[50]), "+f"(d[51]), "+f"(d[52]), "+f"(d[53]), "+f"(d[54]), "+f"(d[55]),
          "+f"(d[56]), "+f"(d[57]), "+f"(d[58]), "+f"(d[59]), "+f"(d[60]), "+f"(d[61]), "+f"(d[62]), "+f"(d[63])
        : "r"(a0), "r"(a1), "r"(a2), "r"(a3), "l"(db), "n"(TB));
}
template <int TA, int TB>
__device__ __forceinline__ void wgmma_n8(float (&d)[4], uint64_t da, uint64_t db, int acc = 1) {
    asm volatile("{\n.reg .pred p;\nsetp.ne.b32 p, %8, 0;\n"
        "wgmma.mma_async.sync.aligned.m64n8k16.f32.bf16.bf16 "
        "{%0, %1, %2, %3}, "
        "%4, %5, p, 1, 1, %6, %7;\n}\n"
        : "+f"(d[0]), "+f"(d[1]), "+f"(d[2]), "+f"(d[3])
        : "l"(da), "l"(db), "n"(TA), "n"(TB), "r"(acc));
}

__device__ __forceinline__ uint32_t norm_pair(uint32_t u, float m, float rinv) {
    uint32_t d = pack_bf16(bf_lo(u) - m, bf_hi(u) - m);
    return pack_bf16(bf_lo(d) * rinv, bf_hi(d) * rinv);
}

__global__ void __launch_bounds__(512, 1)
fused_kernel(int by_sm, const __nv_bfloat16* __restrict__ x, const __nv_bfloat16* __restrict__ wqkv, const __nv_bfloat16* __restrict__ wr,
             Scratch* const S, const char* __restrict__ wg, const char* __restrict__ wu, const char* __restrict__ wd, const char* __restrict__ wo,
             const __grid_constant__ CUtensorMap mw, const __grid_constant__ CUtensorMap mx, const __grid_constant__ CUtensorMap mwo,
             const __grid_constant__ CUtensorMap mxs, const __grid_constant__ CUtensorMap mout, const __grid_constant__ CUtensorMap mgu, const __grid_constant__ CUtensorMap mwd) {
    extern __shared__ __align__(1024) uint8_t smem[];
    constexpr uint32_t sb = 1024, bars = sb + OFF_BAR, sd = sb >> 4;
    const int tid = threadIdx.x, lane = tid & 31, warp = __shfl_sync(0xffffffffu, tid >> 5, 0);
    uint32_t smid;
    asm("mov.u32 %0, %%smid;" : "=r"(smid));
    const int T = smid >> 1, T8 = T < 32 ? T : T + 1 + (((T - 32) * 37) >> 8), pr = T < 60 ? (~T8 & 7) * 8 + (T8 >> 3) : T < 62 ? T + 4 : T - 2;
    const int fb = by_sm ? pr * 2 + (smid & 1) : blockIdx.x, kc = fb >> 4, c2 = fb & 15;
    const int b = (fb & ~31) | (fb & 1) << 4 | (fb & 31) >> 1;
    const int mt = b >> 4, nt = b & 15, hp = b & 1, cb = nt >> 1;
    const int par = mt >> 2, j0 = (mt & 3) * 256;
    uint8_t* const g_o = S->o;

    TSC(TIMING == 5 && tid == 0, 32);
    if (fb >= 128) {
        if (fb > 128) { nap(16); TS_END(); return; }
        const uint32_t tag = (ld_rlx(&S->epoch) & 1) - 1;
        if (tid < 8) st_rlx2(&S->sel[tid], ~tag, ~tag);
        uint4 ra, rb;
#pragma unroll 1
        for (int it = 0; it < SPIN_LIMIT; it++) {
            ra = ld_rlx4(&S->rec[tid * 2]); rb = ld_rlx4(&S->rec[1024 + tid * 2]);
            if (!((mism(ra.x, ra.z, tag) | mism(rb.x, rb.z, tag)) & 0x8000u)) break;
        }
        __syncwarp();
        TSC(tid == 0, 31);
        TSC(TIMING == 7 && lane == 0, 32 + warp);
        sts4(sb + 1024 + tid * 16, ra.y, rb.y, ra.w, rb.w);
        uint4 k = make_uint4(ra.x, ra.z, rb.x, rb.z);
        uint32_t cand;
#pragma unroll 1
        for (int pass = 0; pass < 2; pass++) {
            const uint32_t a0 = max(k.x, k.y), a1 = min(k.x, k.y), a2 = max(k.z, k.w), a3 = min(k.z, k.w), c1 = min(a0, a2), c2 = max(a1, a3);
            k = make_uint4(max(a0, a2), max(c1, c2), min(c1, c2), min(a1, a3));
#pragma unroll
            for (int r = 0; r < 8; r++) {
                const uint32_t m = redux_max(k.x);
                if (lane == r) cand = m;
                if (k.x == m) k = make_uint4(k.y, k.z, k.w, 0);
            }
            if (pass) break;
            if (lane < 8) sts1(sb + (warp * 8 + lane) * 4, cand);
            __syncthreads();
            if (warp) { TS_END(); return; }
            k = lds4(sb + lane * 16);
            TSC(TIMING == 7 && tid == 0 && k.x != 0x12345, 49);
        }
        if (lane < 8) st_rlx2(&S->sel[lane], cand, lds1(sb + 1024 + (~cand & 0x7ffu) * 4));
        TSC(tid == 0, 20);
        TS_END();
        return;
    }
    auto kblock = [&](int p) { return p; };
    auto load_stage = [&](int p, uint32_t so, int bi, int lag) {
        const int kc0 = kblock(p) * 64;
        const uint32_t fa = bars + 8 * (B_FULLA + bi), fb = bars + 8 * (B_FULLB + bi);
        mbar_expect_tx(fa, 40960);
        if (lag < 0) tma_3d(sb + so + 16384, &mw, fa, nt * 64, kc0, 0);
        tma_4d(sb + so, &mx, fa, par * 1024 + kc0, 0, (j0 >> 5) + 4, 0);
        mbar_expect_tx(fb, 16384);
        tma_4d(sb + so + 40960, &mx, fb, par * 1024 + kc0, 0, j0 >> 5, 0);
        if (lag >= 0) { nap(lag); tma_3d(sb + so + 16384, &mw, fa, nt * 64, kc0, 0); }
    };
    auto prefetch_w = [&](int part, int p0) { prefetch_l2(wqkv + (size_t)(kblock(p0 + (lane >> 3)) * 64 + mt * 8 + (lane & 7)) * 3072 + part * 1024 + nt * 64); };
    auto prefetch_x = [&](int c) { prefetch_l2(x + (size_t)((j0 + nt * 16 + (lane >> 1)) * 2 + par) * 1024 + c * 128 + (lane & 1) * 64); };
    if (warp == 12) {
        if (elect_one()) {
#pragma unroll
            for (int i = 0; i < B_ROW; i++) mbar_init(bars + 8 * i, 1);
            asm volatile("fence.mbarrier_init.release.cluster;" ::: "memory");
            TSC(TIMING == 5, 33);
            load_stage(0, STAGE, 0, -1);
            TSC(TIMING == 5, 34);
        }
    } else {
        if (warp > 12) {
            if (lane < 8) prefetch_w(warp - 13, 0);
        } else if (warp >= 10 && warp < 10 + N_X0) prefetch_x(warp - 10);
        if (warp == 0 && elect_one()) {
#pragma unroll
            for (int i = B_ROW; i < B_WOFULL; i++) mbar_init(bars + 8 * i, i >= B_FFULL && i < B_FEMPTY ? 5 : 1);
            mbar_expect_tx(bars + 8 * (B_ROW + 4), 2048);
            bulk_g2s(sb + OFF_FA, wr, 2048, bars + 8 * (B_ROW + 4));
        }
        if (warp == 1 && elect_one()) {
#pragma unroll
            for (int i = B_EMPTY; i < NBAR; i++) mbar_init(bars + 8 * i, i < B_UPD ? 2 : i < B_AUX ? 4 : i == B_AUX ? 7 : i == B_CSDONE ? 3 : 8);
        }
    }
    TSC(TIMING == 5 && lane == 0, 40 + warp);
    __syncthreads();
    TSC(TIMING >= 4 && tid == 0, 35);
    if (warp == 12 && elect_one()) {
#pragma unroll 1
        for (int p = 1; p < 3; p++) { nap(N_S1); load_stage(p, p == 2 ? 0 : 2 * STAGE, p, -1); }
    }

    if (warp >= 12) {
        reg_dec<24>();
        if (warp > 12) {
            const int p = warp - 13;
            const uint32_t t0 = now();
#pragma unroll 1
            for (int i = 0; i < 4; i++) {
                until(t0 + (p == 0 ? T_X + i * D_X : p == 1 ? T_W + i * D_W : T_ROW + i * D_R));
                if (p == 0) { prefetch_x(min(N_X0 + 2 * i, 7)); prefetch_x(min(N_X0 + 1 + 2 * i, 7)); }
                else if (p == 1) {
#pragma unroll 1
                    for (int c = 0; c < 3; c++) prefetch_w(c, min(3 + i * 4, 12));
                } else if (elect_one()) {
                    mbar_expect_tx(bars + 8 * (B_ROW + i), 8192);
                    tma_3d(sb + OFF_FW + i * 8192, &mxs, bars + 8 * (B_ROW + i), 0, j0 + nt * 16, par * 16 + i * 4);
                }
            }
            until(t0 + T_CS);
            const char* wp = (const char*)(wqkv + (size_t)(mt * 8 + (lane >> 3)) * 3072 + p * 1024 + nt * 64 + (lane & 7) * 8);
            const uint32_t stg = sb + OFF_FW + 32768 + p * 4096 + lane * 16;
            float c[8];
#pragma unroll
            for (int i = 0; i < 8; i++) c[i] = 0.f;
#pragma unroll 1
            for (int n = 0; n < 10; n++) {
                const uint32_t buf = stg + (n & 1) * 2048;
                if (n >= 2) {
                    asm volatile("cp.async.wait_group 1;" ::: "memory");
#pragma unroll 2
                    for (int i = 0; i < 4; i++) {
                        const uint4 v = lds4(buf + i * 512);
                        c[0] += bf_lo(v.x); c[1] += bf_hi(v.x); c[2] += bf_lo(v.y); c[3] += bf_hi(v.y);
                        c[4] += bf_lo(v.z); c[5] += bf_hi(v.z); c[6] += bf_lo(v.w); c[7] += bf_hi(v.w);
                    }
                }
                if (n < 8) {
                    const char* src = wp + (size_t)kblock(2 * n) * 64 * 6144;
#pragma unroll
                    for (int i = 0; i < 4; i++) asm volatile("cp.async.ca.shared.global [%0], [%1], 16;" ::"r"(buf + i * 512), "l"(src + ((i >> 1) * 64 + (i & 1) * 4) * 6144) : "memory");
                }
                asm volatile("cp.async.commit_group;" ::: "memory");
            }
            sts4(stg + lane * 16, __float_as_uint(c[0]), __float_as_uint(c[1]), __float_as_uint(c[2]), __float_as_uint(c[3]));
            sts4(stg + lane * 16 + 16, __float_as_uint(c[4]), __float_as_uint(c[5]), __float_as_uint(c[6]), __float_as_uint(c[7]));
            bar_sync(13, 128);
            const uint32_t tag = lds1(sb + OFF_TAG);
            float* gcs = &S->cs[0][p * 1024 + nt * 64];
            {
                const float2 a0 = lds2f(stg - lane * 8), a1 = lds2f(stg - lane * 8 + 256), a2 = lds2f(stg - lane * 8 + 512), a3 = lds2f(stg - lane * 8 + 768);
                st_rlx2(gcs + mt * 3072 + lane * 2, tagf((a0.x + a1.x) + (a2.x + a3.x), tag), __float_as_uint((a0.y + a1.y) + (a2.y + a3.y)));
            }
            __syncwarp();
            if (lane == 0) mbar_arrive(bars + 8 * B_CSDONE);
            TSC(warp == 13 && lane == 0, 19);
            {
                uint4 v[4];
                const float* src = gcs + (lane >> 4) * 4 * 3072 + (lane & 15) * 4;
#pragma unroll 1
                for (int it = 0; it < SPIN_LIMIT; it++) {
#pragma unroll
                    for (int m = 0; m < 4; m++) v[m] = ld_rlx4(src + m * 3072);
                    if (!((mism(v[0].x, v[1].x, tag) | mism(v[2].x, v[3].x, tag)) & 1)) break;
                }
                __syncwarp();
#pragma unroll
                for (int c = 0; c < 4; c++) {
                    const float a = (__uint_as_float((&v[0].x)[c]) + __uint_as_float((&v[1].x)[c])) + (__uint_as_float((&v[2].x)[c]) + __uint_as_float((&v[3].x)[c]));
                    (&v[0].x)[c] = __float_as_uint(a + __shfl_xor_sync(0xffffffffu, a, 16));
                }
                const uint32_t ca = sb + OFF_CS + p * 384 + ((lane & 15) >> 1) * 48 + (lane & 1) * 8;
#pragma unroll 1
                for (int r = 0; r < 3; r++) {
                    const uint32_t u0 = pack_bf16(__uint_as_float(v[0].x), __uint_as_float(v[0].y)), u1 = pack_bf16(__uint_as_float(v[0].z), __uint_as_float(v[0].w));
                    sts2(ca + r * 16, u0, u1);
                    v[0].x = __float_as_uint(__uint_as_float(v[0].x) - bf_lo(u0)); v[0].y = __float_as_uint(__uint_as_float(v[0].y) - bf_hi(u0));
                    v[0].z = __float_as_uint(__uint_as_float(v[0].z) - bf_lo(u1)); v[0].w = __float_as_uint(__uint_as_float(v[0].w) - bf_hi(u1));
                }
                if (lane < 20) sts1(sb + OFF_CS + 1152 + lane * 4, 0);
                fence_async_smem();
            }
            __syncwarp();
            if (lane == 0) mbar_arrive(bars + 8 * B_AUX);
            TSC(warp == 13 && lane == 0, 21);
            mbar_wait(bars + 8 * B_PART, 0);
            mbar_wait(bars + 8 * (B_EMPTY + 2), 0);
            if (p == 0) {
                uint4 v[4];
#pragma unroll
                for (int c = 0; c < 4; c++) v[c] = make_uint4(0, 0, 0, 0);
                const uint32_t* hsrc = &S->halo[b - 16][lane * 4];
#pragma unroll 1
                for (int it = 0; it < SPIN_LIMIT && j0; it++) {
#pragma unroll
                    for (int c = 0; c < 4; c++) v[c] = ld_rlx4(hsrc + c * 128);
                    if (!((mism(v[0].x, v[1].x, tag) | mism(v[2].x, v[3].x, tag)) & 1)) break;
                }
#pragma unroll
                for (int c = 0; c < 4; c++) sts4(sb + OFF_HALO + c * 512 + lane * 16, v[c].x, v[c].y, v[c].z, v[c].w);
                __syncwarp();
                bar_arrive(3, 64);
                TSC(TIMING == 11 && lane == 0, 34);
            } else {
                const int w = p - 1;
                const uint8_t* osrc = g_o + (size_t)((mt * 2 + hp) * 2 + w) * 131072;
                const bool far = w > hp && j0 && lane >= 16;
                const uint32_t* hsrc = &S->hint[mt * 16 + (lane & 15) - (far ? 16 : 0)][0];
                const uint32_t tn = now();
                if (lane == 0 && !w) st_rlx(&S->hint[b][0], tagw(tn, 1u, tag));
                uint32_t hv;
#pragma unroll 1
                for (int it = 0; it < SPIN_LIMIT; it++) {
                    hv = ld_rlx(hsrc);
                    if (!__any_sync(0xffffffffu, (hv ^ tag) & 1)) break;
                }
                TSC(TIMING == 11 && lane == 0, 32 + w);
                hv = redux_max(hv - tn + (far ? 0x40000000u + T_H : 0x40000000u)) + tn - 0x40000000u + T_O + w * T_O1;
                mbar_wait(bars + 8 * (w ? B_AST : B_G1DONE), 0);
                if (elect_one()) {
#pragma unroll 1
                    for (int st = 0; st < 8; st++) {
                        const uint32_t full = bars + 8 * (B_OFULL + 8 * w + st);
                        if (st == 2 && !w) { until(hv + T_GO); mbar_arrive(bars + 8 * B_GO); }
                        if (st >= 2) mbar_wait(full + 8 * (B_DONE - B_OFULL - 2), 0);
                        if (st < 3) until(hv + (st == 2 ? T_S2 : st * T_S1));
                        TSC(st == 0, 28 + w);
                        mbar_expect_tx(full, 16384);
                        bulk_g2s(sb + (w ? OFF_O1 : OFF_O0) + (st & 1) * 16384, osrc + st * 16384, 16384, full);
                    }
                }
            }
            TS_END();
            return;
        }
        if (elect_one()) {
            auto load_wo = [&](int s, int ws) {
                mbar_expect_tx(bars + 8 * (B_WOFULL + s), 32768);
                tma_4d(sb + OFF_WO + ws * 32768, &mwo, bars + 8 * (B_WOFULL + s), 0, s * 8, 0, cb * 2);
            };
            uint32_t so = STAGE, ph = 0, cnt = PF_CNT;
            int bi = 0, q = 0;
            if (smem_u32(smem) != sb) __trap();
#pragma unroll 1
            for (int i = B_WOFULL; i < B_OFULL; i++) mbar_init(bars + 8 * i, 1);
            const char* pf = (b < 64 ? wg : wu) + (b & 63) * 7168;
#pragma unroll 1
            for (int p = 3; p < 16; p++) {
                mbar_wait(bars + 8 * (B_EMPTY + bi), ph);
                load_stage(p, so, bi, W_LAG);
#pragma unroll 1
                for (int e = q + (cnt & 3); q < e; q++) {
                    if (q == 16) pf = wd + mt * 7 * 131072 + nt * 8192;
                    if (q == 23) pf = wo + b * 8192;
                    bulk_prefetch(pf, q < 16 ? 7168 : 8192);
                    pf += q < 16 ? 64 * 7168 : q < 23 ? 131072 : 1048576;
                }
                cnt >>= 2;
                so = so == 2 * STAGE ? 0 : so + STAGE;
                if (++bi == 3) { bi = 0; ph ^= 1; }
            }
            TS(27);
            int ws = 1;
#pragma unroll 1
            for (int i = 0; i < 8; i++) {
                if (i == 1) {
                    mbar_wait(bars + 8 * (B_EMPTY + 2), 0);
                    mbar_expect_tx(bars + 8 * B_F2FULL, 8192);
                    tma_2d(sb + OFF_F2X, &mwd, bars + 8 * B_F2FULL, DBG_F2 * c2 * 64, DBG_F2 * kc * 448);
#pragma unroll 1
                    for (int c = 0; c < 2; c++) {
                        if (c) mbar_wait(bars + 8 * XR_GATE, 0);
                        mbar_expect_tx(bars + 8 * B_XR, 16384);
                        tma_4d(sb + c * STAGE, &mx, bars + 8 * B_XR, DBG_XR * (par * 1024 + cb * 128 + c * 64), 0, DBG_XR * ((j0 >> 5) + hp * 4), 0);
                    }
                } else {
                    mbar_wait(bars + 8 * (i == 0 ? B_EMPTY + 1 : i == 2 ? B_F2DONE : B_DONE - NWO + i), 0);
                    if (i) mbar_wait(bars + 8 * (i == 2 ? B_OFULL : B_DONE + 8 - NWO + i), 0);
                }
                load_wo(i < 2 ? 1 - i : i, i == 1 ? 0 : ws);
                if (i != 1 && ++ws == NWO) ws = 0;
            }
        }
        TS_END();
    } else if (warp >= 8) {
        reg_dec<40>();
        const int p = warp - 8;
        const bool f1 = fb < 112;
        auto ffn_w = [&](int n, int s) {
            const uint32_t dst = sb + OFF_FW + s * 16384;
            if (n < 8) {
                mbar_expect_tx(bars + 8 * (B_FFULL + s), 16384);
                tma_3d(dst, &mgu, bars + 8 * (B_FFULL + s), DBG_F1 * fb * 32, n * 128, 0);
            } else {
                mbar_expect_tx(bars + 8 * B_F2FULL, 16384);
                tma_2d(dst, &mwd, bars + 8 * B_F2FULL, DBG_F2 * c2 * 64, DBG_F2 * kc * 448 + 64 + s * 128);
                tma_2d(dst + 8192, &mwd, bars + 8 * B_F2FULL, DBG_F2 * c2 * 64, DBG_F2 * kc * 448 + 128 + s * 128);
            }
        };
        const uint32_t epoch = __shfl_sync(0xffffffffu, ld_rlx(&S->epoch), 0), tag = (epoch & 1) - 1;
        float s1 = 0.f, s2 = 0.f, sr = 0.f, sw = 0.f, sh = 0.f;
        {
            const uint32_t xa = sb + OFF_FW + p * 512 + lane * 16, wa = sb + OFF_FA + (((p * 4 + (lane >> 3)) ^ lane) & 7) * 16;
            mbar_wait(bars + 8 * (B_ROW + 4), 0);
#pragma unroll 1
            for (int i = 0; i < 4; i++) {
                const uint4 q = lds4(sb + OFF_FA + i * 512 + lane * 16);
                sw += ((bf_lo(q.x) + bf_hi(q.x)) + (bf_lo(q.y) + bf_hi(q.y))) + ((bf_lo(q.z) + bf_hi(q.z)) + (bf_lo(q.w) + bf_hi(q.w)));
            }
#pragma unroll 1
            for (int o = 1; o < 32; o <<= 1) sw += __shfl_xor_sync(0xffffffffu, sw, o);
            {
                float c1 = 0.f, c2 = 0.f, cr = 0.f;
#pragma unroll 1
                for (int q = 0; q < 4; q++) {
                mbar_wait(bars + 8 * (B_ROW + q), 0);
                TSC(tid == 256 && q == 3, 17);
                TSC(TIMING == 4 && tid == 256, 36 + q);
#pragma unroll
                for (int i = 0; i < 4; i++) {
                    const uint4 u = lds4(xa + q * 8192 + i * 2048), w4 = lds4(wa + q * 512 + i * 128);
                    const float a0 = bf_lo(u.x), a1 = bf_hi(u.x), a2 = bf_lo(u.y), a3 = bf_hi(u.y), a4 = bf_lo(u.z), a5 = bf_hi(u.z), a6 = bf_lo(u.w), a7 = bf_hi(u.w);
                    s1 += a0 + a1; c1 += a4 + a5; s1 += a2 + a3; c1 += a6 + a7;
                    s2 = fmaf(a0, a0, s2); c2 = fmaf(a4, a4, c2); sr = fmaf(a0, bf_lo(w4.x), sr); cr = fmaf(a4, bf_lo(w4.z), cr);
                    s2 = fmaf(a1, a1, s2); c2 = fmaf(a5, a5, c2); sr = fmaf(a1, bf_hi(w4.x), sr); cr = fmaf(a5, bf_hi(w4.z), cr);
                    s2 = fmaf(a2, a2, s2); c2 = fmaf(a6, a6, c2); sr = fmaf(a2, bf_lo(w4.y), sr); cr = fmaf(a6, bf_lo(w4.w), cr);
                    s2 = fmaf(a3, a3, s2); c2 = fmaf(a7, a7, c2); sr = fmaf(a3, bf_hi(w4.y), sr); cr = fmaf(a7, bf_hi(w4.w), cr);
                }
                }
                s1 += c1; s2 += c2; sr += cr;
                TSC(TIMING == 4 && lane == 0 && s1 + s2 + sr != 123.456f, 40 + p);
            }
#pragma unroll 1
            for (int pass = 0;; pass++) {
#pragma unroll
                for (int o = 1; o < 8; o <<= 1) {
                    s1 += __shfl_xor_sync(0xffffffffu, s1, o); s2 += __shfl_xor_sync(0xffffffffu, s2, o); sr += __shfl_xor_sync(0xffffffffu, sr, o);
                }
                s1 *= 1.f / 1024.f;
                s2 = fmaf(-s1, s1, s2 * (1.f / 1024.f));
                if (!__any_sync(0xffffffffu, !pass && s1 * s1 > 256.f * s2)) break;
                sh = bf16r(s1); s1 = 0.f; s2 = 0.f; sr = 0.f;
#pragma unroll 1
                for (uint32_t o = 0; o < 2048; o = opaque(o + ((o & 12) == 12 ? 116 : 4))) {
                    const uint32_t u = lds1(xa + (o >> 7) * 2048 + (o & 12)), q = lds1(wa + o);
                    const float a0 = bf_lo(u) - sh, a1 = bf_hi(u) - sh;
                    s1 += a0 + a1; s2 = fmaf(a0, a0, fmaf(a1, a1, s2)); sr = fmaf(a0, bf_lo(q), fmaf(a1, bf_hi(q), sr));
                }
            }
        }
        const int ta = opaque(tid) - 256, lane = ta & 31, g = lane >> 2, t = lane & 3;
        {
            if ((lane & 7) == 0) {
                const int s = b * 16 + p * 4 + (lane >> 3);
                const float mb = bf16r(sh + s1);
                float den;
                asm("sqrt.approx.f32 %0, %1;" : "=f"(den) : "f"(bf16r(bf16r(s2) + 1e-5f)));
                den = bf16r(den);
                uint32_t rb = pack_bf16(fmaf(sh - mb, sw, sr) * rcp(den), 0.f);
                if (rb == 0x8000u) rb = 0;
                uint32_t ord = (rb & 0x8000u) ? (~rb & 0xffffu) : (rb | 0x8000u);
                if ((rb & 0x7fffu) > 0x7f80u) ord = 0;
                st_rlx2(&S->rec[s], (ord << 16) | (tag & 0x8000u) | (0x47ffu - (s & 1023) * 2 - par), pack_bf16(mb, den));
            }
            TSC(TIMING == 4 && lane == 0, 44 + p);
            TSC(TIMING == 7 && lane == 0, 52 + p);
            if (ta < 48) st_rlx4(&S->cs[mt][(ta >> 4) * 1024 + nt * 64 + (ta & 15) * 4], ~tag, ~tag, ~tag, ~tag);
            st_rlx4(&S->ypart[kc][ta >> 4][c2 * 64 + (ta & 15) * 4], ~tag, ~tag, ~tag, ~tag);
            if (p == 3 && f1) st_rlx4(&S->h[fb * 128 + lane * 4], ~tag, ~tag, ~tag, ~tag);
            if (ta < 2) st_rlx4(&S->hint[b][ta * 4], ~tag, ~tag, ~tag, ~tag);
            st_rlx4(&S->halo[b][ta * 4], ~tag, ~tag, ~tag, ~tag);
            if (elect_one()) {
#pragma unroll 1
                for (int i = B_OFULL + p; i < B_EMPTY; i += 4) mbar_init(bars + 8 * i, 1);
            }
            bar_sync(12, 128);
            if (p == 1) sts1(sb + OFF_ROWMAP + lane * 4, 0xffffffffu);
            if (p == 0) {
                if (lane == 0) {
                    sts1(sb + OFF_TAG, tag);
                    if (f1 && EARLY_FILL > 0) ffn_w(0, 0);
                }
                __syncwarp();
                bar_arrive(13, 128);
            }
            TSC(ta == 0, 18);
        }
        {
            uint2 r[3];
            const uint2* src = &S->rec[mt * 256 + ta];
            const int l2 = ta < 8 && j0 ? -8 : 0;
#pragma unroll 1
            for (int it = 0; it < SPIN_LIMIT; it++) {
                r[0] = ld_rlx2(src + l2); r[1] = ld_rlx2(src); r[2] = ld_rlx2(src + 128);
                if (!((mism(r[0].x, r[1].x, tag) | (r[2].x ^ tag)) & 0x8000u)) break;
            }
#pragma unroll
            for (int n = 0; n < 3; n++)
                if (n || ta < 8) sts2(sb + OFF_STAT + (n ? n * 1024 - 960 : 0) + ta * 8, (r[n].y << 16) ^ 0x80000000u, __float_as_uint(rcp(bf_hi(r[n].y))));
        }
        __syncwarp();
        if (lane == 0) mbar_arrive(bars + 8 * B_AUX);
        TSC(ta == 0, 30);
        if (EARLY_FILL > 1 && f1 && p == 0 && elect_one()) ffn_w(1, 1);
        uint2 sel;
#pragma unroll 1
        for (int it = 0; it < SPIN_LIMIT; it++) {
            sel = ld_rlx2(&S->sel[lane & 7]);
            if (!__any_sync(0xffffffffu, (sel.x ^ tag) & 0x8000u)) break;
            __nanosleep(POLL_NS);
        }
        TSC(ta == 0, 26);
        if (b == 0 && ta == 0) st_rlx(&S->epoch, epoch + 1);
        {
            const __nv_bfloat16* xp = x + (~sel.x & 0x7ffu) * 1024 + (ta >> 3) * 8;
            const float mb = bf_lo(sel.y), rinv = rcp(bf_hi(sel.y));
            uint4 v = ldg_nc(xp);
            int s = f1 ? 0 : 2;
#pragma unroll 1
            for (int n = f1 ? 0 : 8; n < (p ? 8 : 11); n++) {
                mbar_wait(bars + 8 * (f1 ? B_FEMPTY + s : B_PART), f1 && (n < 3 || (n >= 6 && n < 9)));
                if (p == 0 && s == 2) mbar_wait(bars + 8 * B_CSDONE, 0);
                if (p == 0 && n >= EARLY_FILL && elect_one()) ffn_w(n, s);
                if (n < 8) {
                    sts4(sb + OFF_FA + s * 2048 + ta * 16, norm_pair(v.x, mb, rinv), norm_pair(v.y, mb, rinv), norm_pair(v.z, mb, rinv), norm_pair(v.w, mb, rinv));
                    fence_async_smem();
                    __syncwarp();
                    if (lane == 0) mbar_arrive(bars + 8 * (B_FFULL + s));
                    v = ldg_nc(xp + ((n + 1) & 7) * 128);
                }
                if (++s == 3) s = 0;
            }
        }
        mbar_wait(bars + 8 * B_PART, 0);
        if (f1 && p >= 2) {
            const uint32_t pa = sb + OFF_FA + (ta - 64) * 16, go = wu < wg ? 1024 : 0;
            const float4 g0 = lds4f(pa + go), g1 = lds4f(pa + 2048 + go), u0 = lds4f(pa + (go ^ 1024)), u1 = lds4f(pa + 2048 + (go ^ 1024));
            float hv[4];
#pragma unroll
            for (int c = 0; c < 4; c++) {
                const float ga = bf16r((&g0.x)[c] + (&g1.x)[c]), up = bf16r((&u0.x)[c] + (&u1.x)[c]);
                hv[c] = bf16r(ga * sigmoidf(ga)) * up;
            }
#pragma unroll
            for (int hh = 0; hh < 2; hh++) {
                const float o = __shfl_xor_sync(0xffffffffu, (g & 1) ? hv[2 * hh] : hv[2 * hh + 1], 4);
                st_rlx(&S->h[(fb * 4 + (p & 1) * 2 + hh) * 32 + (2 * t + (g & 1)) * 4 + (g >> 1)],
                       tagw((g & 1) ? pack_bf16(o, hv[2 * hh + 1]) : pack_bf16(hv[2 * hh], o), g < 2, tag));
            }
            TSC(ta == 64, 22);
        }
        {
            uint4 hq[4];
            const uint32_t* hp4 = S->h + kc * 1792 + ta * 4;
#pragma unroll 1
            for (int it = 0; it < SPIN_LIMIT; it++) {
#pragma unroll
                for (int n = 0; n < 4; n++) hq[n] = ld_rlx4(hp4 + (n < 3 ? n * 512 : p < 2 ? 1536 : 0));
                if (!((mism(hq[0].x, hq[1].x, tag) | mism(hq[2].x, hq[3].x, tag)) & 1)) break;
            }
            mbar_wait(bars + 8 * B_G1DONE, 0);
            bar_sync(12, 128);
#pragma unroll
            for (int n = 0; n < 4; n++) sts4(sb + OFF_FA + ta * 16 + (n < 3 ? n * 2048 : p < 2 ? 6144 : 0), hq[n].x, hq[n].y, hq[n].z, hq[n].w);
            fence_async_smem();
            bar_sync(12, 128);
            TSC(ta == 0, 25);
            mbar_wait(bars + 8 * B_F2FULL, 0);
            mbar_wait(bars + 8 * B_ATT, 0);
            float acc[4] = {0.f, 0.f, 0.f, 0.f};
            uint32_t da = sd + dlo(OFF_F2X, 8192), db = sd + dlo(OFF_FA, 128);
#pragma unroll 1
            for (int q = 0; q < 7; q++) {
                wg_fence();
#pragma unroll
                for (int j = 0; j < 4; j++) wgmma_n8<1, 0>(acc, mkdesc(da + j * 128, dhi(1024, 1)), mkdesc(db + j * 16, dhi(128, 0)));
                wg_commit();
                da = sd + dlo(OFF_FW, 8192) + q * 512; db += 64;
            }
            wg_wait<0>();
            if (ta == 0) mbar_arrive(bars + 8 * B_F2DONE);
#pragma unroll
            for (int c = 0; c < 4; c++) st_rlx(&S->ypart[kc][2 * t + (c & 1)][c2 * 64 + p * 16 + (c >> 1) * 8 + g], tagf(acc[c], tag));
            TSC(ta == 0, 23);
            bar_sync(12, 128);
        }
#pragma unroll 1
        for (int j = 2 * p; j < 2 * p + 2; j++) {
            const uint32_t kj = __shfl_sync(0xffffffffu, sel.x, j);
            const int row = 0x7ff - (kj & 0x7ffu), jj = (row >> 1) - j0 - hp * 128;
            float a0 = 0.f, a1 = 0.f, a2 = 0.f, a3 = 0.f, sig = 0.f;
            if ((row & 1) == par && jj >= 0 && jj < 128) {
                sig = bf16r(sigmoidf(__uint_as_float(((int)kj < 0 ? kj ^ 0x80000000u : ~kj) & 0xffff0000u)));
#pragma unroll 1
                for (int hh = 0; hh < 8; hh += 4) {
                    uint4 v[4];
#pragma unroll 1
                    for (int it = 0; it < SPIN_LIMIT; it++) {
#pragma unroll
                        for (int m = 0; m < 4; m++) v[m] = ld_rlx4(&S->ypart[hh + m][j][cb * 128 + lane * 4]);
                        if (!((mism(v[0], tag) | mism(v[1], tag) | mism(v[2], tag) | mism(v[3], tag)) & 1)) break;
                    }
#pragma unroll
                    for (int m = 0; m < 4; m++) { a0 += __uint_as_float(v[m].x); a1 += __uint_as_float(v[m].y); a2 += __uint_as_float(v[m].z); a3 += __uint_as_float(v[m].w); }
                }
                asm volatile("st.shared.u8 [%0], %1;" ::"r"(sb + OFF_ROWMAP + jj), "r"(j) : "memory");
            }
            sts2(sb + OFF_FA + (lane >> 1) * 128 + j * 16 + (lane & 1) * 8, pack_bf16(bf16r(a0) * sig, bf16r(a1) * sig), pack_bf16(bf16r(a2) * sig, bf16r(a3) * sig));
        }
        fence_async_smem();
        __syncwarp();
        if (lane == 0) mbar_arrive(bars + 8 * B_UPD);
        TSC(ta == 0, 24);
        TS_END();
    } else {
        reg_inc<224>();
        TSC(TIMING == 5 && tid == 0, 36);
        const int w = warp >> 2, wi = warp & 3, tw = (1 - w) * 4 + wi;
        const bool elect = (tid & 127) == 0;
        const uint32_t ln = opaque(lane), g = ln >> 2, t = ln & 3;
        uint32_t tag, ow[8][4];
        auto store_o = [&](int f0, int f1) {
            uint8_t* ob = g_o + (size_t)((mt * 2 + 1 - w) * 2 + 1 - (wi >> 1)) * 131072 + nt * 1024 + (wi & 1) * 512 + ln * 4;
#pragma unroll
            for (int f = f0; f < f1; f++)
#pragma unroll
                for (int i = 3; i >= 0; i--)
                    st_rlx(ob + f * 16384 + i * 128, ow[f][i]);
        };
        {
            float acc[2][96];
            const uint32_t sta = opaque(sb + OFF_STAT + tw * 256 + 64 + g * 8);
            {
                float fa[4] = {0.f, 0.f, 0.f, 0.f};
                uint32_t so = STAGE >> 4, bo = bars, ph = 0;
                const uint32_t dx0 = sd + dlo(w ? 40960 : 0, 16), dw0 = sd + dlo(16384, 8192);
                int p = 0;
                auto step = [&](bool ffn, int fs, uint32_t fph, bool last) {
                    mbar_wait(bo + 8 * B_FULLA, ph);
                    if (w) mbar_wait(bo + 8 * B_FULLB, ph);
                    TSC(TIMING == 9 && elect && p >= 11, 32 + (p - 11) * 6 + w * 3);
                    if (ffn) mbar_wait(bars + 8 * (B_FFULL + fs), fph);
                    TSC(TIMING == 9 && elect && p >= 11, 33 + (p - 11) * 6 + w * 3);
                    TSC(elect && p == 0, 1 + 8 * w);
                    bar_sync(1 + w, 256);
                    TSC(TIMING == 1 && tid == 0, 32 + p);
                    wg_fence();
                    if (last) {
                        wgmma_n192<0, 1>(acc[0], mkdesc(sd + dlo(OFF_MEAN, 0) + w * 128, dhi(128, 0)), mkdesc(sd + dlo(OFF_CS, 0), dhi(48, 0)));
                        wgmma_n192<0, 1>(acc[1], mkdesc(sd + dlo(OFF_MEAN + 1024, 0) + w * 128, dhi(128, 0)), mkdesc(sd + dlo(OFF_CS, 0), dhi(48, 0)));
                    }
#pragma unroll
                    for (int k = 0; k < 4; k++) {
                        wgmma_n192<0, 1>(acc[0], mkdesc(dx0 + so + k * 2, dhi(1024, 1)), mkdesc(dw0 + so + k * 128, dhi(1024, 1)), k || ffn || last ? 1 : p);
                        wgmma_n192<0, 1>(acc[1], mkdesc(dx0 + so + 512 + k * 2, dhi(1024, 1)), mkdesc(dw0 + so + k * 128, dhi(1024, 1)), k || ffn || last ? 1 : p);
                        if (ffn && k == 2) {
#pragma unroll
                            for (int j = 0; j < 8; j++)
                                wgmma_n8<1, 0>(fa, mkdesc(sd + dlo(OFF_FW, 8192) + fs * 1024 + j * 64, dhi(512, 2)), mkdesc(sd + dlo(OFF_FA, 128) + fs * 128 + j * 16, dhi(128, 0)));
                        }
                    }
                    wg_commit();
                    bar_arrive(2 - w, 256);
                    wg_wait<0>();
                    TSC(TIMING == 9 && elect && p >= 11, 34 + (p - 11) * 6 + w * 3);
                    if (wi == 0 && elect_one()) { mbar_arrive(bo + 8 * B_EMPTY); if (ffn) mbar_arrive(bars + 8 * (B_FEMPTY + fs)); }
                    so = so == 2 * (STAGE >> 4) ? 0 : so + (STAGE >> 4);
                    bo += 8;
                    if (bo == bars + 24) { bo = bars; ph ^= 1; }
                };
                if (w) bar_arrive(1, 256);
                uint32_t fm = opaque((fb < 112 ? (F1_MASK >> (16 * w)) & 0xffff : 0u) | 0x80000000u), fph = 0;
                int fs = w;
#pragma unroll 1
                for (; p < 16; p++) {
                    if (fm & 1) { step(true, fs, fph, false); fs += 2; if (fs >= 3) { fs -= 3; fph ^= 1; } }
                    else if (fm & 0x10000) step(false, 0, 0, true);
                    else step(false, 0, 0, false);
                    fm >>= 1;
                    if (p == P_PART) {
                        if (fb < 112) sts4(sb + OFF_FA + tid * 16, __float_as_uint(fa[0]), __float_as_uint(fa[1]), __float_as_uint(fa[2]), __float_as_uint(fa[3]));
                        __syncwarp();
                        if (lane == 0) mbar_arrive(bars + 8 * B_PART);
                    }
                    if (p != 14) continue;
                    mbar_wait(bars + 8 * B_AUX, 0);
                    mbar_wait(bars + 8 * (B_EMPTY + 1), 0);
                    const uint32_t hm = __float_as_uint(0.5f * lds1f(sb + OFF_STAT + 64 + tw * 256 + ln * 8)) >> 16;
                    sts4(sb + OFF_MEAN + w * 2048 + wi * 256 + (ln >> 4) * 1024 + (ln & 15) * 16, hm * 0x10001u, hm, 0, 0);
                    fence_async_smem();
                }
                if (elect) mbar_arrive(bars + 8 * B_G1DONE);
            }
            TSC(elect, 2 + 8 * w);

            tag = lds1(sb + OFF_TAG);
            mbar_wait(bars + 8 * (B_EMPTY + 2), 0);
            uint32_t pk[4][24];
            auto np = [&](int i, int j) {
                const float* a = &acc[i >> 1][4 * j + 2 * (i & 1)];
                pk[i][j] = pack_bf16(a[0], a[1]);
                if (j >= 16) pk[i][j] = movm(pk[i][j]);
            };
            const uint32_t ha = sb + OFF_HALO + tw * 2048 + ln * 8;
#pragma unroll
            for (int j = 8; j < 24; j += 2) { np(3, j); np(3, j + 1); }
            if (tw < 7) {
#pragma unroll
                for (int j = 8; j < 24; j += 2) sts2(ha + 2048 + (j - 8) * 128, pk[3][j], pk[3][j + 1]);
                bar_arrive(4 + tw, 64);
            } else {
#pragma unroll
                for (int j = 8; j < 24; j += 2) st_rlx2(&S->halo[b][(j - 8) * 32 + ln * 2], tagw(pk[3][j], ~ln & 1, tag), pk[3][j + 1]);
            }
            TSC(TIMING == 8 && ln == 0 && wi == 1, 32 + 8 * w);
            const bool u0 = 2 * t > g, u1 = 2 * t + 1 > g;
            const uint32_t mU = (u0 ? 0xffffu : 0u) | (u1 ? 0xffff0000u : 0u);
            uint2 hl[8];
            float rk[4][2], fq[4][2];
            const float mask = tw == 0 && j0 == 0 ? -INFINITY : 0.f;
#pragma unroll
            for (int hd = 0; hd < 2; hd++) {
#pragma unroll
                for (int jj = 0; jj < 12; jj++) {
                    const int j = (jj >> 2) * 8 + hd * 4 + (jj & 3);
                    np(0, j); np(1, j); np(2, j);
                    if (j < 8) np(3, j);
                }
                float s[2][3][4];
#pragma unroll
                for (int h = 1; h >= 0; h--)
#pragma unroll
                    for (int n = 2; n >= 0; n--) {
                        if (h == 0 && n == 0 && hd == 0) {
                            const uint32_t ka = sb + OFF_STAT + tw * 256 + 4 + t * 16, k0 = opaque(ka + (u0 ? 0 : 64)), k1 = opaque(ka + (u1 ? 8 : 72));
#pragma unroll
                            for (int i = 0; i < 4; i++) {
                                const float rq = lds1f(sta + i * 64 + 4) * (0.17677669529663687f * 1.4426950408889634f);
                                rk[i][0] = lds1f(k0 + i * 64); rk[i][1] = lds1f(k1 + i * 64);
                                fq[i][0] = rq * rk[i][0]; fq[i][1] = rq * rk[i][1];
                            }
                            TSC(TIMING == 8 && ln == 0 && wi == 1 && s[1][0][0] + s[0][1][0] != 123.456f, 33 + 8 * w);
                            bar_sync(3 + tw, 64);
#pragma unroll
                            for (int c = 0; c < 8; c++) hl[c] = lds2(ha + c * 256);
                        }
                        const int kg = 2 * h - 1 + n;
                        s[h][n][0] = s[h][n][1] = kg < 0 ? mask : 0.f; s[h][n][2] = s[h][n][3] = 0.f;
#pragma unroll
                        for (int ks = 0; ks < 2; ks++) {
                            const int q = hd * 4 + 2 * ks;
                            const uint32_t* k = kg < 0 ? &hl[hd * 2 + ks].x : &pk[kg < 0 ? 0 : kg][8 + q];
                            mma16816(s[h][n], pk[2 * h][q], pk[2 * h + 1][q], pk[2 * h][q + 1], pk[2 * h + 1][q + 1], k[0], k[1]);
                        }
                    }
                uint32_t pp[4], pc[4];
#pragma unroll
                for (int i = 0; i < 4; i++) {
                    const float* sp = &s[i >> 1][i & 1][2 * (i & 1)];
                    const float* sc = &s[i >> 1][(i & 1) + 1][2 * (i & 1)];
                    float a0 = (u0 ? sp[0] : sc[0]) * fq[i][0], a1 = (u1 ? sp[1] : sc[1]) * fq[i][1];
                    float m = fmaxf(a0, a1);
                    m = fmaxf(m, __shfl_xor_sync(0xffffffffu, m, 1));
                    m = fmaxf(m, __shfl_xor_sync(0xffffffffu, m, 2));
                    a0 = ex2(a0 - m); a1 = ex2(a1 - m);
                    float sum = a0 + a1;
                    sum += __shfl_xor_sync(0xffffffffu, sum, 1);
                    sum += __shfl_xor_sync(0xffffffffu, sum, 2);
                    const float inv = rcp(sum);
                    const uint32_t pw = pack_bf16(a0 * rk[i][0] * inv, a1 * rk[i][1] * inv);
                    pp[i] = pw & mU; pc[i] = pw & ~mU;
                }
                TSC(TIMING == 8 && ln == 0 && wi == 1 && pp[0] + pp[3] != 0x12345, 34 + 2 * hd + 8 * w);
#pragma unroll
                for (int fh = 0; fh < 2; fh++)
#pragma unroll
                    for (int i = 0; i < 4; i++) {
                        const int v = 16 + hd * 4 + 2 * fh;
                        const uint32_t* vp = i ? &pk[i ? i - 1 : 0][v] : &hl[4 + hd * 2 + fh].x;
                        float o[4] = {0.f, 0.f, 0.f, 0.f};
                        if (i & 1) mma16816(o, vp[0], vp[1], pk[i][v], pk[i][v + 1], pp[i], pc[i]);
                        else { mma1688(o, pk[i][v], pk[i][v + 1], pc[i]); mma1688(o, vp[0], vp[1], pp[i]); }
                        const uint32_t tm = (ln & 7) == (nt & 3) * 2 + (i & 1);
                        ow[hd * 4 + 2 * fh][i] = tagw(pack_bf16(o[0], o[1]), tm, tag); ow[hd * 4 + 2 * fh + 1][i] = tagw(pack_bf16(o[2], o[3]), tm, tag);
                    }
                if (hd && ln == 0) mbar_arrive(bars + 8 * B_ATT);
                store_o(hd ? ST_A : 0, hd ? ST_B : ST_A);
                if (!hd && ln == 0) mbar_arrive(bars + 8 * B_AST);
                TSC(TIMING == 11 && !hd && ln == 0 && wi == 3, 45 + w);
                TSC(elect && hd == 0, 3 + 8 * w);
                TSC(TIMING == 8 && ln == 0 && wi == 1, 35 + 2 * hd + 8 * w);
            }
        }
        TSC(elect, 4 + 8 * w);
        mbar_wait(bars + 8 * B_XR, 0);
        float acc2[64];
        const uint32_t xs = sb + (wi & 1) * 8192 + (tw >> 1) * 2048, mad = xs + (ln & 15) * 128;
        {
            const uint32_t sta = sb + OFF_STAT + (8 + hp * 128 + tw * 16 + g) * 8;
            const float2 s0 = lds2f(sta), s1 = lds2f(sta + 64);
            const float m0 = s0.x * s0.y, r0 = 1.f + s0.y, m1 = s1.x * s1.y, r1 = 1.f + s1.y;
#pragma unroll
            for (int j = 0; j < 16; j += 2) {
                uint32_t a0, a1, a2, a3;
                const int ch = (j & 7) + (ln >> 4);
                asm volatile("ldmatrix.sync.aligned.m8n8.x4.shared.b16 {%0,%1,%2,%3}, [%4];" : "=r"(a0), "=r"(a1), "=r"(a2), "=r"(a3)
                             : "r"(mad + (j >> 3) * STAGE + ((ch ^ (ln & 7)) << 4)) : "memory");
                acc2[4 * j + 0] = fmaf(bf_lo(a0), r0, m0); acc2[4 * j + 1] = fmaf(bf_hi(a0), r0, m0);
                acc2[4 * j + 2] = fmaf(bf_lo(a1), r1, m1); acc2[4 * j + 3] = fmaf(bf_hi(a1), r1, m1);
                acc2[4 * j + 4] = fmaf(bf_lo(a2), r0, m0); acc2[4 * j + 5] = fmaf(bf_hi(a2), r0, m0);
                acc2[4 * j + 6] = fmaf(bf_lo(a3), r1, m1); acc2[4 * j + 7] = fmaf(bf_hi(a3), r1, m1);
            }
        }
        TSC(elect, 5 + 8 * w);
        {
            if (ST_B < ST_C) { mbar_wait(bars + 8 * B_GO, 0); store_o(ST_B, ST_C); }
            mbar_wait(bars + 8 * B_ATT, 0);
            const uint32_t ring = sb + (w ? OFF_O1 : OFF_O0), da0 = (ring >> 4) + dlo(0, 1024);
            const uint32_t chk = ring + wi * 256 + (ln >> 3) * 1032 + (g & 1) * 132 + t * 32;
            uint32_t db = sd + dlo(OFF_WO, 16384);
#pragma unroll 1
            for (int s = 0; s < 8; s++) {
                const uint32_t ro = (s & 1) * 16384;
                mbar_wait(bars + 8 * (B_WOFULL + s), 0);
                TSC(TIMING == 11 && tid == 0 && s == 0, 43);
                mbar_wait(bars + 8 * (B_OFULL + s) + 64 * w, 0);
                TSC(TIMING == 11 && tid == 0 && s == 0, 44);
#pragma unroll 1
                for (int it = 0; __any_sync(0xffffffffu, (mism(lds1(chk + ro), lds1(chk + ro + 4096), tag) | mism(lds1(chk + ro + 8192), lds1(chk + ro + 12288), tag)) & 1) && it < SPIN_LIMIT; it++) {
                    NRETRY();
                    const uint32_t fo = wi * 256 + (ln >> 4) * 1024 + (ln & 15) * 16;
                    uint4 v[8];
#pragma unroll
                    for (int c = 0; c < 8; c++) v[c] = ld_rlx4(g_o + (size_t)(((mt * 2 + hp) * 2 + w) * 8 + s) * 16384 + fo + c * 2048);
#pragma unroll
                    for (int c = 0; c < 8; c++) sts4(ring + ro + fo + c * 2048, v[c].x, v[c].y, v[c].z, v[c].w);
                    fence_async_smem();
                    __syncwarp();
                }
                auto issue = [&](bool last) {
                uint32_t e0, e1;
                if (last) {
                    mbar_wait(bars + 8 * B_UPD, 0);
                    int sl0, sl1;
                    asm volatile("ld.shared.s8 %0, [%1];" : "=r"(sl0) : "r"(sb + OFF_ROWMAP + tw * 16 + g) : "memory");
                    asm volatile("ld.shared.s8 %0, [%1];" : "=r"(sl1) : "r"(sb + OFF_ROWMAP + tw * 16 + 8 + g) : "memory");
                    e0 = (sl0 >> 1) == (int)t ? 0x3f80u << ((sl0 & 1) * 16) : 0u; e1 = (sl1 >> 1) == (int)t ? 0x3f80u << ((sl1 & 1) * 16) : 0u;
                }
                bar_sync(1 + w, 256);
                TSC(elect && s == 0, 6 + 8 * w);
                TSC(TIMING == 2 && elect, 32 + 16 * w + s);
                wg_fence();
                if (last) wgmma_rs_n128<1>(acc2, e0, e1, 0u, 0u, mkdesc(sd + dlo(OFF_FA, 0), dhi(128, 0)));
#pragma unroll
                for (int k = 0; k < 8; k++)
                    wgmma_n128<1, 1>(acc2, mkdesc(da0 + (ro >> 4) + k * 128, dhi(128, 0)), mkdesc(db + k * 128, dhi(1024, 1)));
                wg_commit();
                bar_arrive(2 - w, 256);
                if (!last && s == 0) store_o(ST_C, 8);
                db = db == sd + dlo(OFF_WO + (NWO - 1) * 32768, 16384) ? sd + dlo(OFF_WO, 16384) : db + 2048;
                wg_wait<0>();
                if (elect && !last) mbar_arrive(bars + 8 * (B_DONE + s) + 64 * w);
                };
                if (s < 7) issue(false); else issue(true);
            }
#pragma unroll
            for (int i = 0; i < 64; i++) asm volatile("" : "+f"(acc2[i]) :: "memory");
            TSC(elect, 7 + 8 * w);
#pragma unroll
            for (int j = 0; j < 16; j += 2) {
                const int ch = (j & 7) + (ln >> 4);
                asm volatile("stmatrix.sync.aligned.m8n8.x4.shared.b16 [%0], {%1,%2,%3,%4};" ::"r"(mad + (j >> 3) * STAGE + ((ch ^ (ln & 7)) << 4)),
                             "r"(pack_bf16(acc2[4 * j], acc2[4 * j + 1])), "r"(pack_bf16(acc2[4 * j + 2], acc2[4 * j + 3])),
                             "r"(pack_bf16(acc2[4 * j + 4], acc2[4 * j + 5])), "r"(pack_bf16(acc2[4 * j + 6], acc2[4 * j + 7])) : "memory");
                if ((j & 7) == 6) {
                    fence_async_smem();
                    __syncwarp();
                    if (ln == 0) tma_store_2d(&mout, xs + (j >> 3) * STAGE, par * 1024 + cb * 128 + (j >> 3) * 64, j0 + hp * 128 + tw * 16);
                }
            }
            if (ln == 0) asm volatile("cp.async.bulk.commit_group;\ncp.async.bulk.wait_group.read 0;" ::: "memory");
            TSC(elect, 8 + 8 * w);
            TS_END();
        }
    }
}

typedef CUresult (*EncodeFn)(CUtensorMap*, CUtensorMapDataType, cuuint32_t, void*, const cuuint64_t*, const cuuint64_t*, const cuuint32_t*,
                             const cuuint32_t*, CUtensorMapInterleave, CUtensorMapSwizzle, CUtensorMapL2promotion, CUtensorMapFloatOOBfill);

CUtensorMap make_map(EncodeFn fn, const void* base, int rank, const cuuint64_t* dims, const cuuint64_t* strides, const cuuint32_t* box,
                     CUtensorMapSwizzle swz = CU_TENSOR_MAP_SWIZZLE_128B, CUtensorMapL2promotion pro = CU_TENSOR_MAP_L2_PROMOTION_L2_256B) {
    CUtensorMap m;
    cuuint32_t es[5] = {1, 1, 1, 1, 1};
    fn(&m, CU_TENSOR_MAP_DATA_TYPE_BFLOAT16, rank, (void*)base, dims, strides, box, es, CU_TENSOR_MAP_INTERLEAVE_NONE,
       swz, pro, CU_TENSOR_MAP_FLOAT_OOB_FILL_NONE);
    return m;
}

}

extern "C" void kernel_launch(void* const* d_in, const int* in_sizes, int n_in, void* d_out, int out_size) {
    (void)in_sizes; (void)n_in; (void)out_size;
    const __nv_bfloat16* x = (const __nv_bfloat16*)d_in[0];
    const __nv_bfloat16* wqkv = (const __nv_bfloat16*)d_in[1];
    const char* wo = (const char*)d_in[2];
    const __nv_bfloat16* wr = (const __nv_bfloat16*)d_in[4];
    const char* wg = (const char*)d_in[5];
    const char* wu = (const char*)d_in[6];
    const char* wd = (const char*)d_in[7];
    static EncodeFn fn = nullptr;
    static int by_sm = 0;
    static Scratch* scr = nullptr;
    if (!fn) {
        void* p = nullptr; cudaDriverEntryPointQueryResult q;
        cudaGetDriverEntryPoint("cuTensorMapEncodeTiled", &p, cudaEnableDefault, &q);
        fn = (EncodeFn)p;
        cudaFuncSetAttribute(fused_kernel, cudaFuncAttributeMaxDynamicSharedMemorySize, SMEM_LAUNCH);
        cudaGetSymbolAddress((void**)&scr, g_scr);
        int dev = 0, sms = 0;
        cudaGetDevice(&dev);
        cudaDeviceGetAttribute(&sms, cudaDevAttrMultiProcessorCount, dev);
        by_sm = sms == 132;
    }
    const cuuint64_t xd[4] = {2048, 16, 32, 2}, xs[3] = {4096, 131072, 65536};
    const cuuint32_t xb[4] = {64, 16, 4, 2};
    const cuuint64_t wdm[3] = {1024, 1024, 3}, wst[2] = {6144, 2048};
    const cuuint32_t wb[3] = {64, 64, 3};
    const cuuint64_t od[4] = {64, 64, 16, 16}, ost[3] = {2048, 131072, 128};
    const cuuint32_t ob[4] = {64, 8, 16, 2};
    const cuuint64_t yd[2] = {2048, 1024}, yst[1] = {4096};
    const cuuint32_t yb[2] = {64, 16};
    const cuuint64_t sd[3] = {64, 1024, 32}, sst[2] = {4096, 128};
    const cuuint32_t sbx[3] = {64, 16, 4};
    CUtensorMap mxs = make_map(fn, x, 3, sd, sst, sbx);
    CUtensorMap mx = make_map(fn, x, 4, xd, xs, xb), mw = make_map(fn, wqkv, 3, wdm, wst, wb);
    CUtensorMap mwo = make_map(fn, wo, 4, od, ost, ob), mout = make_map(fn, d_out, 2, yd, yst, yb);
    const cuuint64_t gd[3] = {3584, 1024, 2}, gst[2] = {7168, (cuuint64_t)(wu < wg ? wg - wu : wu - wg)};
    const cuuint32_t gb[3] = {32, 128, 2};
    const cuuint64_t dd[2] = {1024, 3584}, dst[1] = {2048};
    const cuuint32_t db[2] = {64, 64};
    CUtensorMap mgu = make_map(fn, wu < wg ? wu : wg, 3, gd, gst, gb, CU_TENSOR_MAP_SWIZZLE_64B, CU_TENSOR_MAP_L2_PROMOTION_L2_128B);
    CUtensorMap mwd = make_map(fn, wd, 2, dd, dst, db, CU_TENSOR_MAP_SWIZZLE_128B, CU_TENSOR_MAP_L2_PROMOTION_L2_128B);
    fused_kernel<<<132, 512, SMEM_LAUNCH, cudaStreamPerThread>>>(by_sm, x, wqkv, wr, scr, wg, wu, wd, wo, mw, mx, mwo, mxs, mout, mgu, mwd);
}
```

```cpp
#include <cuda_runtime.h>
#include <cuda.h>
#include <cuda_bf16.h>
#include <stdint.h>

namespace {

constexpr int STAGE = 57344;
constexpr int OFF_FW = 3 * STAGE;
constexpr int OFF_FA = OFF_FW + 49152;
constexpr int OFF_CS = OFF_FA + 6144;
constexpr int OFF_STAT = OFF_CS + 1232;
constexpr int OFF_ROWMAP = OFF_STAT + 2112;
constexpr int OFF_TAG = OFF_ROWMAP + 128;
constexpr int OFF_BAR = OFF_TAG + 8;
constexpr int OFF_F2X = 16384, OFF_HALO = 24576, OFF_O1 = 24576, OFF_O0 = 73728, OFF_WO = 106496, NWO = 3, OFF_MEAN = 2 * STAGE;
static_assert(OFF_WO + NWO * 32768 <= OFF_FA && OFF_O0 + 32768 == OFF_WO && OFF_O1 + 32768 == STAGE, "alias");
constexpr int B_FULLA = 0, B_FULLB = 3, B_ROW = 6, B_FFULL = 11, B_FEMPTY = 14, B_F2DONE = 17, B_GO = 18, B_WOFULL = 19, B_OFULL = B_WOFULL + 8,
              B_DONE = B_OFULL + 16;
constexpr int B_EMPTY = B_DONE + 16, B_XR = B_EMPTY + 3, B_G1DONE = B_XR + 1;
constexpr int B_UPD = B_G1DONE + 1, B_F2FULL = B_UPD + 1;
constexpr int B_AUX = B_F2FULL + 1, B_PART = B_AUX + 1, B_ATT = B_PART + 1, B_CSDONE = B_ATT + 1, B_AST = B_CSDONE + 1, NBAR = B_AST + 1;
constexpr int SMEM_BYTES = OFF_BAR + NBAR * 8;
static_assert(SMEM_BYTES <= 232448 && OFF_BAR % 8 == 0, "smem");
#define P_PART 13
#define F1_MASK (0x6a005a00u >> (14 - P_PART))
#define PF_CNT 0x2aaaaac
#define EARLY_FILL 2
#define N_S1 2
#define T_X 300
#define D_X 330
#define T_ROW 1000
#define D_R 400
#define T_W 1500
#define D_W 500
#define T_CS 2400
#define W_LAG -1
#define ST_A 2
#define ST_B 2
#define N_X0 1
#define MAP 1
#define DBG_F2 1
#define DBG_F1 1
#define DBG_XR 1
#define T_H 400
#define T_O1 128
#define XR_GATE B_G1DONE
#define ST_C 5
#define T_O 2250
#define T_S1 128
#define T_GO 256
#define T_S2 1200
#define POLL_NS 100
#define STATS_UNROLL 4
constexpr int kStatsUnroll = STATS_UNROLL;
constexpr int SPIN_LIMIT = 1 << 18;

struct Scratch {
    uint8_t o[2048 * 1024 * 2];
    uint2 rec[2048];
    float cs[8][3072];
    uint32_t halo[128][512];
    uint32_t h[14336];
    float ypart[8][8][1024];
    uint2 sel[16];
    uint32_t hint[128][8];
    uint32_t epoch;
};
__device__ __align__(1024) Scratch g_scr;

#define TS(i) do {} while (0)
#define TS_END() do {} while (0)
constexpr int SMEM_LAUNCH = SMEM_BYTES;
#define TSC(c, i) do {} while (0)
#define NRETRY() do {} while (0)
__device__ __forceinline__ uint32_t smem_u32(const void* p) { return (uint32_t)__cvta_generic_to_shared(p); }
__device__ __forceinline__ void mbar_init(uint32_t bar, uint32_t cnt) { asm volatile("mbarrier.init.shared::cta.b64 [%0], %1;" ::"r"(bar), "r"(cnt) : "memory"); }
__device__ __forceinline__ void mbar_expect_tx(uint32_t bar, uint32_t bytes) { asm volatile("mbarrier.arrive.expect_tx.shared::cta.b64 _, [%0], %1;" ::"r"(bar), "r"(bytes) : "memory"); }
__device__ __forceinline__ void mbar_arrive(uint32_t bar) { asm volatile("mbarrier.arrive.shared::cta.b64 _, [%0];" ::"r"(bar) : "memory"); }
__device__ __forceinline__ void mbar_wait(uint32_t bar, uint32_t parity) {
    asm volatile("{\n.reg .pred P1;\nLAB_WAIT:\nmbarrier.try_wait.parity.shared::cta.b64 P1, [%0], %1;\n@!P1 bra LAB_WAIT;\n}" ::"r"(bar), "r"(parity) : "memory");
}
__device__ __forceinline__ bool mbar_test(uint32_t bar, uint32_t parity) {
    uint32_t ok;
    asm volatile("{\n.reg .pred p;\nmbarrier.test_wait.parity.shared::cta.b64 p, [%1], %2;\nselp.u32 %0, 1, 0, p;\n}" : "=r"(ok) : "r"(bar), "r"(parity) : "memory");
    return ok;
}
__device__ __forceinline__ void tma_2d(uint32_t dst, const CUtensorMap* m, uint32_t bar, int c0, int c1) {
    asm volatile("cp.async.bulk.tensor.2d.shared::cluster.global.mbarrier::complete_tx::bytes [%0], [%1, {%3, %4}], [%2];" ::"r"(dst), "l"(m), "r"(bar), "r"(c0), "r"(c1) : "memory");
}
__device__ __forceinline__ void tma_3d(uint32_t dst, const CUtensorMap* m, uint32_t bar, int c0, int c1, int c2) {
    asm volatile("cp.async.bulk.tensor.3d.shared::cluster.global.mbarrier::complete_tx::bytes [%0], [%1, {%3, %4, %5}], [%2];" ::"r"(dst), "l"(m), "r"(bar), "r"(c0), "r"(c1), "r"(c2) : "memory");
}
__device__ __forceinline__ void tma_4d(uint32_t dst, const CUtensorMap* m, uint32_t bar, int c0, int c1, int c2, int c3) {
    asm volatile("cp.async.bulk.tensor.4d.shared::cluster.global.mbarrier::complete_tx::bytes [%0], [%1, {%3, %4, %5, %6}], [%2];" ::"r"(dst), "l"(m), "r"(bar), "r"(c0), "r"(c1), "r"(c2), "r"(c3) : "memory");
}
__device__ __forceinline__ void tma_store_2d(const CUtensorMap* m, uint32_t src, int c0, int c1) {
    asm volatile("cp.async.bulk.tensor.2d.global.shared::cta.bulk_group [%0, {%2, %3}], [%1];" ::"l"(m), "r"(src), "r"(c0), "r"(c1) : "memory");
}
__device__ __forceinline__ void bulk_g2s(uint32_t dst, const void* src, uint32_t bytes, uint32_t bar) {
    asm volatile("cp.async.bulk.shared::cluster.global.mbarrier::complete_tx::bytes [%0], [%1], %2, [%3];" ::"r"(dst), "l"(src), "r"(bytes), "r"(bar) : "memory");
}
__device__ __forceinline__ void bulk_prefetch(const void* p, uint32_t bytes) { asm volatile("cp.async.bulk.prefetch.L2.global [%0], %1;" ::"l"(p), "r"(bytes) : "memory"); }
__device__ __forceinline__ void fence_async_smem() { asm volatile("fence.proxy.async.shared::cta;" ::: "memory"); }
__device__ __forceinline__ void wg_fence() { asm volatile("wgmma.fence.sync.aligned;" ::: "memory"); }
__device__ __forceinline__ void wg_commit() { asm volatile("wgmma.commit_group.sync.aligned;" ::: "memory"); }
template <int N> __device__ __forceinline__ void wg_wait() { asm volatile("wgmma.wait_group.sync.aligned %0;" ::"n"(N) : "memory"); }
__device__ __forceinline__ uint64_t mkdesc(uint32_t lo, uint32_t hi) { return ((uint64_t)hi << 32) | lo; }
__host__ __device__ constexpr uint32_t dhi(uint32_t sbo, uint32_t mode) { return (sbo >> 4) | (mode << 30); }
__host__ __device__ constexpr uint32_t dlo(uint32_t off, uint32_t lbo) { return (off >> 4) + ((lbo >> 4) << 16); }
__device__ __forceinline__ bool elect_one() {
    uint32_t e;
    asm volatile("{\n.reg .pred p;\nelect.sync _|p, 0xffffffff;\nselp.u32 %0, 1, 0, p;\n}" : "=r"(e));
    return e;
}
template <int R> __device__ __forceinline__ void reg_inc() { asm volatile("setmaxnreg.inc.sync.aligned.u32 %0;" ::"n"(R)); }
template <int R> __device__ __forceinline__ void reg_dec() { asm volatile("setmaxnreg.dec.sync.aligned.u32 %0;" ::"n"(R)); }
__device__ __forceinline__ void bar_sync(int id, int n) { asm volatile("bar.sync %0, %1;" ::"r"(id), "r"(n) : "memory"); }
__device__ __forceinline__ void bar_arrive(int id, int n) { asm volatile("bar.arrive %0, %1;" ::"r"(id), "r"(n) : "memory"); }
__device__ __forceinline__ uint32_t pack_bf16(float lo, float hi) { uint32_t r; asm("cvt.rn.bf16x2.f32 %0, %1, %2;" : "=r"(r) : "f"(hi), "f"(lo)); return r; }
__device__ __forceinline__ float bf_lo(uint32_t u) { return __uint_as_float(u << 16); }
__device__ __forceinline__ float bf_hi(uint32_t u) { return __uint_as_float(u & 0xffff0000u); }
__device__ __forceinline__ float bf16r(float v) { return bf_lo(pack_bf16(v, 0.f)); }
__device__ __forceinline__ uint32_t tagw(uint32_t w, uint32_t m, uint32_t tag) { uint32_t r; asm("lop3.b32 %0, %1, %2, %3, 0xb8;" : "=r"(r) : "r"(w), "r"(m), "r"(tag)); return r; }
__device__ __forceinline__ uint32_t tagf(float f, uint32_t tag) { return tagw(__float_as_uint(f), 1u, tag); }
__device__ __forceinline__ uint32_t movm(uint32_t a) { uint32_t d; asm volatile("movmatrix.sync.aligned.m8n8.trans.b16 %0, %1;" : "=r"(d) : "r"(a)); return d; }
__device__ __forceinline__ void mma16816(float (&c)[4], uint32_t a0, uint32_t a1, uint32_t a2, uint32_t a3, uint32_t b0, uint32_t b1) {
    asm volatile("mma.sync.aligned.m16n8k16.row.col.f32.bf16.bf16.f32 {%0,%1,%2,%3}, {%4,%5,%6,%7}, {%8,%9}, {%0,%1,%2,%3};"
                 : "+f"(c[0]), "+f"(c[1]), "+f"(c[2]), "+f"(c[3]) : "r"(a0), "r"(a1), "r"(a2), "r"(a3), "r"(b0), "r"(b1));
}
__device__ __forceinline__ void mma1688(float (&c)[4], uint32_t a0, uint32_t a1, uint32_t b0) {
    asm volatile("mma.sync.aligned.m16n8k8.row.col.f32.bf16.bf16.f32 {%0,%1,%2,%3}, {%4,%5}, {%6}, {%0,%1,%2,%3};"
                 : "+f"(c[0]), "+f"(c[1]), "+f"(c[2]), "+f"(c[3]) : "r"(a0), "r"(a1), "r"(b0));
}
__device__ __forceinline__ uint32_t ld_rlx(const void* p) { uint32_t v; asm volatile("ld.relaxed.gpu.global.u32 %0, [%1];" : "=r"(v) : "l"(p) : "memory"); return v; }
__device__ __forceinline__ uint2 ld_rlx2(const void* p) { uint2 v; asm volatile("ld.relaxed.gpu.global.v2.u32 {%0,%1}, [%2];" : "=r"(v.x), "=r"(v.y) : "l"(p) : "memory"); return v; }
__device__ __forceinline__ uint4 ld_rlx4(const void* p) { uint4 v; asm volatile("ld.relaxed.gpu.global.v4.u32 {%0,%1,%2,%3}, [%4];" : "=r"(v.x), "=r"(v.y), "=r"(v.z), "=r"(v.w) : "l"(p) : "memory"); return v; }
__device__ __forceinline__ uint32_t ld_acq(const void* p) { uint32_t v; asm volatile("ld.acquire.gpu.global.u32 %0, [%1];" : "=r"(v) : "l"(p) : "memory"); return v; }
__device__ __forceinline__ void st_rlx(void* p, uint32_t v) { asm volatile("st.relaxed.gpu.global.u32 [%0], %1;" ::"l"(p), "r"(v) : "memory"); }
__device__ __forceinline__ void st_rlx2(void* p, uint32_t a, uint32_t b) { asm volatile("st.relaxed.gpu.global.v2.u32 [%0], {%1,%2};" ::"l"(p), "r"(a), "r"(b) : "memory"); }
__device__ __forceinline__ void st_rlx4(void* p, uint32_t a, uint32_t b, uint32_t c, uint32_t d) { asm volatile("st.relaxed.gpu.global.v4.u32 [%0], {%1,%2,%3,%4};" ::"l"(p), "r"(a), "r"(b), "r"(c), "r"(d) : "memory"); }
__device__ __forceinline__ uint4 ldg_nc(const void* p) { uint4 v; asm volatile("ld.global.nc.v4.u32 {%0,%1,%2,%3}, [%4];" : "=r"(v.x), "=r"(v.y), "=r"(v.z), "=r"(v.w) : "l"(p)); return v; }
__device__ __forceinline__ uint32_t mism(uint32_t a, uint32_t b, uint32_t tag) { uint32_t r; asm("lop3.b32 %0, %1, %2, %3, 0x7e;" : "=r"(r) : "r"(a), "r"(b), "r"(tag)); return r; }
__device__ __forceinline__ uint32_t mism(const uint4& v, uint32_t tag) { return mism(v.x, v.y, tag) | mism(v.z, v.w, tag); }
__device__ __forceinline__ void prefetch_l2(const void* p) { asm volatile("prefetch.global.L2 [%0];" ::"l"(p)); }
__device__ __forceinline__ void touch256(uint32_t dst, const void* p) { asm volatile("cp.async.ca.shared.global.L2::256B [%0], [%1], 4;" ::"r"(dst), "l"(p) : "memory"); }
__device__ __forceinline__ void nap(int n) {
#pragma unroll 1
    for (int i = 0; i < n; i++) __nanosleep(100);
}
__device__ __forceinline__ uint32_t now() { uint32_t t; asm volatile("mov.u32 %0, %%globaltimer_lo;" : "=r"(t)); return t; }
__device__ __forceinline__ void until(uint32_t t) {
    while (t - now() - 1 < 16384u) __nanosleep(50);
}
__device__ __forceinline__ uint32_t opaque(uint32_t v) { return __shfl_xor_sync(0xffffffffu, v, 0); }
__device__ __forceinline__ void sts4(uint32_t a, uint32_t x, uint32_t y, uint32_t z, uint32_t w) { asm volatile("st.shared.v4.u32 [%0], {%1,%2,%3,%4};" ::"r"(a), "r"(x), "r"(y), "r"(z), "r"(w) : "memory"); }
__device__ __forceinline__ void sts2(uint32_t a, uint32_t x, uint32_t y) { asm volatile("st.shared.v2.u32 [%0], {%1,%2};" ::"r"(a), "r"(x), "r"(y) : "memory"); }
__device__ __forceinline__ uint4 lds4(uint32_t a) { uint4 v; asm volatile("ld.shared.v4.u32 {%0,%1,%2,%3}, [%4];" : "=r"(v.x), "=r"(v.y), "=r"(v.z), "=r"(v.w) : "r"(a) : "memory"); return v; }
__device__ __forceinline__ float4 lds4f(uint32_t a) { float4 v; asm volatile("ld.shared.v4.f32 {%0,%1,%2,%3}, [%4];" : "=f"(v.x), "=f"(v.y), "=f"(v.z), "=f"(v.w) : "r"(a) : "memory"); return v; }
__device__ __forceinline__ uint2 lds2(uint32_t a) { uint2 v; asm volatile("ld.shared.v2.u32 {%0,%1}, [%2];" : "=r"(v.x), "=r"(v.y) : "r"(a) : "memory"); return v; }
__device__ __forceinline__ float2 lds2f(uint32_t a) { float2 v; asm volatile("ld.shared.v2.f32 {%0,%1}, [%2];" : "=f"(v.x), "=f"(v.y) : "r"(a) : "memory"); return v; }
__device__ __forceinline__ uint32_t lds1(uint32_t a) { uint32_t v; asm volatile("ld.shared.u32 %0, [%1];" : "=r"(v) : "r"(a) : "memory"); return v; }
__device__ __forceinline__ float lds1f(uint32_t a) { return __uint_as_float(lds1(a)); }
__device__ __forceinline__ void sts1(uint32_t a, uint32_t v) { asm volatile("st.shared.u32 [%0], %1;" ::"r"(a), "r"(v) : "memory"); }
__device__ __forceinline__ uint32_t redux_max(uint32_t v) { uint32_t r; asm volatile("redux.sync.max.u32 %0, %1, 0xffffffff;" : "=r"(r) : "r"(v)); return r; }
__device__ __forceinline__ float ex2(float x) { float r; asm("ex2.approx.ftz.f32 %0, %1;" : "=f"(r) : "f"(x)); return r; }
__device__ __forceinline__ float rcp(float x) { float r; asm("rcp.approx.ftz.f32 %0, %1;" : "=f"(r) : "f"(x)); return r; }
__device__ __forceinline__ float sigmoidf(float v) { return rcp(1.f + ex2(v * -1.4426950408889634f)); }

template <int TA, int TB>
__device__ __forceinline__ void wgmma_n192(float (&d)[96], uint64_t da, uint64_t db, int acc = 1) {
    asm volatile("{\n.reg .pred p;\nsetp.ne.b32 p, %100, 0;\n"
        "wgmma.mma_async.sync.aligned.m64n192k16.f32.bf16.bf16 "
        "{%0, %1, %2, %3, %4, %5, %6, %7, %8, %9, %10, %11, %12, %13, %14, %15, "
        "%16, %17, %18, %19, %20, %21, %22, %23, %24, %25, %26, %27, %28, %29, %30, %31, "
        "%32, %33, %34, %35, %36, %37, %38, %39, %40, %41, %42, %43, %44, %45, %46, %47, "
        "%48, %49, %50, %51, %52, %53, %54, %55, %56, %57, %58, %59, %60, %61, %62, %63, "
        "%64, %65, %66, %67, %68, %69, %70, %71, %72, %73, %74, %75, %76, %77, %78, %79, "
        "%80, %81, %82, %83, %84, %85, %86, %87, %88, %89, %90, %91, %92, %93, %94, %95}, "
        "%96, %97, p, 1, 1, %98, %99;\n}\n"
        : "+f"(d[0]), "+f"(d[1]), "+f"(d[2]), "+f"(d[3]), "+f"(d[4]), "+f"(d[5]), "+f"(d[6]), "+f"(d[7]),
          "+f"(d[8]), "+f"(d[9]), "+f"(d[10]), "+f"(d[11]), "+f"(d[12]), "+f"(d[13]), "+f"(d[14]), "+f"(d[15]),
          "+f"(d[16]), "+f"(d[17]), "+f"(d[18]), "+f"(d[19]), "+f"(d[20]), "+f"(d[21]), "+f"(d[22]), "+f"(d[23]),
          "+f"(d[24]), "+f"(d[25]), "+f"(d[26]), "+f"(d[27]), "+f"(d[28]), "+f"(d[29]), "+f"(d[30]), "+f"(d[31]),
          "+f"(d[32]), "+f"(d[33]), "+f"(d[34]), "+f"(d[35]), "+f"(d[36]), "+f"(d[37]), "+f"(d[38]), "+f"(d[39]),
          "+f"(d[40]), "+f"(d[41]), "+f"(d[42]), "+f"(d[43]), "+f"(d[44]), "+f"(d[45]), "+f"(d[46]), "+f"(d[47]),
          "+f"(d[48]), "+f"(d[49]), "+f"(d[50]), "+f"(d[51]), "+f"(d[52]), "+f"(d[53]), "+f"(d[54]), "+f"(d[55]),
          "+f"(d[56]), "+f"(d[57]), "+f"(d[58]), "+f"(d[59]), "+f"(d[60]), "+f"(d[61]), "+f"(d[62]), "+f"(d[63]),
          "+f"(d[64]), "+f"(d[65]), "+f"(d[66]), "+f"(d[67]), "+f"(d[68]), "+f"(d[69]), "+f"(d[70]), "+f"(d[71]),
          "+f"(d[72]), "+f"(d[73]), "+f"(d[74]), "+f"(d[75]), "+f"(d[76]), "+f"(d[77]), "+f"(d[78]), "+f"(d[79]),
          "+f"(d[80]), "+f"(d[81]), "+f"(d[82]), "+f"(d[83]), "+f"(d[84]), "+f"(d[85]), "+f"(d[86]), "+f"(d[87]),
          "+f"(d[88]), "+f"(d[89]), "+f"(d[90]), "+f"(d[91]), "+f"(d[92]), "+f"(d[93]), "+f"(d[94]), "+f"(d[95])
        : "l"(da), "l"(db), "n"(TA), "n"(TB), "r"(acc));
}
template <int TA, int TB>
__device__ __forceinline__ void wgmma_n128(float (&d)[64], uint64_t da, uint64_t db, int acc = 1) {
    asm volatile("{\n.reg .pred p;\nsetp.ne.b32 p, %68, 0;\n"
        "wgmma.mma_async.sync.aligned.m64n128k16.f32.bf16.bf16 "
        "{%0, %1, %2, %3, %4, %5, %6, %7, %8, %9, %10, %11, %12, %13, %14, %15, "
        "%16, %17, %18, %19, %20, %21, %22, %23, %24, %25, %26, %27, %28, %29, %30, %31, "
        "%32, %33, %34, %35, %36, %37, %38, %39, %40, %41, %42, %43, %44, %45, %46, %47, "
        "%48, %49, %50, %51, %52, %53, %54, %55, %56, %57, %58, %59, %60, %61, %62, %63}, "
        "%64, %65, p, 1, 1, %66, %67;\n}\n"
        : "+f"(d[0]), "+f"(d[1]), "+f"(d[2]), "+f"(d[3]), "+f"(d[4]), "+f"(d[5]), "+f"(d[6]), "+f"(d[7]),
          "+f"(d[8]), "+f"(d[9]), "+f"(d[10]), "+f"(d[11]), "+f"(d[12]), "+f"(d[13]), "+f"(d[14]), "+f"(d[15]),
          "+f"(d[16]), "+f"(d[17]), "+f"(d[18]), "+f"(d[19]), "+f"(d[20]), "+f"(d[21]), "+f"(d[22]), "+f"(d[23]),
          "+f"(d[24]), "+f"(d[25]), "+f"(d[26]), "+f"(d[27]), "+f"(d[28]), "+f"(d[29]), "+f"(d[30]), "+f"(d[31]),
          "+f"(d[32]), "+f"(d[33]), "+f"(d[34]), "+f"(d[35]), "+f"(d[36]), "+f"(d[37]), "+f"(d[38]), "+f"(d[39]),
          "+f"(d[40]), "+f"(d[41]), "+f"(d[42]), "+f"(d[43]), "+f"(d[44]), "+f"(d[45]), "+f"(d[46]), "+f"(d[47]),
          "+f"(d[48]), "+f"(d[49]), "+f"(d[50]), "+f"(d[51]), "+f"(d[52]), "+f"(d[53]), "+f"(d[54]), "+f"(d[55]),
          "+f"(d[56]), "+f"(d[57]), "+f"(d[58]), "+f"(d[59]), "+f"(d[60]), "+f"(d[61]), "+f"(d[62]), "+f"(d[63])
        : "l"(da), "l"(db), "n"(TA), "n"(TB), "r"(acc));
}
template <int TB>
__device__ __forceinline__ void wgmma_rs_n128(float (&d)[64], uint32_t a0, uint32_t a1, uint32_t a2, uint32_t a3, uint64_t db) {
    asm volatile("{\n.reg .pred p;\nsetp.ne.b32 p, 1, 0;\n"
        "wgmma.mma_async.sync.aligned.m64n128k16.f32.bf16.bf16 "
        "{%0, %1, %2, %3, %4, %5, %6, %7, %8, %9, %10, %11, %12, %13, %14, %15, "
        "%16, %17, %18, %19, %20, %21, %22, %23, %24, %25, %26, %27, %28, %29, %30, %31, "
        "%32, %33, %34, %35, %36, %37, %38, %39, %40, %41, %42, %43, %44, %45, %46, %47, "
        "%48, %49, %50, %51, %52, %53, %54, %55, %56, %57, %58, %59, %60, %61, %62, %63}, "
        "{%64, %65, %66, %67}, %68, p, 1, 1, %69;\n}\n"
        : "+f"(d[0]), "+f"(d[1]), "+f"(d[2]), "+f"(d[3]), "+f"(d[4]), "+f"(d[5]), "+f"(d[6]), "+f"(d[7]),
          "+f"(d[8]), "+f"(d[9]), "+f"(d[10]), "+f"(d[11]), "+f"(d[12]), "+f"(d[13]), "+f"(d[14]), "+f"(d[15]),
          "+f"(d[16]), "+f"(d[17]), "+f"(d[18]), "+f"(d[19]), "+f"(d[20]), "+f"(d[21]), "+f"(d[22]), "+f"(d[23]),
          "+f"(d[24]), "+f"(d[25]), "+f"(d[26]), "+f"(d[27]), "+f"(d[28]), "+f"(d[29]), "+f"(d[30]), "+f"(d[31]),
          "+f"(d[32]), "+f"(d[33]), "+f"(d[34]), "+f"(d[35]), "+f"(d[36]), "+f"(d[37]), "+f"(d[38]), "+f"(d[39]),
          "+f"(d[40]), "+f"(d[41]), "+f"(d[42]), "+f"(d[43]), "+f"(d[44]), "+f"(d[45]), "+f"(d[46]), "+f"(d[47]),
          "+f"(d[48]), "+f"(d[49]), "+f"(d[50]), "+f"(d[51]), "+f"(d[52]), "+f"(d[53]), "+f"(d[54]), "+f"(d[55]),
          "+f"(d[56]), "+f"(d[57]), "+f"(d[58]), "+f"(d[59]), "+f"(d[60]), "+f"(d[61]), "+f"(d[62]), "+f"(d[63])
        : "r"(a0), "r"(a1), "r"(a2), "r"(a3), "l"(db), "n"(TB));
}
template <int TA, int TB>
__device__ __forceinline__ void wgmma_n8(float (&d)[4], uint64_t da, uint64_t db, int acc = 1) {
    asm volatile("{\n.reg .pred p;\nsetp.ne.b32 p, %8, 0;\n"
        "wgmma.mma_async.sync.aligned.m64n8k16.f32.bf16.bf16 "
        "{%0, %1, %2, %3}, "
        "%4, %5, p, 1, 1, %6, %7;\n}\n"
        : "+f"(d[0]), "+f"(d[1]), "+f"(d[2]), "+f"(d[3])
        : "l"(da), "l"(db), "n"(TA), "n"(TB), "r"(acc));
}

__device__ __forceinline__ uint32_t norm_pair(uint32_t u, float m, float rinv) {
    uint32_t d = pack_bf16(bf_lo(u) - m, bf_hi(u) - m);
    return pack_bf16(bf_lo(d) * rinv, bf_hi(d) * rinv);
}

__global__ void __launch_bounds__(512, 1)
fused_kernel(int by_sm, const __nv_bfloat16* __restrict__ x, const __nv_bfloat16* __restrict__ wqkv, const __nv_bfloat16* __restrict__ wr,
             Scratch* const S, const char* __restrict__ wg, const char* __restrict__ wu, const char* __restrict__ wd, const char* __restrict__ wo,
             const __grid_constant__ CUtensorMap mw, const __grid_constant__ CUtensorMap mx, const __grid_constant__ CUtensorMap mwo,
             const __grid_constant__ CUtensorMap mxs, const __grid_constant__ CUtensorMap mout, const __grid_constant__ CUtensorMap mgu, const __grid_constant__ CUtensorMap mwd) {
    extern __shared__ __align__(1024) uint8_t smem[];
    constexpr uint32_t sb = 1024, bars = sb + OFF_BAR, sd = sb >> 4;
    const int tid = threadIdx.x, lane = tid & 31, warp = __shfl_sync(0xffffffffu, tid >> 5, 0);
    uint32_t smid;
    asm("mov.u32 %0, %%smid;" : "=r"(smid));
    const int T = smid >> 1, T8 = T < 32 ? T : T + 1 + (((T - 32) * 37) >> 8), pr = T < 60 ? (~T8 & 7) * 8 + (T8 >> 3) : T < 62 ? T + 4 : T - 2;
    const int fb = by_sm ? pr * 2 + (smid & 1) : blockIdx.x, kc = fb >> 4, c2 = fb & 15;
    const int b = (fb & ~31) | (fb & 1) << 4 | (fb & 31) >> 1;
    const int mt = b >> 4, nt = b & 15, hp = b & 1, cb = nt >> 1;
    const int par = mt >> 2, j0 = (mt & 3) * 256;
    uint8_t* const g_o = S->o;

    if (fb >= 128) {
        if (fb > 128) { nap(16); TS_END(); return; }
        const uint32_t tag = (ld_rlx(&S->epoch) & 1) - 1;
        if (tid < 8) st_rlx2(&S->sel[tid], ~tag, ~tag);
        uint4 ra, rb;
#pragma unroll 1
        for (int it = 0; it < SPIN_LIMIT; it++) {
            ra = ld_rlx4(&S->rec[tid * 2]); rb = ld_rlx4(&S->rec[1024 + tid * 2]);
            if (!((mism(ra.x, ra.z, tag) | mism(rb.x, rb.z, tag)) & 0x8000u)) break;
        }
        __syncwarp();
        TSC(tid == 0, 31);
        sts4(sb + 1024 + tid * 16, ra.y, rb.y, ra.w, rb.w);
        uint4 k = make_uint4(ra.x, ra.z, rb.x, rb.z);
        uint32_t cand;
#pragma unroll 1
        for (int pass = 0; pass < 2; pass++) {
            const uint32_t a0 = max(k.x, k.y), a1 = min(k.x, k.y), a2 = max(k.z, k.w), a3 = min(k.z, k.w), c1 = min(a0, a2), c2 = max(a1, a3);
            k = make_uint4(max(a0, a2), max(c1, c2), min(c1, c2), min(a1, a3));
#pragma unroll
            for (int r = 0; r < 8; r++) {
                const uint32_t m = redux_max(k.x);
                if (lane == r) cand = m;
                if (k.x == m) k = make_uint4(k.y, k.z, k.w, 0);
            }
            if (pass) break;
            if (lane < 8) sts1(sb + (warp * 8 + lane) * 4, cand);
            __syncthreads();
            if (warp) { TS_END(); return; }
            k = lds4(sb + lane * 16);
        }
        if (lane < 8) st_rlx2(&S->sel[lane], cand, lds1(sb + 1024 + (~cand & 0x7ffu) * 4));
        TSC(tid == 0, 20);
        TS_END();
        return;
    }
    auto kblock = [&](int p) { return p; };
    auto load_stage = [&](int p, uint32_t so, int bi, int lag) {
        const int kc0 = kblock(p) * 64;
        const uint32_t fa = bars + 8 * (B_FULLA + bi), fb = bars + 8 * (B_FULLB + bi);
        mbar_expect_tx(fa, 40960);
        if (lag < 0) tma_3d(sb + so + 16384, &mw, fa, nt * 64, kc0, 0);
        tma_4d(sb + so, &mx, fa, par * 1024 + kc0, 0, (j0 >> 5) + 4, 0);
        mbar_expect_tx(fb, 16384);
        tma_4d(sb + so + 40960, &mx, fb, par * 1024 + kc0, 0, j0 >> 5, 0);
        if (lag >= 0) { nap(lag); tma_3d(sb + so + 16384, &mw, fa, nt * 64, kc0, 0); }
    };
    auto prefetch_w = [&](int part, int p0) { prefetch_l2(wqkv + (size_t)(kblock(p0 + (lane >> 3)) * 64 + mt * 8 + (lane & 7)) * 3072 + part * 1024 + nt * 64); };
    auto prefetch_x = [&](int c) { prefetch_l2(x + (size_t)((j0 + nt * 16 + (lane >> 1)) * 2 + par) * 1024 + c * 128 + (lane & 1) * 64); };
    if (warp == 12) {
        if (elect_one()) {
#pragma unroll
            for (int i = 0; i < B_ROW; i++) mbar_init(bars + 8 * i, 1);
            asm volatile("fence.mbarrier_init.release.cluster;" ::: "memory");
            load_stage(0, STAGE, 0, -1);
        }
    } else {
        if (warp > 12) {
            if (lane < 8) prefetch_w(warp - 13, 0);
        } else if (warp >= 10 && warp < 10 + N_X0) prefetch_x(warp - 10);
        if (warp == 0 && elect_one()) {
#pragma unroll
            for (int i = B_ROW; i < B_WOFULL; i++) mbar_init(bars + 8 * i, i >= B_FFULL && i < B_FEMPTY ? 5 : 1);
            mbar_expect_tx(bars + 8 * (B_ROW + 4), 2048);
            bulk_g2s(sb + OFF_FA, wr, 2048, bars + 8 * (B_ROW + 4));
        }
        if (warp == 1 && elect_one()) {
#pragma unroll
            for (int i = B_EMPTY; i < NBAR; i++) mbar_init(bars + 8 * i, i < B_UPD ? 2 : i < B_AUX ? 4 : i == B_AUX ? 7 : i == B_CSDONE ? 3 : 8);
        }
    }
    __syncthreads();
    if (warp == 12 && elect_one()) {
#pragma unroll 1
        for (int p = 1; p < 3; p++) { nap(N_S1); load_stage(p, p == 2 ? 0 : 2 * STAGE, p, -1); }
    }
    __syncwarp();

    if (warp >= 12) {
        reg_dec<24>();
        if (warp > 12) {
            const int p = warp - 13;
            const uint32_t t0 = now();
#pragma unroll 1
            for (int i = 0; i < 4; i++) {
                until(t0 + (p == 0 ? T_X + i * D_X : p == 1 ? T_W + i * D_W : T_ROW + i * D_R));
                if (p == 0) { prefetch_x(min(N_X0 + 2 * i, 7)); prefetch_x(min(N_X0 + 1 + 2 * i, 7)); }
                else if (p == 1) {
#pragma unroll 1
                    for (int c = 0; c < 3; c++) prefetch_w(c, min(3 + i * 4, 12));
                } else if (elect_one()) {
                    mbar_expect_tx(bars + 8 * (B_ROW + i), 8192);
                    tma_3d(sb + OFF_FW + i * 8192, &mxs, bars + 8 * (B_ROW + i), 0, j0 + nt * 16, par * 16 + i * 4);
                }
            }
            until(t0 + T_CS);
            const char* wp = (const char*)(wqkv + (size_t)(mt * 8 + (lane >> 3)) * 3072 + p * 1024 + nt * 64 + (lane & 7) * 8);
            const uint32_t stg = sb + OFF_FW + 32768 + p * 4096 + lane * 16;
            float c[8];
#pragma unroll
            for (int i = 0; i < 8; i++) c[i] = 0.f;
#pragma unroll 1
            for (int n = 0; n < 10; n++) {
                const uint32_t buf = stg + (n & 1) * 2048;
                if (n >= 2) {
                    asm volatile("cp.async.wait_group 1;" ::: "memory");
#pragma unroll 2
                    for (int i = 0; i < 4; i++) {
                        const uint4 v = lds4(buf + i * 512);
                        c[0] += bf_lo(v.x); c[1] += bf_hi(v.x); c[2] += bf_lo(v.y); c[3] += bf_hi(v.y);
                        c[4] += bf_lo(v.z); c[5] += bf_hi(v.z); c[6] += bf_lo(v.w); c[7] += bf_hi(v.w);
                    }
                }
                if (n < 8) {
                    const char* src = wp + (size_t)kblock(2 * n) * 64 * 6144;
#pragma unroll
                    for (int i = 0; i < 4; i++) asm volatile("cp.async.ca.shared.global [%0], [%1], 16;" ::"r"(buf + i * 512), "l"(src + ((i >> 1) * 64 + (i & 1) * 4) * 6144) : "memory");
                }
                asm volatile("cp.async.commit_group;" ::: "memory");
            }
            sts4(stg + lane * 16, __float_as_uint(c[0]), __float_as_uint(c[1]), __float_as_uint(c[2]), __float_as_uint(c[3]));
            sts4(stg + lane * 16 + 16, __float_as_uint(c[4]), __float_as_uint(c[5]), __float_as_uint(c[6]), __float_as_uint(c[7]));
            bar_sync(13, 128);
            const uint32_t tag = lds1(sb + OFF_TAG);
            float* gcs = &S->cs[0][p * 1024 + nt * 64];
            {
                const float2 a0 = lds2f(stg - lane * 8), a1 = lds2f(stg - lane * 8 + 256), a2 = lds2f(stg - lane * 8 + 512), a3 = lds2f(stg - lane * 8 + 768);
                st_rlx2(gcs + mt * 3072 + lane * 2, tagf((a0.x + a1.x) + (a2.x + a3.x), tag), __float_as_uint((a0.y + a1.y) + (a2.y + a3.y)));
            }
            __syncwarp();
            if (lane == 0) mbar_arrive(bars + 8 * B_CSDONE);
            TSC(warp == 13 && lane == 0, 19);
            {
                uint4 v[4];
                const float* src = gcs + (lane >> 4) * 4 * 3072 + (lane & 15) * 4;
#pragma unroll 1
                for (int it = 0; it < SPIN_LIMIT; it++) {
#pragma unroll
                    for (int m = 0; m < 4; m++) v[m] = ld_rlx4(src + m * 3072);
                    if (!((mism(v[0].x, v[1].x, tag) | mism(v[2].x, v[3].x, tag)) & 1)) break;
                }
                __syncwarp();
#pragma unroll
                for (int c = 0; c < 4; c++) {
                    const float a = (__uint_as_float((&v[0].x)[c]) + __uint_as_float((&v[1].x)[c])) + (__uint_as_float((&v[2].x)[c]) + __uint_as_float((&v[3].x)[c]));
                    (&v[0].x)[c] = __float_as_uint(a + __shfl_xor_sync(0xffffffffu, a, 16));
                }
                const uint32_t ca = sb + OFF_CS + p * 384 + ((lane & 15) >> 1) * 48 + (lane & 1) * 8;
#pragma unroll 1
                for (int r = 0; r < 3; r++) {
                    const uint32_t u0 = pack_bf16(__uint_as_float(v[0].x), __uint_as_float(v[0].y)), u1 = pack_bf16(__uint_as_float(v[0].z), __uint_as_float(v[0].w));
                    sts2(ca + r * 16, u0, u1);
                    v[0].x = __float_as_uint(__uint_as_float(v[0].x) - bf_lo(u0)); v[0].y = __float_as_uint(__uint_as_float(v[0].y) - bf_hi(u0));
                    v[0].z = __float_as_uint(__uint_as_float(v[0].z) - bf_lo(u1)); v[0].w = __float_as_uint(__uint_as_float(v[0].w) - bf_hi(u1));
                }
                if (lane < 20) sts1(sb + OFF_CS + 1152 + lane * 4, 0);
                fence_async_smem();
            }
            __syncwarp();
            if (lane == 0) mbar_arrive(bars + 8 * B_AUX);
            TSC(warp == 13 && lane == 0, 21);
            mbar_wait(bars + 8 * B_PART, 0);
            mbar_wait(bars + 8 * (B_EMPTY + 2), 0);
            if (p == 0) {
                uint4 v[4];
#pragma unroll
                for (int c = 0; c < 4; c++) v[c] = make_uint4(0, 0, 0, 0);
                const uint32_t* hsrc = &S->halo[b - 16][lane * 4];
#pragma unroll 1
                for (int it = 0; it < SPIN_LIMIT && j0; it++) {
#pragma unroll
                    for (int c = 0; c < 4; c++) v[c] = ld_rlx4(hsrc + c * 128);
                    if (!((mism(v[0].x, v[1].x, tag) | mism(v[2].x, v[3].x, tag)) & 1)) break;
                }
#pragma unroll
                for (int c = 0; c < 4; c++) sts4(sb + OFF_HALO + c * 512 + lane * 16, v[c].x, v[c].y, v[c].z, v[c].w);
                __syncwarp();
                bar_arrive(3, 64);
                TSC(TIMING == 11 && lane == 0, 34);
            } else {
                const int w = p - 1;
                const uint8_t* osrc = g_o + (size_t)((mt * 2 + hp) * 2 + w) * 131072;
                const bool far = w > hp && j0 && lane >= 16;
                const uint32_t* hsrc = &S->hint[mt * 16 + (lane & 15) - (far ? 16 : 0)][0];
                const uint32_t tn = now();
                if (lane == 0 && !w) st_rlx(&S->hint[b][0], tagw(tn, 1u, tag));
                uint32_t hv;
#pragma unroll 1
                for (int it = 0; it < SPIN_LIMIT; it++) {
                    hv = ld_rlx(hsrc);
                    if (!__any_sync(0xffffffffu, (hv ^ tag) & 1)) break;
                }
                TSC(TIMING == 11 && lane == 0, 32 + w);
                hv = redux_max(hv - tn + (far ? 0x40000000u + T_H : 0x40000000u)) + tn - 0x40000000u + T_O + w * T_O1;
                mbar_wait(bars + 8 * (w ? B_AST : B_G1DONE), 0);
                if (elect_one()) {
#pragma unroll 1
                    for (int st = 0; st < 8; st++) {
                        const uint32_t full = bars + 8 * (B_OFULL + 8 * w + st);
                        if (st == 2 && !w) { until(hv + T_GO); mbar_arrive(bars + 8 * B_GO); }
                        if (st >= 2) mbar_wait(full + 8 * (B_DONE - B_OFULL - 2), 0);
                        if (st < 3) until(hv + (st == 2 ? T_S2 : st * T_S1));
                        TSC(st == 0, 28 + w);
                        mbar_expect_tx(full, 16384);
                        bulk_g2s(sb + (w ? OFF_O1 : OFF_O0) + (st & 1) * 16384, osrc + st * 16384, 16384, full);
                    }
                }
            }
            TS_END();
            return;
        }
        if (elect_one()) {
            auto load_wo = [&](int s, int ws) {
                mbar_expect_tx(bars + 8 * (B_WOFULL + s), 32768);
                tma_4d(sb + OFF_WO + ws * 32768, &mwo, bars + 8 * (B_WOFULL + s), 0, s * 8, 0, cb * 2);
            };
            uint32_t so = STAGE, ph = 0, cnt = PF_CNT;
            int bi = 0, q = 0;
            if (smem_u32(smem) != sb) __trap();
#pragma unroll 1
            for (int i = B_WOFULL; i < B_OFULL; i++) mbar_init(bars + 8 * i, 1);
            const char* pf = (b < 64 ? wg : wu) + (b & 63) * 7168;
#pragma unroll 1
            for (int p = 3; p < 16; p++) {
                mbar_wait(bars + 8 * (B_EMPTY + bi), ph);
                load_stage(p, so, bi, W_LAG);
#pragma unroll 1
                for (int e = q + (cnt & 3); q < e; q++) {
                    if (q == 16) pf = wd + mt * 7 * 131072 + nt * 8192;
                    if (q == 23) pf = wo + b * 8192;
                    bulk_prefetch(pf, q < 16 ? 7168 : 8192);
                    pf += q < 16 ? 64 * 7168 : q < 23 ? 131072 : 1048576;
                }
                cnt >>= 2;
                so = so == 2 * STAGE ? 0 : so + STAGE;
                if (++bi == 3) { bi = 0; ph ^= 1; }
            }
            TS(27);
            int ws = 1;
#pragma unroll 1
            for (int i = 0; i < 8; i++) {
                if (i == 1) {
                    mbar_wait(bars + 8 * (B_EMPTY + 2), 0);
                    mbar_expect_tx(bars + 8 * B_F2FULL, 8192);
                    tma_2d(sb + OFF_F2X, &mwd, bars + 8 * B_F2FULL, DBG_F2 * c2 * 64, DBG_F2 * kc * 448);
#pragma unroll 1
                    for (int c = 0; c < 2; c++) {
                        if (c) mbar_wait(bars + 8 * XR_GATE, 0);
                        mbar_expect_tx(bars + 8 * B_XR, 16384);
                        tma_4d(sb + c * STAGE, &mx, bars + 8 * B_XR, DBG_XR * (par * 1024 + cb * 128 + c * 64), 0, DBG_XR * ((j0 >> 5) + hp * 4), 0);
                    }
                } else {
                    mbar_wait(bars + 8 * (i == 0 ? B_EMPTY + 1 : i == 2 ? B_F2DONE : B_DONE - NWO + i), 0);
                    if (i) mbar_wait(bars + 8 * (i == 2 ? B_OFULL : B_DONE + 8 - NWO + i), 0);
                }
                load_wo(i < 2 ? 1 - i : i, i == 1 ? 0 : ws);
                if (i != 1 && ++ws == NWO) ws = 0;
            }
        }
        TS_END();
    } else if (warp >= 8) {
        reg_dec<40>();
        const int p = warp - 8;
        const bool f1 = fb < 112;
        auto ffn_w = [&](int n, int s) {
            const uint32_t dst = sb + OFF_FW + s * 16384;
            if (n < 8) {
                mbar_expect_tx(bars + 8 * (B_FFULL + s), 16384);
                tma_3d(dst, &mgu, bars + 8 * (B_FFULL + s), DBG_F1 * fb * 32, n * 128, 0);
            } else {
                mbar_expect_tx(bars + 8 * B_F2FULL, 16384);
                tma_2d(dst, &mwd, bars + 8 * B_F2FULL, DBG_F2 * c2 * 64, DBG_F2 * kc * 448 + 64 + s * 128);
                tma_2d(dst + 8192, &mwd, bars + 8 * B_F2FULL, DBG_F2 * c2 * 64, DBG_F2 * kc * 448 + 128 + s * 128);
            }
        };
        const uint32_t epoch = __shfl_sync(0xffffffffu, ld_rlx(&S->epoch), 0), tag = (epoch & 1) - 1;
        float s1 = 0.f, s2 = 0.f, sr = 0.f, sw = 0.f, sh = 0.f;
        {
            const uint32_t xa = sb + OFF_FW + p * 512 + lane * 16, wa = sb + OFF_FA + (((p * 4 + (lane >> 3)) ^ lane) & 7) * 16;
            mbar_wait(bars + 8 * (B_ROW + 4), 0);
#pragma unroll 1
            for (int i = 0; i < 4; i++) {
                const uint4 q = lds4(sb + OFF_FA + i * 512 + lane * 16);
                sw += ((bf_lo(q.x) + bf_hi(q.x)) + (bf_lo(q.y) + bf_hi(q.y))) + ((bf_lo(q.z) + bf_hi(q.z)) + (bf_lo(q.w) + bf_hi(q.w)));
            }
#pragma unroll 1
            for (int o = 1; o < 32; o <<= 1) sw += __shfl_xor_sync(0xffffffffu, sw, o);
            {
                float c1 = 0.f, c2 = 0.f, cr = 0.f;
#pragma unroll 1
                for (int q = 0; q < 4; q++) {
                mbar_wait(bars + 8 * (B_ROW + q), 0);
                TSC(tid == 256 && q == 3, 17);
#pragma unroll
                for (int i = 0; i < 4; i++) {
                    const uint4 u = lds4(xa + q * 8192 + i * 2048), w4 = lds4(wa + q * 512 + i * 128);
                    const float a0 = bf_lo(u.x), a1 = bf_hi(u.x), a2 = bf_lo(u.y), a3 = bf_hi(u.y), a4 = bf_lo(u.z), a5 = bf_hi(u.z), a6 = bf_lo(u.w), a7 = bf_hi(u.w);
                    s1 += a0 + a1; c1 += a4 + a5; s1 += a2 + a3; c1 += a6 + a7;
                    s2 = fmaf(a0, a0, s2); c2 = fmaf(a4, a4, c2); sr = fmaf(a0, bf_lo(w4.x), sr); cr = fmaf(a4, bf_lo(w4.z), cr);
                    s2 = fmaf(a1, a1, s2); c2 = fmaf(a5, a5, c2); sr = fmaf(a1, bf_hi(w4.x), sr); cr = fmaf(a5, bf_hi(w4.z), cr);
                    s2 = fmaf(a2, a2, s2); c2 = fmaf(a6, a6, c2); sr = fmaf(a2, bf_lo(w4.y), sr); cr = fmaf(a6, bf_lo(w4.w), cr);
                    s2 = fmaf(a3, a3, s2); c2 = fmaf(a7, a7, c2); sr = fmaf(a3, bf_hi(w4.y), sr); cr = fmaf(a7, bf_hi(w4.w), cr);
                }
                }
                s1 += c1; s2 += c2; sr += cr;
            }
#pragma unroll 1
            for (int pass = 0;; pass++) {
#pragma unroll
                for (int o = 1; o < 8; o <<= 1) {
                    s1 += __shfl_xor_sync(0xffffffffu, s1, o); s2 += __shfl_xor_sync(0xffffffffu, s2, o); sr += __shfl_xor_sync(0xffffffffu, sr, o);
                }
                s1 *= 1.f / 1024.f;
                s2 = fmaf(-s1, s1, s2 * (1.f / 1024.f));
                if (!__any_sync(0xffffffffu, !pass && s1 * s1 > 256.f * s2)) break;
                sh = bf16r(s1); s1 = 0.f; s2 = 0.f; sr = 0.f;
#pragma unroll 1
                for (uint32_t o = 0; o < 2048; o = opaque(o + ((o & 12) == 12 ? 116 : 4))) {
                    const uint32_t u = lds1(xa + (o >> 7) * 2048 + (o & 12)), q = lds1(wa + o);
                    const float a0 = bf_lo(u) - sh, a1 = bf_hi(u) - sh;
                    s1 += a0 + a1; s2 = fmaf(a0, a0, fmaf(a1, a1, s2)); sr = fmaf(a0, bf_lo(q), fmaf(a1, bf_hi(q), sr));
                }
            }
        }
        const int ta = opaque(tid) - 256, lane = ta & 31, g = lane >> 2, t = lane & 3;
        {
            if ((lane & 7) == 0) {
                const int s = b * 16 + p * 4 + (lane >> 3);
                const float mb = bf16r(sh + s1);
                float den;
                asm("sqrt.approx.f32 %0, %1;" : "=f"(den) : "f"(bf16r(bf16r(s2) + 1e-5f)));
                den = bf16r(den);
                uint32_t rb = pack_bf16(fmaf(sh - mb, sw, sr) * rcp(den), 0.f);
                if (rb == 0x8000u) rb = 0;
                uint32_t ord = (rb & 0x8000u) ? (~rb & 0xffffu) : (rb | 0x8000u);
                if ((rb & 0x7fffu) > 0x7f80u) ord = 0;
                st_rlx2(&S->rec[s], (ord << 16) | (tag & 0x8000u) | (0x47ffu - (s & 1023) * 2 - par), pack_bf16(mb, den));
            }
            if (ta < 48) st_rlx4(&S->cs[mt][(ta >> 4) * 1024 + nt * 64 + (ta & 15) * 4], ~tag, ~tag, ~tag, ~tag);
            st_rlx4(&S->ypart[kc][ta >> 4][c2 * 64 + (ta & 15) * 4], ~tag, ~tag, ~tag, ~tag);
            if (p == 3 && f1) st_rlx4(&S->h[fb * 128 + lane * 4], ~tag, ~tag, ~tag, ~tag);
            if (ta < 2) st_rlx4(&S->hint[b][ta * 4], ~tag, ~tag, ~tag, ~tag);
            st_rlx4(&S->halo[b][ta * 4], ~tag, ~tag, ~tag, ~tag);
            if (elect_one()) {
#pragma unroll 1
                for (int i = B_OFULL + p; i < B_EMPTY; i += 4) mbar_init(bars + 8 * i, 1);
            }
            bar_sync(12, 128);
            if (p == 1) sts1(sb + OFF_ROWMAP + lane * 4, 0xffffffffu);
            if (p == 0) {
                if (lane == 0) {
                    sts1(sb + OFF_TAG, tag);
                    if (f1 && EARLY_FILL > 0) ffn_w(0, 0);
                }
                __syncwarp();
                bar_arrive(13, 128);
            }
            TSC(ta == 0, 18);
        }
        {
            uint2 r[3];
            const uint2* src = &S->rec[mt * 256 + ta];
            const int l2 = ta < 8 && j0 ? -8 : 0;
#pragma unroll 1
            for (int it = 0; it < SPIN_LIMIT; it++) {
                r[0] = ld_rlx2(src + l2); r[1] = ld_rlx2(src); r[2] = ld_rlx2(src + 128);
                if (!((mism(r[0].x, r[1].x, tag) | (r[2].x ^ tag)) & 0x8000u)) break;
            }
#pragma unroll
            for (int n = 0; n < 3; n++)
                if (n || ta < 8) sts2(sb + OFF_STAT + (n ? n * 1024 - 960 : 0) + ta * 8, (r[n].y << 16) ^ 0x80000000u, __float_as_uint(rcp(bf_hi(r[n].y))));
        }
        __syncwarp();
        if (lane == 0) mbar_arrive(bars + 8 * B_AUX);
        TSC(ta == 0, 30);
        if (EARLY_FILL > 1 && f1 && p == 0 && elect_one()) ffn_w(1, 1);
        uint2 sel;
#pragma unroll 1
        for (int it = 0; it < SPIN_LIMIT; it++) {
            sel = ld_rlx2(&S->sel[lane & 7]);
            if (!__any_sync(0xffffffffu, (sel.x ^ tag) & 0x8000u)) break;
            __nanosleep(POLL_NS);
        }
        TSC(ta == 0, 26);
        if (b == 0 && ta == 0) st_rlx(&S->epoch, epoch + 1);
        {
            const __nv_bfloat16* xp = x + (~sel.x & 0x7ffu) * 1024 + (ta >> 3) * 8;
            const float mb = bf_lo(sel.y), rinv = rcp(bf_hi(sel.y));
            uint4 v = ldg_nc(xp);
            int s = f1 ? 0 : 2;
#pragma unroll 1
            for (int n = f1 ? 0 : 8; n < (p ? 8 : 11); n++) {
                mbar_wait(bars + 8 * (f1 ? B_FEMPTY + s : B_PART), f1 && (n < 3 || (n >= 6 && n < 9)));
                if (p == 0 && s == 2) mbar_wait(bars + 8 * B_CSDONE, 0);
                if (p == 0 && n >= EARLY_FILL && elect_one()) ffn_w(n, s);
                if (n < 8) {
                    sts4(sb + OFF_FA + s * 2048 + ta * 16, norm_pair(v.x, mb, rinv), norm_pair(v.y, mb, rinv), norm_pair(v.z, mb, rinv), norm_pair(v.w, mb, rinv));
                    fence_async_smem();
                    __syncwarp();
                    if (lane == 0) mbar_arrive(bars + 8 * (B_FFULL + s));
                    v = ldg_nc(xp + ((n + 1) & 7) * 128);
                }
                if (++s == 3) s = 0;
            }
        }
        mbar_wait(bars + 8 * B_PART, 0);
        if (f1 && p >= 2) {
            const uint32_t pa = sb + OFF_FA + (ta - 64) * 16, go = wu < wg ? 1024 : 0;
            const float4 g0 = lds4f(pa + go), g1 = lds4f(pa + 2048 + go), u0 = lds4f(pa + (go ^ 1024)), u1 = lds4f(pa + 2048 + (go ^ 1024));
            float hv[4];
#pragma unroll
            for (int c = 0; c < 4; c++) {
                const float ga = bf16r((&g0.x)[c] + (&g1.x)[c]), up = bf16r((&u0.x)[c] + (&u1.x)[c]);
                hv[c] = bf16r(ga * sigmoidf(ga)) * up;
            }
#pragma unroll
            for (int hh = 0; hh < 2; hh++) {
                const float o = __shfl_xor_sync(0xffffffffu, (g & 1) ? hv[2 * hh] : hv[2 * hh + 1], 4);
                st_rlx(&S->h[(fb * 4 + (p & 1) * 2 + hh) * 32 + (2 * t + (g & 1)) * 4 + (g >> 1)],
                       tagw((g & 1) ? pack_bf16(o, hv[2 * hh + 1]) : pack_bf16(hv[2 * hh], o), g < 2, tag));
            }
            TSC(ta == 64, 22);
        }
        {
            uint4 hq[4];
            const uint32_t* hp4 = S->h + kc * 1792 + ta * 4;
#pragma unroll 1
            for (int it = 0; it < SPIN_LIMIT; it++) {
#pragma unroll
                for (int n = 0; n < 4; n++) hq[n] = ld_rlx4(hp4 + (n < 3 ? n * 512 : p < 2 ? 1536 : 0));
                if (!((mism(hq[0].x, hq[1].x, tag) | mism(hq[2].x, hq[3].x, tag)) & 1)) break;
            }
            mbar_wait(bars + 8 * B_G1DONE, 0);
            bar_sync(12, 128);
#pragma unroll
            for (int n = 0; n < 4; n++) sts4(sb + OFF_FA + ta * 16 + (n < 3 ? n * 2048 : p < 2 ? 6144 : 0), hq[n].x, hq[n].y, hq[n].z, hq[n].w);
            fence_async_smem();
            bar_sync(12, 128);
            TSC(ta == 0, 25);
            mbar_wait(bars + 8 * B_F2FULL, 0);
            mbar_wait(bars + 8 * B_ATT, 0);
            float acc[4] = {0.f, 0.f, 0.f, 0.f};
            uint32_t da = sd + dlo(OFF_F2X, 8192), db = sd + dlo(OFF_FA, 128);
#pragma unroll 1
            for (int q = 0; q < 7; q++) {
                wg_fence();
#pragma unroll
                for (int j = 0; j < 4; j++) wgmma_n8<1, 0>(acc, mkdesc(da + j * 128, dhi(1024, 1)), mkdesc(db + j * 16, dhi(128, 0)));
                wg_commit();
                da = sd + dlo(OFF_FW, 8192) + q * 512; db += 64;
            }
            wg_wait<0>();
            if (ta == 0) mbar_arrive(bars + 8 * B_F2DONE);
#pragma unroll
            for (int c = 0; c < 4; c++) st_rlx(&S->ypart[kc][2 * t + (c & 1)][c2 * 64 + p * 16 + (c >> 1) * 8 + g], tagf(acc[c], tag));
            TSC(ta == 0, 23);
            bar_sync(12, 128);
        }
#pragma unroll 1
        for (int j = 2 * p; j < 2 * p + 2; j++) {
            const uint32_t kj = __shfl_sync(0xffffffffu, sel.x, j);
            const int row = 0x7ff - (kj & 0x7ffu), jj = (row >> 1) - j0 - hp * 128;
            float a0 = 0.f, a1 = 0.f, a2 = 0.f, a3 = 0.f, sig = 0.f;
            if ((row & 1) == par && jj >= 0 && jj < 128) {
                sig = bf16r(sigmoidf(__uint_as_float(((int)kj < 0 ? kj ^ 0x80000000u : ~kj) & 0xffff0000u)));
#pragma unroll 1
                for (int hh = 0; hh < 8; hh += 4) {
                    uint4 v[4];
#pragma unroll 1
                    for (int it = 0; it < SPIN_LIMIT; it++) {
#pragma unroll
                        for (int m = 0; m < 4; m++) v[m] = ld_rlx4(&S->ypart[hh + m][j][cb * 128 + lane * 4]);
                        if (!((mism(v[0], tag) | mism(v[1], tag) | mism(v[2], tag) | mism(v[3], tag)) & 1)) break;
                    }
#pragma unroll
                    for (int m = 0; m < 4; m++) { a0 += __uint_as_float(v[m].x); a1 += __uint_as_float(v[m].y); a2 += __uint_as_float(v[m].z); a3 += __uint_as_float(v[m].w); }
                }
                asm volatile("st.shared.u8 [%0], %1;" ::"r"(sb + OFF_ROWMAP + jj), "r"(j) : "memory");
            }
            sts2(sb + OFF_FA + (lane >> 1) * 128 + j * 16 + (lane & 1) * 8, pack_bf16(bf16r(a0) * sig, bf16r(a1) * sig), pack_bf16(bf16r(a2) * sig, bf16r(a3) * sig));
        }
        fence_async_smem();
        __syncwarp();
        if (lane == 0) mbar_arrive(bars + 8 * B_UPD);
        TSC(ta == 0, 24);
        TS_END();
    } else {
        reg_inc<224>();
        const int w = warp >> 2, wi = warp & 3, tw = (1 - w) * 4 + wi;
        const bool elect = (tid & 127) == 0;
        const uint32_t ln = opaque(lane), g = ln >> 2, t = ln & 3;
        uint32_t tag, ow[8][4];
        auto store_o = [&](int f0, int f1) {
            uint8_t* ob = g_o + (size_t)((mt * 2 + 1 - w) * 2 + 1 - (wi >> 1)) * 131072 + nt * 1024 + (wi & 1) * 512 + ln * 4;
#pragma unroll
            for (int f = f0; f < f1; f++)
#pragma unroll
                for (int i = 3; i >= 0; i--)
                    st_rlx(ob + f * 16384 + i * 128, ow[f][i]);
        };
        {
            float acc[2][96];
            const uint32_t sta = opaque(sb + OFF_STAT + tw * 256 + 64 + g * 8);
            {
                float fa[4] = {0.f, 0.f, 0.f, 0.f};
                uint32_t so = STAGE >> 4, bo = bars, ph = 0;
                const uint32_t dx0 = sd + dlo(w ? 40960 : 0, 16), dw0 = sd + dlo(16384, 8192);
                int p = 0;
                auto step = [&](bool ffn, int fs, uint32_t fph, bool last) {
                    mbar_wait(bo + 8 * B_FULLA, ph);
                    if (w) mbar_wait(bo + 8 * B_FULLB, ph);
                    TSC(TIMING == 9 && elect && p >= 11, 32 + (p - 11) * 6 + w * 3);
                    if (ffn) mbar_wait(bars + 8 * (B_FFULL + fs), fph);
                    TSC(TIMING == 9 && elect && p >= 11, 33 + (p - 11) * 6 + w * 3);
                    TSC(elect && p == 0, 1 + 8 * w);
                    bar_sync(1 + w, 256);
                    TSC(TIMING == 1 && tid == 0, 32 + p);
                    wg_fence();
                    if (last) {
                        wgmma_n192<0, 1>(acc[0], mkdesc(sd + dlo(OFF_MEAN, 0) + w * 128, dhi(128, 0)), mkdesc(sd + dlo(OFF_CS, 0), dhi(48, 0)));
                        wgmma_n192<0, 1>(acc[1], mkdesc(sd + dlo(OFF_MEAN + 1024, 0) + w * 128, dhi(128, 0)), mkdesc(sd + dlo(OFF_CS, 0), dhi(48, 0)));
                    }
#pragma unroll
                    for (int k = 0; k < 4; k++) {
                        wgmma_n192<0, 1>(acc[0], mkdesc(dx0 + so + k * 2, dhi(1024, 1)), mkdesc(dw0 + so + k * 128, dhi(1024, 1)), k || ffn || last ? 1 : p);
                        wgmma_n192<0, 1>(acc[1], mkdesc(dx0 + so + 512 + k * 2, dhi(1024, 1)), mkdesc(dw0 + so + k * 128, dhi(1024, 1)), k || ffn || last ? 1 : p);
                        if (ffn && k == 2) {
#pragma unroll
                            for (int j = 0; j < 8; j++)
                                wgmma_n8<1, 0>(fa, mkdesc(sd + dlo(OFF_FW, 8192) + fs * 1024 + j * 64, dhi(512, 2)), mkdesc(sd + dlo(OFF_FA, 128) + fs * 128 + j * 16, dhi(128, 0)));
                        }
                    }
                    wg_commit();
                    bar_arrive(2 - w, 256);
                    wg_wait<0>();
                    TSC(TIMING == 9 && elect && p >= 11, 34 + (p - 11) * 6 + w * 3);
                    if (wi == 0 && elect_one()) { mbar_arrive(bo + 8 * B_EMPTY); if (ffn) mbar_arrive(bars + 8 * (B_FEMPTY + fs)); }
                    so = so == 2 * (STAGE >> 4) ? 0 : so + (STAGE >> 4);
                    bo += 8;
                    if (bo == bars + 24) { bo = bars; ph ^= 1; }
                };
                if (w) bar_arrive(1, 256);
                uint32_t fm = opaque((fb < 112 ? (F1_MASK >> (16 * w)) & 0xffff : 0u) | 0x80000000u), fph = 0;
                int fs = w;
#pragma unroll 1
                for (; p < 16; p++) {
                    if (fm & 1) { step(true, fs, fph, false); fs += 2; if (fs >= 3) { fs -= 3; fph ^= 1; } }
                    else if (fm & 0x10000) step(false, 0, 0, true);
                    else step(false, 0, 0, false);
                    fm >>= 1;
                    if (p == P_PART) {
                        if (fb < 112) sts4(sb + OFF_FA + tid * 16, __float_as_uint(fa[0]), __float_as_uint(fa[1]), __float_as_uint(fa[2]), __float_as_uint(fa[3]));
                        __syncwarp();
                        if (lane == 0) mbar_arrive(bars + 8 * B_PART);
                    }
                    if (p != 14) continue;
                    mbar_wait(bars + 8 * B_AUX, 0);
                    mbar_wait(bars + 8 * (B_EMPTY + 1), 0);
                    const uint32_t hm = __float_as_uint(0.5f * lds1f(sb + OFF_STAT + 64 + tw * 256 + ln * 8)) >> 16;
                    sts4(sb + OFF_MEAN + w * 2048 + wi * 256 + (ln >> 4) * 1024 + (ln & 15) * 16, hm * 0x10001u, hm, 0, 0);
                    fence_async_smem();
                }
                if (elect) mbar_arrive(bars + 8 * B_G1DONE);
            }
            TSC(elect, 2 + 8 * w);

            tag = lds1(sb + OFF_TAG);
            mbar_wait(bars + 8 * (B_EMPTY + 2), 0);
            uint32_t pk[4][24];
            auto np = [&](int i, int j) {
                const float* a = &acc[i >> 1][4 * j + 2 * (i & 1)];
                pk[i][j] = pack_bf16(a[0], a[1]);
                if (j >= 16) pk[i][j] = movm(pk[i][j]);
            };
            const uint32_t ha = sb + OFF_HALO + tw * 2048 + ln * 8;
#pragma unroll
            for (int j = 8; j < 24; j += 2) { np(3, j); np(3, j + 1); }
            if (tw < 7) {
#pragma unroll
                for (int j = 8; j < 24; j += 2) sts2(ha + 2048 + (j - 8) * 128, pk[3][j], pk[3][j + 1]);
                bar_arrive(4 + tw, 64);
            } else {
#pragma unroll
                for (int j = 8; j < 24; j += 2) st_rlx2(&S->halo[b][(j - 8) * 32 + ln * 2], tagw(pk[3][j], ~ln & 1, tag), pk[3][j + 1]);
            }
            TSC(TIMING == 8 && ln == 0 && wi == 1, 32 + 8 * w);
            const bool u0 = 2 * t > g, u1 = 2 * t + 1 > g;
            const uint32_t mU = (u0 ? 0xffffu : 0u) | (u1 ? 0xffff0000u : 0u);
            uint2 hl[8];
            float rk[4][2], fq[4][2];
            const float mask = tw == 0 && j0 == 0 ? -INFINITY : 0.f;
#pragma unroll
            for (int hd = 0; hd < 2; hd++) {
#pragma unroll
                for (int jj = 0; jj < 12; jj++) {
                    const int j = (jj >> 2) * 8 + hd * 4 + (jj & 3);
                    np(0, j); np(1, j); np(2, j);
                    if (j < 8) np(3, j);
                }
                float s[2][3][4];
#pragma unroll
                for (int h = 1; h >= 0; h--)
#pragma unroll
                    for (int n = 2; n >= 0; n--) {
                        if (h == 0 && n == 0 && hd == 0) {
                            const uint32_t ka = sb + OFF_STAT + tw * 256 + 4 + t * 16, k0 = opaque(ka + (u0 ? 0 : 64)), k1 = opaque(ka + (u1 ? 8 : 72));
#pragma unroll
                            for (int i = 0; i < 4; i++) {
                                const float rq = lds1f(sta + i * 64 + 4) * (0.17677669529663687f * 1.4426950408889634f);
                                rk[i][0] = lds1f(k0 + i * 64); rk[i][1] = lds1f(k1 + i * 64);
                                fq[i][0] = rq * rk[i][0]; fq[i][1] = rq * rk[i][1];
                            }
                            TSC(TIMING == 8 && ln == 0 && wi == 1 && s[1][0][0] + s[0][1][0] != 123.456f, 33 + 8 * w);
                            bar_sync(3 + tw, 64);
#pragma unroll
                            for (int c = 0; c < 8; c++) hl[c] = lds2(ha + c * 256);
                        }
                        const int kg = 2 * h - 1 + n;
                        s[h][n][0] = s[h][n][1] = kg < 0 ? mask : 0.f; s[h][n][2] = s[h][n][3] = 0.f;
#pragma unroll
                        for (int ks = 0; ks < 2; ks++) {
                            const int q = hd * 4 + 2 * ks;
                            const uint32_t* k = kg < 0 ? &hl[hd * 2 + ks].x : &pk[kg < 0 ? 0 : kg][8 + q];
                            mma16816(s[h][n], pk[2 * h][q], pk[2 * h + 1][q], pk[2 * h][q + 1], pk[2 * h + 1][q + 1], k[0], k[1]);
                        }
                    }
                uint32_t pp[4], pc[4];
#pragma unroll
                for (int i = 0; i < 4; i++) {
                    const float* sp = &s[i >> 1][i & 1][2 * (i & 1)];
                    const float* sc = &s[i >> 1][(i & 1) + 1][2 * (i & 1)];
                    float a0 = (u0 ? sp[0] : sc[0]) * fq[i][0], a1 = (u1 ? sp[1] : sc[1]) * fq[i][1];
                    float m = fmaxf(a0, a1);
                    m = fmaxf(m, __shfl_xor_sync(0xffffffffu, m, 1));
                    m = fmaxf(m, __shfl_xor_sync(0xffffffffu, m, 2));
                    a0 = ex2(a0 - m); a1 = ex2(a1 - m);
                    float sum = a0 + a1;
                    sum += __shfl_xor_sync(0xffffffffu, sum, 1);
                    sum += __shfl_xor_sync(0xffffffffu, sum, 2);
                    const float inv = rcp(sum);
                    const uint32_t pw = pack_bf16(a0 * rk[i][0] * inv, a1 * rk[i][1] * inv);
                    pp[i] = pw & mU; pc[i] = pw & ~mU;
                }
                TSC(TIMING == 8 && ln == 0 && wi == 1 && pp[0] + pp[3] != 0x12345, 34 + 2 * hd + 8 * w);
#pragma unroll
                for (int fh = 0; fh < 2; fh++)
#pragma unroll
                    for (int i = 0; i < 4; i++) {
                        const int v = 16 + hd * 4 + 2 * fh;
                        const uint32_t* vp = i ? &pk[i ? i - 1 : 0][v] : &hl[4 + hd * 2 + fh].x;
                        float o[4] = {0.f, 0.f, 0.f, 0.f};
                        if (i & 1) mma16816(o, vp[0], vp[1], pk[i][v], pk[i][v + 1], pp[i], pc[i]);
                        else { mma1688(o, pk[i][v], pk[i][v + 1], pc[i]); mma1688(o, vp[0], vp[1], pp[i]); }
                        const uint32_t tm = (ln & 7) == (nt & 3) * 2 + (i & 1);
                        ow[hd * 4 + 2 * fh][i] = tagw(pack_bf16(o[0], o[1]), tm, tag); ow[hd * 4 + 2 * fh + 1][i] = tagw(pack_bf16(o[2], o[3]), tm, tag);
                    }
                if (hd && ln == 0) mbar_arrive(bars + 8 * B_ATT);
                store_o(hd ? ST_A : 0, hd ? ST_B : ST_A);
                if (!hd && ln == 0) mbar_arrive(bars + 8 * B_AST);
                TSC(TIMING == 11 && !hd && ln == 0 && wi == 3, 45 + w);
                TSC(elect && hd == 0, 3 + 8 * w);
                TSC(TIMING == 8 && ln == 0 && wi == 1, 35 + 2 * hd + 8 * w);
            }
        }
        TSC(elect, 4 + 8 * w);
        mbar_wait(bars + 8 * B_XR, 0);
        float acc2[64];
        const uint32_t xs = sb + (wi & 1) * 8192 + (tw >> 1) * 2048, mad = xs + (ln & 15) * 128;
        {
            const uint32_t sta = sb + OFF_STAT + (8 + hp * 128 + tw * 16 + g) * 8;
            const float2 s0 = lds2f(sta), s1 = lds2f(sta + 64);
            const float m0 = s0.x * s0.y, r0 = 1.f + s0.y, m1 = s1.x * s1.y, r1 = 1.f + s1.y;
#pragma unroll
            for (int j = 0; j < 16; j += 2) {
                uint32_t a0, a1, a2, a3;
                const int ch = (j & 7) + (ln >> 4);
                asm volatile("ldmatrix.sync.aligned.m8n8.x4.shared.b16 {%0,%1,%2,%3}, [%4];" : "=r"(a0), "=r"(a1), "=r"(a2), "=r"(a3)
                             : "r"(mad + (j >> 3) * STAGE + ((ch ^ (ln & 7)) << 4)) : "memory");
                acc2[4 * j + 0] = fmaf(bf_lo(a0), r0, m0); acc2[4 * j + 1] = fmaf(bf_hi(a0), r0, m0);
                acc2[4 * j + 2] = fmaf(bf_lo(a1), r1, m1); acc2[4 * j + 3] = fmaf(bf_hi(a1), r1, m1);
                acc2[4 * j + 4] = fmaf(bf_lo(a2), r0, m0); acc2[4 * j + 5] = fmaf(bf_hi(a2), r0, m0);
                acc2[4 * j + 6] = fmaf(bf_lo(a3), r1, m1); acc2[4 * j + 7] = fmaf(bf_hi(a3), r1, m1);
            }
        }
        TSC(elect, 5 + 8 * w);
        {
            if (ST_B < ST_C) { mbar_wait(bars + 8 * B_GO, 0); store_o(ST_B, ST_C); }
            mbar_wait(bars + 8 * B_ATT, 0);
            const uint32_t ring = sb + (w ? OFF_O1 : OFF_O0), da0 = (ring >> 4) + dlo(0, 1024);
            const uint32_t chk = ring + wi * 256 + (ln >> 3) * 1032 + (g & 1) * 132 + t * 32;
            uint32_t db = sd + dlo(OFF_WO, 16384);
#pragma unroll 1
            for (int s = 0; s < 8; s++) {
                const uint32_t ro = (s & 1) * 16384;
                mbar_wait(bars + 8 * (B_WOFULL + s), 0);
                TSC(TIMING == 11 && tid == 0 && s == 0, 43);
                mbar_wait(bars + 8 * (B_OFULL + s) + 64 * w, 0);
                TSC(TIMING == 11 && tid == 0 && s == 0, 44);
#pragma unroll 1
                for (int it = 0; __any_sync(0xffffffffu, (mism(lds1(chk + ro), lds1(chk + ro + 4096), tag) | mism(lds1(chk + ro + 8192), lds1(chk + ro + 12288), tag)) & 1) && it < SPIN_LIMIT; it++) {
                    NRETRY();
                    const uint32_t fo = wi * 256 + (ln >> 4) * 1024 + (ln & 15) * 16;
                    uint4 v[8];
#pragma unroll
                    for (int c = 0; c < 8; c++) v[c] = ld_rlx4(g_o + (size_t)(((mt * 2 + hp) * 2 + w) * 8 + s) * 16384 + fo + c * 2048);
#pragma unroll
                    for (int c = 0; c < 8; c++) sts4(ring + ro + fo + c * 2048, v[c].x, v[c].y, v[c].z, v[c].w);
                    fence_async_smem();
                    __syncwarp();
                }
                auto issue = [&](bool last) {
                uint32_t e0, e1;
                if (last) {
                    mbar_wait(bars + 8 * B_UPD, 0);
                    int sl0, sl1;
                    asm volatile("ld.shared.s8 %0, [%1];" : "=r"(sl0) : "r"(sb + OFF_ROWMAP + tw * 16 + g) : "memory");
                    asm volatile("ld.shared.s8 %0, [%1];" : "=r"(sl1) : "r"(sb + OFF_ROWMAP + tw * 16 + 8 + g) : "memory");
                    e0 = (sl0 >> 1) == (int)t ? 0x3f80u << ((sl0 & 1) * 16) : 0u; e1 = (sl1 >> 1) == (int)t ? 0x3f80u << ((sl1 & 1) * 16) : 0u;
                }
                bar_sync(1 + w, 256);
                TSC(elect && s == 0, 6 + 8 * w);
                TSC(TIMING == 2 && elect, 32 + 16 * w + s);
                wg_fence();
                if (last) wgmma_rs_n128<1>(acc2, e0, e1, 0u, 0u, mkdesc(sd + dlo(OFF_FA, 0), dhi(128, 0)));
#pragma unroll
                for (int k = 0; k < 8; k++)
                    wgmma_n128<1, 1>(acc2, mkdesc(da0 + (ro >> 4) + k * 128, dhi(128, 0)), mkdesc(db + k * 128, dhi(1024, 1)));
                wg_commit();
                bar_arrive(2 - w, 256);
                if (!last && s == 0) store_o(ST_C, 8);
                db = db == sd + dlo(OFF_WO + (NWO - 1) * 32768, 16384) ? sd + dlo(OFF_WO, 16384) : db + 2048;
                wg_wait<0>();
                if (elect && !last) mbar_arrive(bars + 8 * (B_DONE + s) + 64 * w);
                };
                if (s < 7) issue(false); else issue(true);
            }
#pragma unroll
            for (int i = 0; i < 64; i++) asm volatile("" : "+f"(acc2[i]) :: "memory");
            TSC(elect, 7 + 8 * w);
#pragma unroll
            for (int j = 0; j < 16; j += 2) {
                const int ch = (j & 7) + (ln >> 4);
                asm volatile("stmatrix.sync.aligned.m8n8.x4.shared.b16 [%0], {%1,%2,%3,%4};" ::"r"(mad + (j >> 3) * STAGE + ((ch ^ (ln & 7)) << 4)),
                             "r"(pack_bf16(acc2[4 * j], acc2[4 * j + 1])), "r"(pack_bf16(acc2[4 * j + 2], acc2[4 * j + 3])),
                             "r"(pack_bf16(acc2[4 * j + 4], acc2[4 * j + 5])), "r"(pack_bf16(acc2[4 * j + 6], acc2[4 * j + 7])) : "memory");
                if ((j & 7) == 6) {
                    fence_async_smem();
                    __syncwarp();
                    if (ln == 0) tma_store_2d(&mout, xs + (j >> 3) * STAGE, par * 1024 + cb * 128 + (j >> 3) * 64, j0 + hp * 128 + tw * 16);
                }
            }
            if (ln == 0) asm volatile("cp.async.bulk.commit_group;\ncp.async.bulk.wait_group.read 0;" ::: "memory");
            TSC(elect, 8 + 8 * w);
            TS_END();
        }
    }
}

typedef CUresult (*EncodeFn)(CUtensorMap*, CUtensorMapDataType, cuuint32_t, void*, const cuuint64_t*, const cuuint64_t*, const cuuint32_t*,
                             const cuuint32_t*, CUtensorMapInterleave, CUtensorMapSwizzle, CUtensorMapL2promotion, CUtensorMapFloatOOBfill);

CUtensorMap make_map(EncodeFn fn, const void* base, int rank, const cuuint64_t* dims, const cuuint64_t* strides, const cuuint32_t* box,
                     CUtensorMapSwizzle swz = CU_TENSOR_MAP_SWIZZLE_128B, CUtensorMapL2promotion pro = CU_TENSOR_MAP_L2_PROMOTION_L2_256B) {
    CUtensorMap m;
    cuuint32_t es[5] = {1, 1, 1, 1, 1};
    fn(&m, CU_TENSOR_MAP_DATA_TYPE_BFLOAT16, rank, (void*)base, dims, strides, box, es, CU_TENSOR_MAP_INTERLEAVE_NONE,
       swz, pro, CU_TENSOR_MAP_FLOAT_OOB_FILL_NONE);
    return m;
}

}

extern "C" void kernel_launch(void* const* d_in, const int* in_sizes, int n_in, void* d_out, int out_size) {
    (void)in_sizes; (void)n_in; (void)out_size;
    const __nv_bfloat16* x = (const __nv_bfloat16*)d_in[0];
    const __nv_bfloat16* wqkv = (const __nv_bfloat16*)d_in[1];
    const char* wo = (const char*)d_in[2];
    const __nv_bfloat16* wr = (const __nv_bfloat16*)d_in[4];
    const char* wg = (const char*)d_in[5];
    const char* wu = (const char*)d_in[6];
    const char* wd = (const char*)d_in[7];
    static EncodeFn fn = nullptr;
    static int by_sm = 0;
    static Scratch* scr = nullptr;
    if (!fn) {
        void* p = nullptr; cudaDriverEntryPointQueryResult q;
        cudaGetDriverEntryPoint("cuTensorMapEncodeTiled", &p, cudaEnableDefault, &q);
        fn = (EncodeFn)p;
        cudaFuncSetAttribute(fused_kernel, cudaFuncAttributeMaxDynamicSharedMemorySize, SMEM_LAUNCH);
        cudaGetSymbolAddress((void**)&scr, g_scr);
        int dev = 0, sms = 0;
        cudaGetDevice(&dev);
        cudaDeviceGetAttribute(&sms, cudaDevAttrMultiProcessorCount, dev);
        by_sm = sms == 132;
    }
    const cuuint64_t xd[4] = {2048, 16, 32, 2}, xs[3] = {4096, 131072, 65536};
    const cuuint32_t xb[4] = {64, 16, 4, 2};
    const cuuint64_t wdm[3] = {1024, 1024, 3}, wst[2] = {6144, 2048};
    const cuuint32_t wb[3] = {64, 64, 3};
    const cuuint64_t od[4] = {64, 64, 16, 16}, ost[3] = {2048, 131072, 128};
    const cuuint32_t ob[4] = {64, 8, 16, 2};
    const cuuint64_t yd[2] = {2048, 1024}, yst[1] = {4096};
    const cuuint32_t yb[2] = {64, 16};
    const cuuint64_t sd[3] = {64, 1024, 32}, sst[2] = {4096, 128};
    const cuuint32_t sbx[3] = {64, 16, 4};
    CUtensorMap mxs = make_map(fn, x, 3, sd, sst, sbx);
    CUtensorMap mx = make_map(fn, x, 4, xd, xs, xb), mw = make_map(fn, wqkv, 3, wdm, wst, wb);
    CUtensorMap mwo = make_map(fn, wo, 4, od, ost, ob), mout = make_map(fn, d_out, 2, yd, yst, yb);
    const cuuint64_t gd[3] = {3584, 1024, 2}, gst[2] = {7168, (cuuint64_t)(wu < wg ? wg - wu : wu - wg)};
    const cuuint32_t gb[3] = {32, 128, 2};
    const cuuint64_t dd[2] = {1024, 3584}, dst[1] = {2048};
    const cuuint32_t db[2] = {64, 64};
    CUtensorMap mgu = make_map(fn, wu < wg ? wu : wg, 3, gd, gst, gb, CU_TENSOR_MAP_SWIZZLE_64B, CU_TENSOR_MAP_L2_PROMOTION_L2_128B);
    CUtensorMap mwd = make_map(fn, wd, 2, dd, dst, db, CU_TENSOR_MAP_SWIZZLE_128B, CU_TENSOR_MAP_L2_PROMOTION_L2_128B);
    fused_kernel<<<132, 512, SMEM_LAUNCH, cudaStreamPerThread>>>(by_sm, x, wqkv, wr, scr, wg, wu, wd, wo, mw, mx, mwo, mxs, mout, mgu, mwd);
}
```

```cpp
#include <cuda_runtime.h>
#include <cuda.h>
#include <cuda_bf16.h>
#include <stdint.h>

namespace {

constexpr int STAGE = 57344;
constexpr int OFF_FW = 3 * STAGE;
constexpr int OFF_FA = OFF_FW + 49152;
constexpr int OFF_CS = OFF_FA + 6144;
constexpr int OFF_STAT = OFF_CS + 1232;
constexpr int OFF_ROWMAP = OFF_STAT + 2112;
constexpr int OFF_TAG = OFF_ROWMAP + 128;
constexpr int OFF_BAR = OFF_TAG + 8;
constexpr int OFF_F2X = 16384, OFF_HALO = 24576, OFF_O1 = 24576, OFF_O0 = 73728, OFF_WO = 106496, NWO = 3, OFF_MEAN = 2 * STAGE;
static_assert(OFF_WO + NWO * 32768 <= OFF_FA && OFF_O0 + 32768 == OFF_WO && OFF_O1 + 32768 == STAGE, "alias");
constexpr int B_FULLA = 0, B_FULLB = 3, B_ROW = 6, B_FFULL = 11, B_FEMPTY = 14, B_F2DONE = 17, B_GO = 18, B_CS = 19, B_WOFULL = 25, B_OFULL = B_WOFULL + 8,
              B_DONE = B_OFULL + 16;
constexpr int B_EMPTY = B_DONE + 16, B_XR = B_EMPTY + 3, B_G1DONE = B_XR + 1;
constexpr int B_UPD = B_G1DONE + 1, B_F2FULL = B_UPD + 1;
constexpr int B_AUX = B_F2FULL + 1, B_PART = B_AUX + 1, B_ATT = B_PART + 1, B_CSDONE = B_ATT + 1, B_AST = B_CSDONE + 1, NBAR = B_AST + 1;
constexpr int SMEM_BYTES = OFF_BAR + NBAR * 8;
static_assert(SMEM_BYTES <= 232448 && OFF_BAR % 8 == 0, "smem");
#define P_PART 13
#define F1_MASK (0x6a005a00u >> (14 - P_PART))
#define PF_CNT 0x2aaaaac
#define EARLY_FILL 2
#define N_S1 2
#define T_X 300
#define D_X 330
#define T_ROW 1000
#define D_R 400
#define T_W 1500
#define D_W 500
#define T_CS 2400
#define W_LAG -1
#define ST_A 2
#define ST_B 2
#define N_X0 1
#define MAP 1
#define DBG_F2 1
#define DBG_F1 1
#define DBG_XR 1
#define T_H 250
#define T_O1 250
#define XR_GATE B_G1DONE
#define ST_C 4
#define T_O 2350
#define T_S1 128
#define T_GO 256
#define T_S2 950
#define DBG_CS 0
#define DBG_ST 0
#define N_GA 4
#define POLL_NS 100
#define STATS_UNROLL 4
constexpr int kStatsUnroll = STATS_UNROLL;
constexpr int SPIN_LIMIT = 1 << 18;

struct Scratch {
    uint8_t o[2048 * 1024 * 2];
    uint2 rec[2048];
    float cs[8][3072];
    uint32_t halo[128][512];
    uint32_t h[14336];
    float ypart[8][8][1024];
    uint2 sel[16];
    uint32_t hint[128][8];
    uint32_t epoch;
};
__device__ __align__(1024) Scratch g_scr;

#define TS(i) do {} while (0)
#define TS_END() do {} while (0)
constexpr int SMEM_LAUNCH = SMEM_BYTES;
#define TSC(c, i) do {} while (0)
#define NRETRY() do {} while (0)
__device__ __forceinline__ uint32_t smem_u32(const void* p) { return (uint32_t)__cvta_generic_to_shared(p); }
__device__ __forceinline__ void mbar_init(uint32_t bar, uint32_t cnt) { asm volatile("mbarrier.init.shared::cta.b64 [%0], %1;" ::"r"(bar), "r"(cnt) : "memory"); }
__device__ __forceinline__ void mbar_expect_tx(uint32_t bar, uint32_t bytes) { asm volatile("mbarrier.arrive.expect_tx.shared::cta.b64 _, [%0], %1;" ::"r"(bar), "r"(bytes) : "memory"); }
__device__ __forceinline__ void mbar_arrive(uint32_t bar) { asm volatile("mbarrier.arrive.shared::cta.b64 _, [%0];" ::"r"(bar) : "memory"); }
__device__ __forceinline__ void mbar_wait(uint32_t bar, uint32_t parity) {
    asm volatile("{\n.reg .pred P1;\nLAB_WAIT:\nmbarrier.try_wait.parity.shared::cta.b64 P1, [%0], %1;\n@!P1 bra LAB_WAIT;\n}" ::"r"(bar), "r"(parity) : "memory");
}
__device__ __forceinline__ bool mbar_test(uint32_t bar, uint32_t parity) {
    uint32_t ok;
    asm volatile("{\n.reg .pred p;\nmbarrier.test_wait.parity.shared::cta.b64 p, [%1], %2;\nselp.u32 %0, 1, 0, p;\n}" : "=r"(ok) : "r"(bar), "r"(parity) : "memory");
    return ok;
}
__device__ __forceinline__ void tma_2d(uint32_t dst, const CUtensorMap* m, uint32_t bar, int c0, int c1) {
    asm volatile("cp.async.bulk.tensor.2d.shared::cluster.global.mbarrier::complete_tx::bytes [%0], [%1, {%3, %4}], [%2];" ::"r"(dst), "l"(m), "r"(bar), "r"(c0), "r"(c1) : "memory");
}
__device__ __forceinline__ void tma_3d(uint32_t dst, const CUtensorMap* m, uint32_t bar, int c0, int c1, int c2) {
    asm volatile("cp.async.bulk.tensor.3d.shared::cluster.global.mbarrier::complete_tx::bytes [%0], [%1, {%3, %4, %5}], [%2];" ::"r"(dst), "l"(m), "r"(bar), "r"(c0), "r"(c1), "r"(c2) : "memory");
}
__device__ __forceinline__ void tma_4d(uint32_t dst, const CUtensorMap* m, uint32_t bar, int c0, int c1, int c2, int c3) {
    asm volatile("cp.async.bulk.tensor.4d.shared::cluster.global.mbarrier::complete_tx::bytes [%0], [%1, {%3, %4, %5, %6}], [%2];" ::"r"(dst), "l"(m), "r"(bar), "r"(c0), "r"(c1), "r"(c2), "r"(c3) : "memory");
}
__device__ __forceinline__ void tma_store_2d(const CUtensorMap* m, uint32_t src, int c0, int c1) {
    asm volatile("cp.async.bulk.tensor.2d.global.shared::cta.bulk_group [%0, {%2, %3}], [%1];" ::"l"(m), "r"(src), "r"(c0), "r"(c1) : "memory");
}
__device__ __forceinline__ void bulk_g2s(uint32_t dst, const void* src, uint32_t bytes, uint32_t bar) {
    asm volatile("cp.async.bulk.shared::cluster.global.mbarrier::complete_tx::bytes [%0], [%1], %2, [%3];" ::"r"(dst), "l"(src), "r"(bytes), "r"(bar) : "memory");
}
__device__ __forceinline__ void bulk_prefetch(const void* p, uint32_t bytes) { asm volatile("cp.async.bulk.prefetch.L2.global [%0], %1;" ::"l"(p), "r"(bytes) : "memory"); }
__device__ __forceinline__ void fence_async_smem() { asm volatile("fence.proxy.async.shared::cta;" ::: "memory"); }
__device__ __forceinline__ void wg_fence() { asm volatile("wgmma.fence.sync.aligned;" ::: "memory"); }
__device__ __forceinline__ void wg_commit() { asm volatile("wgmma.commit_group.sync.aligned;" ::: "memory"); }
template <int N> __device__ __forceinline__ void wg_wait() { asm volatile("wgmma.wait_group.sync.aligned %0;" ::"n"(N) : "memory"); }
__device__ __forceinline__ uint64_t mkdesc(uint32_t lo, uint32_t hi) { return ((uint64_t)hi << 32) | lo; }
__host__ __device__ constexpr uint32_t dhi(uint32_t sbo, uint32_t mode) { return (sbo >> 4) | (mode << 30); }
__host__ __device__ constexpr uint32_t dlo(uint32_t off, uint32_t lbo) { return (off >> 4) + ((lbo >> 4) << 16); }
__device__ __forceinline__ bool elect_one() {
    uint32_t e;
    asm volatile("{\n.reg .pred p;\nelect.sync _|p, 0xffffffff;\nselp.u32 %0, 1, 0, p;\n}" : "=r"(e));
    return e;
}
template <int R> __device__ __forceinline__ void reg_inc() { asm volatile("setmaxnreg.inc.sync.aligned.u32 %0;" ::"n"(R)); }
template <int R> __device__ __forceinline__ void reg_dec() { asm volatile("setmaxnreg.dec.sync.aligned.u32 %0;" ::"n"(R)); }
__device__ __forceinline__ void bar_sync(int id, int n) { asm volatile("bar.sync %0, %1;" ::"r"(id), "r"(n) : "memory"); }
__device__ __forceinline__ void bar_arrive(int id, int n) { asm volatile("bar.arrive %0, %1;" ::"r"(id), "r"(n) : "memory"); }
__device__ __forceinline__ uint32_t pack_bf16(float lo, float hi) { uint32_t r; asm("cvt.rn.bf16x2.f32 %0, %1, %2;" : "=r"(r) : "f"(hi), "f"(lo)); return r; }
__device__ __forceinline__ float bf_lo(uint32_t u) { return __uint_as_float(u << 16); }
__device__ __forceinline__ float bf_hi(uint32_t u) { return __uint_as_float(u & 0xffff0000u); }
__device__ __forceinline__ float bf16r(float v) { return bf_lo(pack_bf16(v, 0.f)); }
__device__ __forceinline__ uint32_t tagw(uint32_t w, uint32_t m, uint32_t tag) { uint32_t r; asm("lop3.b32 %0, %1, %2, %3, 0xb8;" : "=r"(r) : "r"(w), "r"(m), "r"(tag)); return r; }
__device__ __forceinline__ uint32_t tagf(float f, uint32_t tag) { return tagw(__float_as_uint(f), 1u, tag); }
__device__ __forceinline__ uint32_t movm(uint32_t a) { uint32_t d; asm volatile("movmatrix.sync.aligned.m8n8.trans.b16 %0, %1;" : "=r"(d) : "r"(a)); return d; }
__device__ __forceinline__ void mma16816(float (&c)[4], uint32_t a0, uint32_t a1, uint32_t a2, uint32_t a3, uint32_t b0, uint32_t b1) {
    asm volatile("mma.sync.aligned.m16n8k16.row.col.f32.bf16.bf16.f32 {%0,%1,%2,%3}, {%4,%5,%6,%7}, {%8,%9}, {%0,%1,%2,%3};"
                 : "+f"(c[0]), "+f"(c[1]), "+f"(c[2]), "+f"(c[3]) : "r"(a0), "r"(a1), "r"(a2), "r"(a3), "r"(b0), "r"(b1));
}
__device__ __forceinline__ void mma1688(float (&c)[4], uint32_t a0, uint32_t a1, uint32_t b0) {
    asm volatile("mma.sync.aligned.m16n8k8.row.col.f32.bf16.bf16.f32 {%0,%1,%2,%3}, {%4,%5}, {%6}, {%0,%1,%2,%3};"
                 : "+f"(c[0]), "+f"(c[1]), "+f"(c[2]), "+f"(c[3]) : "r"(a0), "r"(a1), "r"(b0));
}
__device__ __forceinline__ uint32_t ld_rlx(const void* p) { uint32_t v; asm volatile("ld.relaxed.gpu.global.u32 %0, [%1];" : "=r"(v) : "l"(p) : "memory"); return v; }
__device__ __forceinline__ uint2 ld_rlx2(const void* p) { uint2 v; asm volatile("ld.relaxed.gpu.global.v2.u32 {%0,%1}, [%2];" : "=r"(v.x), "=r"(v.y) : "l"(p) : "memory"); return v; }
__device__ __forceinline__ uint4 ld_rlx4(const void* p) { uint4 v; asm volatile("ld.relaxed.gpu.global.v4.u32 {%0,%1,%2,%3}, [%4];" : "=r"(v.x), "=r"(v.y), "=r"(v.z), "=r"(v.w) : "l"(p) : "memory"); return v; }
__device__ __forceinline__ uint32_t ld_acq(const void* p) { uint32_t v; asm volatile("ld.acquire.gpu.global.u32 %0, [%1];" : "=r"(v) : "l"(p) : "memory"); return v; }
__device__ __forceinline__ void st_rlx(void* p, uint32_t v) { asm volatile("st.relaxed.gpu.global.u32 [%0], %1;" ::"l"(p), "r"(v) : "memory"); }
__device__ __forceinline__ void st_rlx2(void* p, uint32_t a, uint32_t b) { asm volatile("st.relaxed.gpu.global.v2.u32 [%0], {%1,%2};" ::"l"(p), "r"(a), "r"(b) : "memory"); }
__device__ __forceinline__ void st_rlx4(void* p, uint32_t a, uint32_t b, uint32_t c, uint32_t d) { asm volatile("st.relaxed.gpu.global.v4.u32 [%0], {%1,%2,%3,%4};" ::"l"(p), "r"(a), "r"(b), "r"(c), "r"(d) : "memory"); }
__device__ __forceinline__ uint4 ldg_nc(const void* p) { uint4 v; asm volatile("ld.global.nc.v4.u32 {%0,%1,%2,%3}, [%4];" : "=r"(v.x), "=r"(v.y), "=r"(v.z), "=r"(v.w) : "l"(p)); return v; }
__device__ __forceinline__ uint32_t mism(uint32_t a, uint32_t b, uint32_t tag) { uint32_t r; asm("lop3.b32 %0, %1, %2, %3, 0x7e;" : "=r"(r) : "r"(a), "r"(b), "r"(tag)); return r; }
__device__ __forceinline__ uint32_t mism(const uint4& v, uint32_t tag) { return mism(v.x, v.y, tag) | mism(v.z, v.w, tag); }
__device__ __forceinline__ void prefetch_l2(const void* p) { asm volatile("prefetch.global.L2 [%0];" ::"l"(p)); }
__device__ __forceinline__ void touch256(uint32_t dst, const void* p) { asm volatile("cp.async.ca.shared.global.L2::256B [%0], [%1], 4;" ::"r"(dst), "l"(p) : "memory"); }
__device__ __forceinline__ void nap(int n) {
#pragma unroll 1
    for (int i = 0; i < n; i++) __nanosleep(100);
}
__device__ __forceinline__ uint32_t now() { uint32_t t; asm volatile("mov.u32 %0, %%globaltimer_lo;" : "=r"(t)); return t; }
__device__ __forceinline__ void until(uint32_t t) {
    while (t - now() - 1 < 16384u) __nanosleep(50);
}
__device__ __forceinline__ uint32_t opaque(uint32_t v) { return __shfl_xor_sync(0xffffffffu, v, 0); }
__device__ __forceinline__ void sts4(uint32_t a, uint32_t x, uint32_t y, uint32_t z, uint32_t w) { asm volatile("st.shared.v4.u32 [%0], {%1,%2,%3,%4};" ::"r"(a), "r"(x), "r"(y), "r"(z), "r"(w) : "memory"); }
__device__ __forceinline__ void sts2(uint32_t a, uint32_t x, uint32_t y) { asm volatile("st.shared.v2.u32 [%0], {%1,%2};" ::"r"(a), "r"(x), "r"(y) : "memory"); }
__device__ __forceinline__ uint4 lds4(uint32_t a) { uint4 v; asm volatile("ld.shared.v4.u32 {%0,%1,%2,%3}, [%4];" : "=r"(v.x), "=r"(v.y), "=r"(v.z), "=r"(v.w) : "r"(a) : "memory"); return v; }
__device__ __forceinline__ float4 lds4f(uint32_t a) { float4 v; asm volatile("ld.shared.v4.f32 {%0,%1,%2,%3}, [%4];" : "=f"(v.x), "=f"(v.y), "=f"(v.z), "=f"(v.w) : "r"(a) : "memory"); return v; }
__device__ __forceinline__ uint2 lds2(uint32_t a) { uint2 v; asm volatile("ld.shared.v2.u32 {%0,%1}, [%2];" : "=r"(v.x), "=r"(v.y) : "r"(a) : "memory"); return v; }
__device__ __forceinline__ float2 lds2f(uint32_t a) { float2 v; asm volatile("ld.shared.v2.f32 {%0,%1}, [%2];" : "=f"(v.x), "=f"(v.y) : "r"(a) : "memory"); return v; }
__device__ __forceinline__ uint32_t lds1(uint32_t a) { uint32_t v; asm volatile("ld.shared.u32 %0, [%1];" : "=r"(v) : "r"(a) : "memory"); return v; }
__device__ __forceinline__ float lds1f(uint32_t a) { return __uint_as_float(lds1(a)); }
__device__ __forceinline__ void sts1(uint32_t a, uint32_t v) { asm volatile("st.shared.u32 [%0], %1;" ::"r"(a), "r"(v) : "memory"); }
__device__ __forceinline__ uint32_t redux_max(uint32_t v) { uint32_t r; asm volatile("redux.sync.max.u32 %0, %1, 0xffffffff;" : "=r"(r) : "r"(v)); return r; }
__device__ __forceinline__ float ex2(float x) { float r; asm("ex2.approx.ftz.f32 %0, %1;" : "=f"(r) : "f"(x)); return r; }
__device__ __forceinline__ float rcp(float x) { float r; asm("rcp.approx.ftz.f32 %0, %1;" : "=f"(r) : "f"(x)); return r; }
__device__ __forceinline__ float sigmoidf(float v) { return rcp(1.f + ex2(v * -1.4426950408889634f)); }

template <int TA, int TB>
__device__ __forceinline__ void wgmma_n192(float (&d)[96], uint64_t da, uint64_t db, int acc = 1) {
    asm volatile("{\n.reg .pred p;\nsetp.ne.b32 p, %100, 0;\n"
        "wgmma.mma_async.sync.aligned.m64n192k16.f32.bf16.bf16 "
        "{%0, %1, %2, %3, %4, %5, %6, %7, %8, %9, %10, %11, %12, %13, %14, %15, "
        "%16, %17, %18, %19, %20, %21, %22, %23, %24, %25, %26, %27, %28, %29, %30, %31, "
        "%32, %33, %34, %35, %36, %37, %38, %39, %40, %41, %42, %43, %44, %45, %46, %47, "
        "%48, %49, %50, %51, %52, %53, %54, %55, %56, %57, %58, %59, %60, %61, %62, %63, "
        "%64, %65, %66, %67, %68, %69, %70, %71, %72, %73, %74, %75, %76, %77, %78, %79, "
        "%80, %81, %82, %83, %84, %85, %86, %87, %88, %89, %90, %91, %92, %93, %94, %95}, "
        "%96, %97, p, 1, 1, %98, %99;\n}\n"
        : "+f"(d[0]), "+f"(d[1]), "+f"(d[2]), "+f"(d[3]), "+f"(d[4]), "+f"(d[5]), "+f"(d[6]), "+f"(d[7]),
          "+f"(d[8]), "+f"(d[9]), "+f"(d[10]), "+f"(d[11]), "+f"(d[12]), "+f"(d[13]), "+f"(d[14]), "+f"(d[15]),
          "+f"(d[16]), "+f"(d[17]), "+f"(d[18]), "+f"(d[19]), "+f"(d[20]), "+f"(d[21]), "+f"(d[22]), "+f"(d[23]),
          "+f"(d[24]), "+f"(d[25]), "+f"(d[26]), "+f"(d[27]), "+f"(d[28]), "+f"(d[29]), "+f"(d[30]), "+f"(d[31]),
          "+f"(d[32]), "+f"(d[33]), "+f"(d[34]), "+f"(d[35]), "+f"(d[36]), "+f"(d[37]), "+f"(d[38]), "+f"(d[39]),
          "+f"(d[40]), "+f"(d[41]), "+f"(d[42]), "+f"(d[43]), "+f"(d[44]), "+f"(d[45]), "+f"(d[46]), "+f"(d[47]),
          "+f"(d[48]), "+f"(d[49]), "+f"(d[50]), "+f"(d[51]), "+f"(d[52]), "+f"(d[53]), "+f"(d[54]), "+f"(d[55]),
          "+f"(d[56]), "+f"(d[57]), "+f"(d[58]), "+f"(d[59]), "+f"(d[60]), "+f"(d[61]), "+f"(d[62]), "+f"(d[63]),
          "+f"(d[64]), "+f"(d[65]), "+f"(d[66]), "+f"(d[67]), "+f"(d[68]), "+f"(d[69]), "+f"(d[70]), "+f"(d[71]),
          "+f"(d[72]), "+f"(d[73]), "+f"(d[74]), "+f"(d[75]), "+f"(d[76]), "+f"(d[77]), "+f"(d[78]), "+f"(d[79]),
          "+f"(d[80]), "+f"(d[81]), "+f"(d[82]), "+f"(d[83]), "+f"(d[84]), "+f"(d[85]), "+f"(d[86]), "+f"(d[87]),
          "+f"(d[88]), "+f"(d[89]), "+f"(d[90]), "+f"(d[91]), "+f"(d[92]), "+f"(d[93]), "+f"(d[94]), "+f"(d[95])
        : "l"(da), "l"(db), "n"(TA), "n"(TB), "r"(acc));
}
template <int TA, int TB>
__device__ __forceinline__ void wgmma_n128(float (&d)[64], uint64_t da, uint64_t db, int acc = 1) {
    asm volatile("{\n.reg .pred p;\nsetp.ne.b32 p, %68, 0;\n"
        "wgmma.mma_async.sync.aligned.m64n128k16.f32.bf16.bf16 "
        "{%0, %1, %2, %3, %4, %5, %6, %7, %8, %9, %10, %11, %12, %13, %14, %15, "
        "%16, %17, %18, %19, %20, %21, %22, %23, %24, %25, %26, %27, %28, %29, %30, %31, "
        "%32, %33, %34, %35, %36, %37, %38, %39, %40, %41, %42, %43, %44, %45, %46, %47, "
        "%48, %49, %50, %51, %52, %53, %54, %55, %56, %57, %58, %59, %60, %61, %62, %63}, "
        "%64, %65, p, 1, 1, %66, %67;\n}\n"
        : "+f"(d[0]), "+f"(d[1]), "+f"(d[2]), "+f"(d[3]), "+f"(d[4]), "+f"(d[5]), "+f"(d[6]), "+f"(d[7]),
          "+f"(d[8]), "+f"(d[9]), "+f"(d[10]), "+f"(d[11]), "+f"(d[12]), "+f"(d[13]), "+f"(d[14]), "+f"(d[15]),
          "+f"(d[16]), "+f"(d[17]), "+f"(d[18]), "+f"(d[19]), "+f"(d[20]), "+f"(d[21]), "+f"(d[22]), "+f"(d[23]),
          "+f"(d[24]), "+f"(d[25]), "+f"(d[26]), "+f"(d[27]), "+f"(d[28]), "+f"(d[29]), "+f"(d[30]), "+f"(d[31]),
          "+f"(d[32]), "+f"(d[33]), "+f"(d[34]), "+f"(d[35]), "+f"(d[36]), "+f"(d[37]), "+f"(d[38]), "+f"(d[39]),
          "+f"(d[40]), "+f"(d[41]), "+f"(d[42]), "+f"(d[43]), "+f"(d[44]), "+f"(d[45]), "+f"(d[46]), "+f"(d[47]),
          "+f"(d[48]), "+f"(d[49]), "+f"(d[50]), "+f"(d[51]), "+f"(d[52]), "+f"(d[53]), "+f"(d[54]), "+f"(d[55]),
          "+f"(d[56]), "+f"(d[57]), "+f"(d[58]), "+f"(d[59]), "+f"(d[60]), "+f"(d[61]), "+f"(d[62]), "+f"(d[63])
        : "l"(da), "l"(db), "n"(TA), "n"(TB), "r"(acc));
}
template <int TB>
__device__ __forceinline__ void wgmma_rs_n128(float (&d)[64], uint32_t a0, uint32_t a1, uint32_t a2, uint32_t a3, uint64_t db) {
    asm volatile("{\n.reg .pred p;\nsetp.ne.b32 p, 1, 0;\n"
        "wgmma.mma_async.sync.aligned.m64n128k16.f32.bf16.bf16 "
        "{%0, %1, %2, %3, %4, %5, %6, %7, %8, %9, %10, %11, %12, %13, %14, %15, "
        "%16, %17, %18, %19, %20, %21, %22, %23, %24, %25, %26, %27, %28, %29, %30, %31, "
        "%32, %33, %34, %35, %36, %37, %38, %39, %40, %41, %42, %43, %44, %45, %46, %47, "
        "%48, %49, %50, %51, %52, %53, %54, %55, %56, %57, %58, %59, %60, %61, %62, %63}, "
        "{%64, %65, %66, %67}, %68, p, 1, 1, %69;\n}\n"
        : "+f"(d[0]), "+f"(d[1]), "+f"(d[2]), "+f"(d[3]), "+f"(d[4]), "+f"(d[5]), "+f"(d[6]), "+f"(d[7]),
          "+f"(d[8]), "+f"(d[9]), "+f"(d[10]), "+f"(d[11]), "+f"(d[12]), "+f"(d[13]), "+f"(d[14]), "+f"(d[15]),
          "+f"(d[16]), "+f"(d[17]), "+f"(d[18]), "+f"(d[19]), "+f"(d[20]), "+f"(d[21]), "+f"(d[22]), "+f"(d[23]),
          "+f"(d[24]), "+f"(d[25]), "+f"(d[26]), "+f"(d[27]), "+f"(d[28]), "+f"(d[29]), "+f"(d[30]), "+f"(d[31]),
          "+f"(d[32]), "+f"(d[33]), "+f"(d[34]), "+f"(d[35]), "+f"(d[36]), "+f"(d[37]), "+f"(d[38]), "+f"(d[39]),
          "+f"(d[40]), "+f"(d[41]), "+f"(d[42]), "+f"(d[43]), "+f"(d[44]), "+f"(d[45]), "+f"(d[46]), "+f"(d[47]),
          "+f"(d[48]), "+f"(d[49]), "+f"(d[50]), "+f"(d[51]), "+f"(d[52]), "+f"(d[53]), "+f"(d[54]), "+f"(d[55]),
          "+f"(d[56]), "+f"(d[57]), "+f"(d[58]), "+f"(d[59]), "+f"(d[60]), "+f"(d[61]), "+f"(d[62]), "+f"(d[63])
        : "r"(a0), "r"(a1), "r"(a2), "r"(a3), "l"(db), "n"(TB));
}
template <int TA, int TB>
__device__ __forceinline__ void wgmma_n8(float (&d)[4], uint64_t da, uint64_t db, int acc = 1) {
    asm volatile("{\n.reg .pred p;\nsetp.ne.b32 p, %8, 0;\n"
        "wgmma.mma_async.sync.aligned.m64n8k16.f32.bf16.bf16 "
        "{%0, %1, %2, %3}, "
        "%4, %5, p, 1, 1, %6, %7;\n}\n"
        : "+f"(d[0]), "+f"(d[1]), "+f"(d[2]), "+f"(d[3])
        : "l"(da), "l"(db), "n"(TA), "n"(TB), "r"(acc));
}

__device__ __forceinline__ uint32_t norm_pair(uint32_t u, float m, float rinv) {
    uint32_t d = pack_bf16(bf_lo(u) - m, bf_hi(u) - m);
    return pack_bf16(bf_lo(d) * rinv, bf_hi(d) * rinv);
}

__global__ void __launch_bounds__(512, 1)
fused_kernel(int by_sm, const __nv_bfloat16* __restrict__ x, const __nv_bfloat16* __restrict__ wqkv, const __nv_bfloat16* __restrict__ wr,
             Scratch* const S, const char* __restrict__ wg, const char* __restrict__ wu, const char* __restrict__ wd, const char* __restrict__ wo,
             const __grid_constant__ CUtensorMap mw, const __grid_constant__ CUtensorMap mx, const __grid_constant__ CUtensorMap mwo,
             const __grid_constant__ CUtensorMap mxs, const __grid_constant__ CUtensorMap mcs, const __grid_constant__ CUtensorMap mout, const __grid_constant__ CUtensorMap mgu, const __grid_constant__ CUtensorMap mwd) {
    extern __shared__ __align__(1024) uint8_t smem[];
    constexpr uint32_t sb = 1024, bars = sb + OFF_BAR, sd = sb >> 4;
    const int tid = threadIdx.x, lane = tid & 31, warp = __shfl_sync(0xffffffffu, tid >> 5, 0);
    uint32_t smid;
    asm("mov.u32 %0, %%smid;" : "=r"(smid));
    const int T = smid >> 1, T8 = T < 32 ? T : T + 1 + (((T - 32) * 37) >> 8), pr = T < 60 ? (~T8 & 7) * 8 + (T8 >> 3) : T < 62 ? T + 4 : T - 2;
    const int fb = by_sm ? pr * 2 + (smid & 1) : blockIdx.x, kc = fb >> 4, c2 = fb & 15;
    const int b = (fb & ~31) | (fb & 1) << 4 | (fb & 31) >> 1;
    const int mt = b >> 4, nt = b & 15, hp = b & 1, cb = nt >> 1;
    const int par = mt >> 2, j0 = (mt & 3) * 256;
    uint8_t* const g_o = S->o;

    if (fb >= 128) {
        if (fb > 128) { nap(16); TS_END(); return; }
        const uint32_t tag = (ld_rlx(&S->epoch) & 1) - 1;
        if (tid < 8) st_rlx2(&S->sel[tid], ~tag, ~tag);
        uint4 ra, rb;
#pragma unroll 1
        for (int it = 0; it < SPIN_LIMIT; it++) {
            ra = ld_rlx4(&S->rec[tid * 2]); rb = ld_rlx4(&S->rec[1024 + tid * 2]);
            if (!((mism(ra.x, ra.z, tag) | mism(rb.x, rb.z, tag)) & 0x8000u)) break;
        }
        __syncwarp();
        TSC(tid == 0, 31);
        sts4(sb + 1024 + tid * 16, ra.y, rb.y, ra.w, rb.w);
        uint4 k = make_uint4(ra.x, ra.z, rb.x, rb.z);
        uint32_t cand;
#pragma unroll 1
        for (int pass = 0; pass < 2; pass++) {
            const uint32_t a0 = max(k.x, k.y), a1 = min(k.x, k.y), a2 = max(k.z, k.w), a3 = min(k.z, k.w), c1 = min(a0, a2), c2 = max(a1, a3);
            k = make_uint4(max(a0, a2), max(c1, c2), min(c1, c2), min(a1, a3));
#pragma unroll
            for (int r = 0; r < 8; r++) {
                const uint32_t m = redux_max(k.x);
                if (lane == r) cand = m;
                if (k.x == m) k = make_uint4(k.y, k.z, k.w, 0);
            }
            if (pass) break;
            if (lane < 8) sts1(sb + (warp * 8 + lane) * 4, cand);
            __syncthreads();
            if (warp) { TS_END(); return; }
            k = lds4(sb + lane * 16);
        }
        if (lane < 8) st_rlx2(&S->sel[lane], cand, lds1(sb + 1024 + (~cand & 0x7ffu) * 4));
        TSC(tid == 0, 20);
        TS_END();
        return;
    }
    auto kblock = [&](int p) { return p; };
    auto load_stage = [&](int p, uint32_t so, int bi, int lag) {
        const int kc0 = kblock(p) * 64;
        const uint32_t fa = bars + 8 * (B_FULLA + bi), fb = bars + 8 * (B_FULLB + bi);
        mbar_expect_tx(fa, 40960);
        if (lag < 0) tma_3d(sb + so + 16384, &mw, fa, nt * 64, kc0, 0);
        tma_4d(sb + so, &mx, fa, par * 1024 + kc0, 0, (j0 >> 5) + 4, 0);
        mbar_expect_tx(fb, 16384);
        tma_4d(sb + so + 40960, &mx, fb, par * 1024 + kc0, 0, j0 >> 5, 0);
        if (lag >= 0) { nap(lag); tma_3d(sb + so + 16384, &mw, fa, nt * 64, kc0, 0); }
    };
    auto prefetch_w = [&](int part, int p0) { prefetch_l2(wqkv + (size_t)(kblock(p0 + (lane >> 3)) * 64 + mt * 8 + (lane & 7)) * 3072 + part * 1024 + nt * 64); };
    auto prefetch_x = [&](int c) { prefetch_l2(x + (size_t)((j0 + nt * 16 + (lane >> 1)) * 2 + par) * 1024 + c * 128 + (lane & 1) * 64); };
    uint32_t epoch;
    if (warp >> 2 == 2) epoch = ld_rlx(&S->epoch);
    if (warp == 12) {
        if (elect_one()) {
#pragma unroll
            for (int i = 0; i < B_ROW; i++) mbar_init(bars + 8 * i, 1);
            asm volatile("fence.mbarrier_init.release.cluster;" ::: "memory");
            load_stage(0, STAGE, 0, -1);
        }
    } else {
        if (warp > 12) {
            if (lane < 8) prefetch_w(warp - 13, 0);
        } else if (warp >= 10 && warp < 10 + N_X0) prefetch_x(warp - 10);
        if (warp == 0 && elect_one()) {
#pragma unroll
            for (int i = B_ROW; i < B_WOFULL; i++) mbar_init(bars + 8 * i, i >= B_FFULL && i < B_FEMPTY ? 5 : 1);
            mbar_expect_tx(bars + 8 * (B_ROW + 4), 2048);
            bulk_g2s(sb + OFF_FA, wr, 2048, bars + 8 * (B_ROW + 4));
        }
        if (warp == 1 && elect_one()) {
#pragma unroll
            for (int i = B_EMPTY; i < NBAR; i++) mbar_init(bars + 8 * i, i < B_UPD ? 2 : i < B_AUX ? 4 : i == B_AUX ? 7 : i == B_CSDONE ? 3 : 8);
        }
    }
    __syncthreads();
    if (warp == 12 && elect_one()) {
#pragma unroll 1
        for (int p = 1; p < 3; p++) { nap(N_S1); load_stage(p, p == 2 ? 0 : 2 * STAGE, p, -1); }
    }
    __syncwarp();

    if (warp >= 12) {
        reg_dec<24>();
        if (warp > 12) {
            const int p = warp - 13;
            const uint32_t t0 = now();
#pragma unroll 1
            for (int i = 0; i < 4; i++) {
                until(t0 + (p == 0 ? T_X + i * D_X : p == 1 ? T_W + i * D_W : T_ROW + i * D_R));
                if (p == 0) { prefetch_x(min(N_X0 + 2 * i, 7)); prefetch_x(min(N_X0 + 1 + 2 * i, 7)); }
                else if (p == 1) {
#pragma unroll 1
                    for (int c = 0; c < 3; c++) prefetch_w(c, min(3 + i * 4, 12));
                } else if (elect_one()) {
                    mbar_expect_tx(bars + 8 * (B_ROW + i), 8192);
                    tma_3d(sb + OFF_FW + i * 8192, &mxs, bars + 8 * (B_ROW + i), 0, j0 + nt * 16, par * 16 + i * 4);
                }
            }
            until(t0 + T_CS);
            const uint32_t stg = sb + OFF_FW + 32768 + p * 4096 + lane * 16;
            float c[8];
#pragma unroll
            for (int i = 0; i < 8; i++) c[i] = 0.f;
#pragma unroll 1
            for (int n = 0; n < 10; n++) {
                const uint32_t bo = (n & 1) * 2048, bar = bars + 8 * (B_CS + 2 * p + (n & 1));
                if (n >= 2) {
                    mbar_wait(bar, ~(n >> 1) & 1);
#pragma unroll 2
                    for (int i = 0; i < 4; i++) {
                        const uint4 v = lds4(stg + bo + i * 512);
                        c[0] += bf_lo(v.x); c[1] += bf_hi(v.x); c[2] += bf_lo(v.y); c[3] += bf_hi(v.y);
                        c[4] += bf_lo(v.z); c[5] += bf_hi(v.z); c[6] += bf_lo(v.w); c[7] += bf_hi(v.w);
                    }
                    asm volatile("" :: "f"(c[7]));
                    __syncwarp();
                }
                if (n < 8 && elect_one()) {
                    mbar_expect_tx(bar, 2048);
                    tma_3d(sb + OFF_FW + 32768 + p * 4096 + bo, &mcs, bar, p * 1024 + nt * 64, mt * 8, 2 * n);
                }
            }
            sts4(stg + lane * 16, __float_as_uint(c[0]), __float_as_uint(c[1]), __float_as_uint(c[2]), __float_as_uint(c[3]));
            sts4(stg + lane * 16 + 16, __float_as_uint(c[4]), __float_as_uint(c[5]), __float_as_uint(c[6]), __float_as_uint(c[7]));
            bar_sync(13, 128);
            const uint32_t tag = lds1(sb + OFF_TAG);
            float* gcs = &S->cs[0][p * 1024 + nt * 64];
            {
                const float2 a0 = lds2f(stg - lane * 8), a1 = lds2f(stg - lane * 8 + 256), a2 = lds2f(stg - lane * 8 + 512), a3 = lds2f(stg - lane * 8 + 768);
                st_rlx2(gcs + mt * 3072 + lane * 2, tagf((a0.x + a1.x) + (a2.x + a3.x), tag), __float_as_uint((a0.y + a1.y) + (a2.y + a3.y)));
            }
            fence_async_smem();
            __syncwarp();
            if (lane == 0) mbar_arrive(bars + 8 * B_CSDONE);
            TSC(warp == 13 && lane == 0, 19);
            {
                uint4 v[4];
                const float* src = gcs + (lane >> 4) * 4 * 3072 + (lane & 15) * 4;
#pragma unroll 1
                for (int it = 0; it < SPIN_LIMIT; it++) {
#pragma unroll
                    for (int m = 0; m < 4; m++) v[m] = ld_rlx4(src + m * 3072);
                    if (!((mism(v[0].x, v[1].x, tag) | mism(v[2].x, v[3].x, tag)) & 1)) break;
                }
                __syncwarp();
#pragma unroll
                for (int c = 0; c < 4; c++) {
                    const float a = (__uint_as_float((&v[0].x)[c]) + __uint_as_float((&v[1].x)[c])) + (__uint_as_float((&v[2].x)[c]) + __uint_as_float((&v[3].x)[c]));
                    (&v[0].x)[c] = __float_as_uint(a + __shfl_xor_sync(0xffffffffu, a, 16));
                }
                const uint32_t ca = sb + OFF_CS + p * 384 + ((lane & 15) >> 1) * 48 + (lane & 1) * 8;
#pragma unroll 1
                for (int r = 0; r < 3; r++) {
                    const uint32_t u0 = pack_bf16(__uint_as_float(v[0].x), __uint_as_float(v[0].y)), u1 = pack_bf16(__uint_as_float(v[0].z), __uint_as_float(v[0].w));
                    sts2(ca + r * 16, u0, u1);
                    v[0].x = __float_as_uint(__uint_as_float(v[0].x) - bf_lo(u0)); v[0].y = __float_as_uint(__uint_as_float(v[0].y) - bf_hi(u0));
                    v[0].z = __float_as_uint(__uint_as_float(v[0].z) - bf_lo(u1)); v[0].w = __float_as_uint(__uint_as_float(v[0].w) - bf_hi(u1));
                }
                if (lane < 20) sts1(sb + OFF_CS + 1152 + lane * 4, 0);
                fence_async_smem();
            }
            __syncwarp();
            if (lane == 0) mbar_arrive(bars + 8 * B_AUX);
            TSC(warp == 13 && lane == 0, 21);
            mbar_wait(bars + 8 * B_PART, 0);
            mbar_wait(bars + 8 * (B_EMPTY + 2), 0);
            if (p == 0) {
                uint4 v[4];
#pragma unroll
                for (int c = 0; c < 4; c++) v[c] = make_uint4(0, 0, 0, 0);
                const uint32_t* hsrc = &S->halo[b - 16][lane * 4];
#pragma unroll 1
                for (int it = 0; it < SPIN_LIMIT && j0; it++) {
#pragma unroll
                    for (int c = 0; c < 4; c++) v[c] = ld_rlx4(hsrc + c * 128);
                    if (!((mism(v[0].x, v[1].x, tag) | mism(v[2].x, v[3].x, tag)) & 1)) break;
                }
#pragma unroll
                for (int c = 0; c < 4; c++) sts4(sb + OFF_HALO + c * 512 + lane * 16, v[c].x, v[c].y, v[c].z, v[c].w);
                __syncwarp();
                bar_arrive(3, 64);
                TSC(TIMING == 11 && lane == 0, 34);
            } else {
                const int w = p - 1;
                const uint8_t* osrc = g_o + (size_t)((mt * 2 + hp) * 2 + w) * 131072;
                const bool far = w > hp && j0 && lane >= 16;
                const uint32_t* hsrc = &S->hint[mt * 16 + (lane & 15) - (far ? 16 : 0)][0];
                const uint32_t tn = now();
                if (lane == 0 && !w) st_rlx(&S->hint[b][0], tagw(tn, 1u, tag));
                uint32_t hv;
#pragma unroll 1
                for (int it = 0; it < SPIN_LIMIT; it++) {
                    hv = ld_rlx(hsrc);
                    if (!__any_sync(0xffffffffu, (hv ^ tag) & 1)) break;
                }
                TSC(TIMING == 11 && lane == 0, 32 + w);
                hv = redux_max(hv - tn + (far ? 0x40000000u + T_H : 0x40000000u)) + tn - 0x40000000u + T_O + w * T_O1;
                mbar_wait(bars + 8 * (w ? B_AST : B_G1DONE), 0);
                if (elect_one()) {
#pragma unroll 1
                    for (int st = 0; st < 8; st++) {
                        const uint32_t full = bars + 8 * (B_OFULL + 8 * w + st);
                        if (st == 2 && !w) { until(hv + T_GO); mbar_arrive(bars + 8 * B_GO); }
                        if (st >= 2) mbar_wait(full + 8 * (B_DONE - B_OFULL - 2), 0);
                        if (st < 3) until(hv + (st == 2 ? T_S2 : st * T_S1));
                        TSC(st == 0, 28 + w);
                        mbar_expect_tx(full, 16384);
                        bulk_g2s(sb + (w ? OFF_O1 : OFF_O0) + (st & 1) * 16384, osrc + st * 16384, 16384, full);
                    }
                }
            }
            TS_END();
            return;
        }
        if (elect_one()) {
            auto load_wo = [&](int s, int ws) {
                mbar_expect_tx(bars + 8 * (B_WOFULL + s), 32768);
                tma_4d(sb + OFF_WO + ws * 32768, &mwo, bars + 8 * (B_WOFULL + s), 0, s * 8, 0, cb * 2);
            };
            uint32_t so = STAGE, ph = 0, cnt = PF_CNT;
            int bi = 0, q = 0;
            if (smem_u32(smem) != sb) __trap();
            const char* pf = (b < 64 ? wg : wu) + (b & 63) * 7168;
#pragma unroll 1
            for (int p = 3; p < 16; p++) {
                mbar_wait(bars + 8 * (B_EMPTY + bi), ph);
                load_stage(p, so, bi, W_LAG);
#pragma unroll 1
                for (int e = q + (cnt & 3); q < e; q++) {
                    if (q == 16) pf = wd + mt * 7 * 131072 + nt * 8192;
                    if (q == 23) pf = wo + b * 8192;
                    bulk_prefetch(pf, q < 16 ? 7168 : 8192);
                    pf += q < 16 ? 64 * 7168 : q < 23 ? 131072 : 1048576;
                }
                cnt >>= 2;
                so = so == 2 * STAGE ? 0 : so + STAGE;
                if (++bi == 3) { bi = 0; ph ^= 1; }
            }
            TS(27);
            int ws = 1;
#pragma unroll 1
            for (int i = 0; i < 8; i++) {
                if (i == 1) {
                    mbar_wait(bars + 8 * (B_EMPTY + 2), 0);
                    mbar_expect_tx(bars + 8 * B_F2FULL, 8192);
                    tma_2d(sb + OFF_F2X, &mwd, bars + 8 * B_F2FULL, DBG_F2 * c2 * 64, DBG_F2 * kc * 448);
#pragma unroll 1
                    for (int c = 0; c < 2; c++) {
                        if (c) mbar_wait(bars + 8 * XR_GATE, 0);
                        mbar_expect_tx(bars + 8 * B_XR, 16384);
                        tma_4d(sb + c * STAGE, &mx, bars + 8 * B_XR, DBG_XR * (par * 1024 + cb * 128 + c * 64), 0, DBG_XR * ((j0 >> 5) + hp * 4), 0);
                    }
                } else {
                    mbar_wait(bars + 8 * (i == 0 ? B_EMPTY + 1 : i == 2 ? B_F2DONE : B_DONE - NWO + i), 0);
                    if (i) mbar_wait(bars + 8 * (i == 2 ? B_OFULL : B_DONE + 8 - NWO + i), 0);
                }
                load_wo(i < 2 ? 1 - i : i, i == 1 ? 0 : ws);
                if (i != 1 && ++ws == NWO) ws = 0;
            }
        }
        TS_END();
    } else if (warp >= 8) {
        reg_dec<40>();
        const int p = warp - 8;
        const bool f1 = fb < 112;
        auto ffn_w = [&](int n, int s) {
            const uint32_t dst = sb + OFF_FW + s * 16384;
            if (n < 8) {
                mbar_expect_tx(bars + 8 * (B_FFULL + s), 16384);
                tma_3d(dst, &mgu, bars + 8 * (B_FFULL + s), DBG_F1 * fb * 32, n * 128, 0);
            } else {
                mbar_expect_tx(bars + 8 * B_F2FULL, 16384);
                tma_2d(dst, &mwd, bars + 8 * B_F2FULL, DBG_F2 * c2 * 64, DBG_F2 * kc * 448 + 64 + s * 128);
                tma_2d(dst + 8192, &mwd, bars + 8 * B_F2FULL, DBG_F2 * c2 * 64, DBG_F2 * kc * 448 + 128 + s * 128);
            }
        };
        const uint32_t tag = (epoch & 1) - 1;
        {
            const int ta = tid - 256;
            if (ta < 48) st_rlx4(&S->cs[mt][(ta >> 4) * 1024 + nt * 64 + (ta & 15) * 4], ~tag, ~tag, ~tag, ~tag);
            st_rlx4(&S->ypart[kc][ta >> 4][c2 * 64 + (ta & 15) * 4], ~tag, ~tag, ~tag, ~tag);
            if (p == 3 && f1) st_rlx4(&S->h[fb * 128 + lane * 4], ~tag, ~tag, ~tag, ~tag);
            if (ta < 2) st_rlx4(&S->hint[b][ta * 4], ~tag, ~tag, ~tag, ~tag);
            st_rlx4(&S->halo[b][ta * 4], ~tag, ~tag, ~tag, ~tag);
        }
        float s1 = 0.f, s2 = 0.f, sr = 0.f, sw = 0.f, sh = 0.f;
        {
            const uint32_t xa = sb + OFF_FW + p * 512 + lane * 16, wa = sb + OFF_FA + (((p * 4 + (lane >> 3)) ^ lane) & 7) * 16;
            mbar_wait(bars + 8 * (B_ROW + 4), 0);
#pragma unroll 1
            for (int i = 0; i < 4; i++) {
                const uint4 q = lds4(sb + OFF_FA + i * 512 + lane * 16);
                sw += ((bf_lo(q.x) + bf_hi(q.x)) + (bf_lo(q.y) + bf_hi(q.y))) + ((bf_lo(q.z) + bf_hi(q.z)) + (bf_lo(q.w) + bf_hi(q.w)));
            }
#pragma unroll 1
            for (int o = 1; o < 32; o <<= 1) sw += __shfl_xor_sync(0xffffffffu, sw, o);
            {
                float c1 = 0.f, c2 = 0.f, cr = 0.f;
#pragma unroll 1
                for (int q = 0; q < 4; q++) {
                mbar_wait(bars + 8 * (B_ROW + q), 0);
                TSC(tid == 256 && q == 3, 17);
#pragma unroll
                for (int i = 0; i < 4; i++) {
                    const uint4 u = lds4(xa + q * 8192 + i * 2048), w4 = lds4(wa + q * 512 + i * 128);
                    if (DBG_ST == 1) { s2 += fabsf(bf_lo(u.x ^ (u.y & u.z & u.w & 1))); sr += bf_lo(w4.x ^ w4.y ^ w4.z ^ w4.w ^ u.x); continue; }
                    const float a0 = bf_lo(u.x), a1 = bf_hi(u.x), a2 = bf_lo(u.y), a3 = bf_hi(u.y), a4 = bf_lo(u.z), a5 = bf_hi(u.z), a6 = bf_lo(u.w), a7 = bf_hi(u.w);
                    s1 += a0 + a1; c1 += a4 + a5; s1 += a2 + a3; c1 += a6 + a7;
                    s2 = fmaf(a0, a0, s2); c2 = fmaf(a4, a4, c2); sr = fmaf(a0, bf_lo(w4.x), sr); cr = fmaf(a4, bf_lo(w4.z), cr);
                    s2 = fmaf(a1, a1, s2); c2 = fmaf(a5, a5, c2); sr = fmaf(a1, bf_hi(w4.x), sr); cr = fmaf(a5, bf_hi(w4.z), cr);
                    s2 = fmaf(a2, a2, s2); c2 = fmaf(a6, a6, c2); sr = fmaf(a2, bf_lo(w4.y), sr); cr = fmaf(a6, bf_lo(w4.w), cr);
                    s2 = fmaf(a3, a3, s2); c2 = fmaf(a7, a7, c2); sr = fmaf(a3, bf_hi(w4.y), sr); cr = fmaf(a7, bf_hi(w4.w), cr);
                }
                }
                s1 += c1; s2 += c2; sr += cr;
            }
#pragma unroll 1
            for (int pass = 0;; pass++) {
#pragma unroll
                for (int o = 1; o < 8; o <<= 1) {
                    s1 += __shfl_xor_sync(0xffffffffu, s1, o); s2 += __shfl_xor_sync(0xffffffffu, s2, o); sr += __shfl_xor_sync(0xffffffffu, sr, o);
                }
                s1 *= 1.f / 1024.f;
                s2 = fmaf(-s1, s1, s2 * (1.f / 1024.f));
                if (!__any_sync(0xffffffffu, !pass && s1 * s1 > 256.f * s2)) break;
                sh = bf16r(s1); s1 = 0.f; s2 = 0.f; sr = 0.f;
#pragma unroll 1
                for (uint32_t o = 0; o < 2048; o = opaque(o + ((o & 12) == 12 ? 116 : 4))) {
                    const uint32_t u = lds1(xa + (o >> 7) * 2048 + (o & 12)), q = lds1(wa + o);
                    const float a0 = bf_lo(u) - sh, a1 = bf_hi(u) - sh;
                    s1 += a0 + a1; s2 = fmaf(a0, a0, fmaf(a1, a1, s2)); sr = fmaf(a0, bf_lo(q), fmaf(a1, bf_hi(q), sr));
                }
            }
        }
        const int ta = opaque(tid) - 256, lane = ta & 31, g = lane >> 2, t = lane & 3;
        {
            if ((lane & 7) == 0) {
                const int s = b * 16 + p * 4 + (lane >> 3);
                const float mb = bf16r(sh + s1);
                float den;
                asm("sqrt.approx.f32 %0, %1;" : "=f"(den) : "f"(bf16r(bf16r(s2) + 1e-5f)));
                den = bf16r(den);
                uint32_t rb = pack_bf16(fmaf(sh - mb, sw, sr) * rcp(den), 0.f);
                if (rb == 0x8000u) rb = 0;
                uint32_t ord = (rb & 0x8000u) ? (~rb & 0xffffu) : (rb | 0x8000u);
                if ((rb & 0x7fffu) > 0x7f80u) ord = 0;
                st_rlx2(&S->rec[s], (ord << 16) | (tag & 0x8000u) | (0x47ffu - (s & 1023) * 2 - par), pack_bf16(mb, den));
            }
            bar_sync(12, 128);
            if (p == 1) sts1(sb + OFF_ROWMAP + lane * 4, 0xffffffffu);
            if (p == 0) {
                if (lane == 0) {
                    sts1(sb + OFF_TAG, tag);
                    if (f1 && EARLY_FILL > 0) ffn_w(0, 0);
                }
                __syncwarp();
                bar_arrive(13, 128);
            }
            TSC(ta == 0, 18);
        }
        {
            uint2 r[3];
            nap(N_GA);
            const uint2* src = &S->rec[mt * 256 + ta];
            const int l2 = ta < 8 && j0 ? -8 : 0;
#pragma unroll 1
            for (int it = 0; it < SPIN_LIMIT; it++) {
                r[0] = ld_rlx2(src + l2); r[1] = ld_rlx2(src); r[2] = ld_rlx2(src + 128);
                if (!((mism(r[0].x, r[1].x, tag) | (r[2].x ^ tag)) & 0x8000u)) break;
            }
#pragma unroll
            for (int n = 0; n < 3; n++)
                if (n || ta < 8) sts2(sb + OFF_STAT + (n ? n * 1024 - 960 : 0) + ta * 8, (r[n].y << 16) ^ 0x80000000u, __float_as_uint(rcp(bf_hi(r[n].y))));
        }
        __syncwarp();
        if (lane == 0) mbar_arrive(bars + 8 * B_AUX);
        TSC(ta == 0, 30);
        if (EARLY_FILL > 1 && f1 && p == 0 && elect_one()) ffn_w(1, 1);
        uint2 sel;
#pragma unroll 1
        for (int it = 0; it < SPIN_LIMIT; it++) {
            sel = ld_rlx2(&S->sel[lane & 7]);
            if (!__any_sync(0xffffffffu, (sel.x ^ tag) & 0x8000u)) break;
            __nanosleep(POLL_NS);
        }
        TSC(ta == 0, 26);
        if (b == 0 && ta == 0) st_rlx(&S->epoch, epoch + 1);
        {
            const __nv_bfloat16* xp = x + (~sel.x & 0x7ffu) * 1024 + (ta >> 3) * 8;
            const float mb = bf_lo(sel.y), rinv = rcp(bf_hi(sel.y));
            uint4 v = ldg_nc(xp);
            int s = f1 ? 0 : 2;
#pragma unroll 1
            for (int n = f1 ? 0 : 8; n < (p ? 8 : 11); n++) {
                mbar_wait(bars + 8 * (f1 ? B_FEMPTY + s : B_PART), f1 && (n < 3 || (n >= 6 && n < 9)));
                if (p == 0 && s == 2) mbar_wait(bars + 8 * B_CSDONE, 0);
                if (p == 0 && n >= EARLY_FILL && elect_one()) ffn_w(n, s);
                if (n < 8) {
                    sts4(sb + OFF_FA + s * 2048 + ta * 16, norm_pair(v.x, mb, rinv), norm_pair(v.y, mb, rinv), norm_pair(v.z, mb, rinv), norm_pair(v.w, mb, rinv));
                    fence_async_smem();
                    __syncwarp();
                    if (lane == 0) mbar_arrive(bars + 8 * (B_FFULL + s));
                    v = ldg_nc(xp + ((n + 1) & 7) * 128);
                }
                if (++s == 3) s = 0;
            }
        }
        mbar_wait(bars + 8 * B_PART, 0);
        if (f1 && p >= 2) {
            const uint32_t pa = sb + OFF_FA + (ta - 64) * 16, go = wu < wg ? 1024 : 0;
            const float4 g0 = lds4f(pa + go), g1 = lds4f(pa + 2048 + go), u0 = lds4f(pa + (go ^ 1024)), u1 = lds4f(pa + 2048 + (go ^ 1024));
            float hv[4];
#pragma unroll
            for (int c = 0; c < 4; c++) {
                const float ga = bf16r((&g0.x)[c] + (&g1.x)[c]), up = bf16r((&u0.x)[c] + (&u1.x)[c]);
                hv[c] = bf16r(ga * sigmoidf(ga)) * up;
            }
#pragma unroll
            for (int hh = 0; hh < 2; hh++) {
                const float o = __shfl_xor_sync(0xffffffffu, (g & 1) ? hv[2 * hh] : hv[2 * hh + 1], 4);
                st_rlx(&S->h[(fb * 4 + (p & 1) * 2 + hh) * 32 + (2 * t + (g & 1)) * 4 + (g >> 1)],
                       tagw((g & 1) ? pack_bf16(o, hv[2 * hh + 1]) : pack_bf16(hv[2 * hh], o), g < 2, tag));
            }
            TSC(ta == 64, 22);
        }
        {
            uint4 hq[4];
            const uint32_t* hp4 = S->h + kc * 1792 + ta * 4;
#pragma unroll 1
            for (int it = 0; it < SPIN_LIMIT; it++) {
#pragma unroll
                for (int n = 0; n < 4; n++) hq[n] = ld_rlx4(hp4 + (n < 3 ? n * 512 : p < 2 ? 1536 : 0));
                if (!((mism(hq[0].x, hq[1].x, tag) | mism(hq[2].x, hq[3].x, tag)) & 1)) break;
            }
            mbar_wait(bars + 8 * B_G1DONE, 0);
            bar_sync(12, 128);
#pragma unroll
            for (int n = 0; n < 4; n++) sts4(sb + OFF_FA + ta * 16 + (n < 3 ? n * 2048 : p < 2 ? 6144 : 0), hq[n].x, hq[n].y, hq[n].z, hq[n].w);
            fence_async_smem();
            bar_sync(12, 128);
            TSC(ta == 0, 25);
            mbar_wait(bars + 8 * B_F2FULL, 0);
            mbar_wait(bars + 8 * B_ATT, 0);
            float acc[4] = {0.f, 0.f, 0.f, 0.f};
            uint32_t da = sd + dlo(OFF_F2X, 8192), db = sd + dlo(OFF_FA, 128);
#pragma unroll 1
            for (int q = 0; q < 7; q++) {
                wg_fence();
#pragma unroll
                for (int j = 0; j < 4; j++) wgmma_n8<1, 0>(acc, mkdesc(da + j * 128, dhi(1024, 1)), mkdesc(db + j * 16, dhi(128, 0)));
                wg_commit();
                da = sd + dlo(OFF_FW, 8192) + q * 512; db += 64;
            }
            wg_wait<0>();
            if (ta == 0) mbar_arrive(bars + 8 * B_F2DONE);
#pragma unroll
            for (int c = 0; c < 4; c++) st_rlx(&S->ypart[kc][2 * t + (c & 1)][c2 * 64 + p * 16 + (c >> 1) * 8 + g], tagf(acc[c], tag));
            TSC(ta == 0, 23);
            bar_sync(12, 128);
        }
#pragma unroll 1
        for (int j = 2 * p; j < 2 * p + 2; j++) {
            const uint32_t kj = __shfl_sync(0xffffffffu, sel.x, j);
            const int row = 0x7ff - (kj & 0x7ffu), jj = (row >> 1) - j0 - hp * 128;
            float a0 = 0.f, a1 = 0.f, a2 = 0.f, a3 = 0.f, sig = 0.f;
            if ((row & 1) == par && jj >= 0 && jj < 128) {
                sig = bf16r(sigmoidf(__uint_as_float(((int)kj < 0 ? kj ^ 0x80000000u : ~kj) & 0xffff0000u)));
#pragma unroll 1
                for (int hh = 0; hh < 8; hh += 4) {
                    uint4 v[4];
#pragma unroll 1
                    for (int it = 0; it < SPIN_LIMIT; it++) {
#pragma unroll
                        for (int m = 0; m < 4; m++) v[m] = ld_rlx4(&S->ypart[hh + m][j][cb * 128 + lane * 4]);
                        if (!((mism(v[0], tag) | mism(v[1], tag) | mism(v[2], tag) | mism(v[3], tag)) & 1)) break;
                    }
#pragma unroll
                    for (int m = 0; m < 4; m++) { a0 += __uint_as_float(v[m].x); a1 += __uint_as_float(v[m].y); a2 += __uint_as_float(v[m].z); a3 += __uint_as_float(v[m].w); }
                }
                asm volatile("st.shared.u8 [%0], %1;" ::"r"(sb + OFF_ROWMAP + jj), "r"(j) : "memory");
            }
            sts2(sb + OFF_FA + (lane >> 1) * 128 + j * 16 + (lane & 1) * 8, pack_bf16(bf16r(a0) * sig, bf16r(a1) * sig), pack_bf16(bf16r(a2) * sig, bf16r(a3) * sig));
        }
        fence_async_smem();
        __syncwarp();
        if (lane == 0) mbar_arrive(bars + 8 * B_UPD);
        TSC(ta == 0, 24);
        TS_END();
    } else {
        if (elect_one()) {
#pragma unroll
            for (int i = 0; i < (B_EMPTY - B_WOFULL) / 8; i++) mbar_init(bars + 8 * (B_WOFULL + 8 * i + warp), 1);
        }
        reg_inc<224>();
        const int w = warp >> 2, wi = warp & 3, tw = (1 - w) * 4 + wi;
        const bool elect = (tid & 127) == 0;
        const uint32_t ln = opaque(lane), g = ln >> 2, t = ln & 3;
        uint32_t tag, ow[8][4];
        auto store_o = [&](int f0, int f1) {
            uint8_t* ob = g_o + (size_t)((mt * 2 + 1 - w) * 2 + 1 - (wi >> 1)) * 131072 + nt * 1024 + (wi & 1) * 512 + ln * 4;
#pragma unroll
            for (int f = f0; f < f1; f++)
#pragma unroll
                for (int i = 3; i >= 0; i--)
                    st_rlx(ob + f * 16384 + i * 128, ow[f][i]);
        };
        {
            float acc[2][96];
            const uint32_t sta = opaque(sb + OFF_STAT + tw * 256 + 64 + g * 8);
            {
                float fa[4] = {0.f, 0.f, 0.f, 0.f};
                uint32_t so = STAGE >> 4, bo = bars, ph = 0;
                const uint32_t dx0 = sd + dlo(w ? 40960 : 0, 16), dw0 = sd + dlo(16384, 8192);
                int p = 0;
                auto step = [&](bool ffn, int fs, uint32_t fph, bool last) {
                    mbar_wait(bo + 8 * B_FULLA, ph);
                    if (w) mbar_wait(bo + 8 * B_FULLB, ph);
                    TSC(TIMING == 9 && elect && p >= 11, 32 + (p - 11) * 6 + w * 3);
                    if (ffn) mbar_wait(bars + 8 * (B_FFULL + fs), fph);
                    TSC(TIMING == 9 && elect && p >= 11, 33 + (p - 11) * 6 + w * 3);
                    TSC(elect && p == 0, 1 + 8 * w);
                    bar_sync(1 + w, 256);
                    TSC(TIMING == 1 && tid == 0, 32 + p);
                    wg_fence();
                    if (last) {
                        wgmma_n192<0, 1>(acc[0], mkdesc(sd + dlo(OFF_MEAN, 0) + w * 128, dhi(128, 0)), mkdesc(sd + dlo(OFF_CS, 0), dhi(48, 0)));
                        wgmma_n192<0, 1>(acc[1], mkdesc(sd + dlo(OFF_MEAN + 1024, 0) + w * 128, dhi(128, 0)), mkdesc(sd + dlo(OFF_CS, 0), dhi(48, 0)));
                    }
#pragma unroll
                    for (int k = 0; k < 4; k++) {
                        wgmma_n192<0, 1>(acc[0], mkdesc(dx0 + so + k * 2, dhi(1024, 1)), mkdesc(dw0 + so + k * 128, dhi(1024, 1)), k || ffn || last ? 1 : p);
                        wgmma_n192<0, 1>(acc[1], mkdesc(dx0 + so + 512 + k * 2, dhi(1024, 1)), mkdesc(dw0 + so + k * 128, dhi(1024, 1)), k || ffn || last ? 1 : p);
                        if (ffn && k == 2) {
#pragma unroll
                            for (int j = 0; j < 8; j++)
                                wgmma_n8<1, 0>(fa, mkdesc(sd + dlo(OFF_FW, 8192) + fs * 1024 + j * 64, dhi(512, 2)), mkdesc(sd + dlo(OFF_FA, 128) + fs * 128 + j * 16, dhi(128, 0)));
                        }
                    }
                    wg_commit();
                    bar_arrive(2 - w, 256);
                    wg_wait<0>();
                    TSC(TIMING == 9 && elect && p >= 11, 34 + (p - 11) * 6 + w * 3);
                    if (wi == 0 && elect_one()) { mbar_arrive(bo + 8 * B_EMPTY); if (ffn) mbar_arrive(bars + 8 * (B_FEMPTY + fs)); }
                    so = so == 2 * (STAGE >> 4) ? 0 : so + (STAGE >> 4);
                    bo += 8;
                    if (bo == bars + 24) { bo = bars; ph ^= 1; }
                };
                if (w) bar_arrive(1, 256);
                uint32_t fm = opaque((fb < 112 ? (F1_MASK >> (16 * w)) & 0xffff : 0u) | 0x80000000u), fph = 0;
                int fs = w;
#pragma unroll 1
                for (; p < 16; p++) {
                    if (fm & 1) { step(true, fs, fph, false); fs += 2; if (fs >= 3) { fs -= 3; fph ^= 1; } }
                    else if (fm & 0x10000) step(false, 0, 0, true);
                    else step(false, 0, 0, false);
                    fm >>= 1;
                    if (p == P_PART) {
                        if (fb < 112) sts4(sb + OFF_FA + tid * 16, __float_as_uint(fa[0]), __float_as_uint(fa[1]), __float_as_uint(fa[2]), __float_as_uint(fa[3]));
                        __syncwarp();
                        if (lane == 0) mbar_arrive(bars + 8 * B_PART);
                    }
                    if (p != 14) continue;
                    mbar_wait(bars + 8 * B_AUX, 0);
                    mbar_wait(bars + 8 * (B_EMPTY + 1), 0);
                    const uint32_t hm = __float_as_uint(0.5f * lds1f(sb + OFF_STAT + 64 + tw * 256 + ln * 8)) >> 16;
                    sts4(sb + OFF_MEAN + w * 2048 + wi * 256 + (ln >> 4) * 1024 + (ln & 15) * 16, hm * 0x10001u, hm, 0, 0);
                    fence_async_smem();
                }
                if (elect) mbar_arrive(bars + 8 * B_G1DONE);
            }
            TSC(elect, 2 + 8 * w);

            tag = lds1(sb + OFF_TAG);
            mbar_wait(bars + 8 * (B_EMPTY + 2), 0);
            uint32_t pk[4][24];
            const uint32_t hm = tw == 7 ? ~ln & 1 : 0;
            auto np = [&](int i, int j) {
                const float* a = &acc[i >> 1][4 * j + 2 * (i & 1)];
                pk[i][j] = pack_bf16(a[0], a[1]);
                if (j >= 16) pk[i][j] = movm(pk[i][j]);
                if (i == 3 && j >= 8 && !(j & 1)) pk[i][j] = tagw(pk[i][j], hm, tag);
            };
            const uint32_t ha = sb + OFF_HALO + tw * 2048 + ln * 8;
#pragma unroll
            for (int j = 8; j < 24; j += 2) {
                np(3, j); np(3, j + 1);
                sts2(ha + 2048 + (j - 8) * 128, pk[3][j], pk[3][j + 1]);
                asm volatile("{\n.reg .pred p;\nsetp.eq.u32 p, %3, 7;\n@p st.relaxed.gpu.global.v2.u32 [%0], {%1,%2};\n}" ::"l"(&S->halo[b][(j - 8) * 32 + ln * 2]),
                             "r"(pk[3][j]), "r"(pk[3][j + 1]), "r"(tw) : "memory");
            }
            bar_arrive(4 + tw, 64);
            TSC(TIMING == 8 && ln == 0 && wi == 1, 32 + 8 * w);
            mbar_wait(bars + 8 * B_G1DONE, 0);
            const bool u0 = 2 * t > g, u1 = 2 * t + 1 > g;
            const uint32_t mU = (u0 ? 0xffffu : 0u) | (u1 ? 0xffff0000u : 0u);
            uint2 hl[8];
            float rk[4][2], fq[4][2];
            const float mask = tw == 0 && j0 == 0 ? -INFINITY : 0.f;
#pragma unroll
            for (int hd = 0; hd < 2; hd++) {
#pragma unroll
                for (int jj = 0; jj < 12; jj++) {
                    const int j = (jj >> 2) * 8 + hd * 4 + (jj & 3);
                    np(0, j); np(1, j); np(2, j);
                    if (j < 8) np(3, j);
                }
                float s[2][3][4];
#pragma unroll
                for (int h = 1; h >= 0; h--)
#pragma unroll
                    for (int n = 2; n >= 0; n--) {
                        if (h == 0 && n == 0 && hd == 0) {
                            const uint32_t ka = sb + OFF_STAT + tw * 256 + 4 + t * 16, k0 = opaque(ka + (u0 ? 0 : 64)), k1 = opaque(ka + (u1 ? 8 : 72));
#pragma unroll
                            for (int i = 0; i < 4; i++) {
                                const float rq = lds1f(sta + i * 64 + 4) * (0.17677669529663687f * 1.4426950408889634f);
                                rk[i][0] = lds1f(k0 + i * 64); rk[i][1] = lds1f(k1 + i * 64);
                                fq[i][0] = rq * rk[i][0]; fq[i][1] = rq * rk[i][1];
                            }
                            TSC(TIMING == 8 && ln == 0 && wi == 1 && s[1][0][0] + s[0][1][0] != 123.456f, 33 + 8 * w);
                            bar_sync(3 + tw, 64);
#pragma unroll
                            for (int c = 0; c < 8; c++) hl[c] = lds2(ha + c * 256);
                        }
                        const int kg = 2 * h - 1 + n;
                        s[h][n][0] = s[h][n][1] = kg < 0 ? mask : 0.f; s[h][n][2] = s[h][n][3] = 0.f;
#pragma unroll
                        for (int ks = 0; ks < 2; ks++) {
                            const int q = hd * 4 + 2 * ks;
                            const uint32_t* k = kg < 0 ? &hl[hd * 2 + ks].x : &pk[kg < 0 ? 0 : kg][8 + q];
                            mma16816(s[h][n], pk[2 * h][q], pk[2 * h + 1][q], pk[2 * h][q + 1], pk[2 * h + 1][q + 1], k[0], k[1]);
                        }
                    }
                uint32_t pp[4], pc[4];
#pragma unroll
                for (int i = 0; i < 4; i++) {
                    const float* sp = &s[i >> 1][i & 1][2 * (i & 1)];
                    const float* sc = &s[i >> 1][(i & 1) + 1][2 * (i & 1)];
                    float a0 = (u0 ? sp[0] : sc[0]) * fq[i][0], a1 = (u1 ? sp[1] : sc[1]) * fq[i][1];
                    float m = fmaxf(a0, a1);
                    m = fmaxf(m, __shfl_xor_sync(0xffffffffu, m, 1));
                    m = fmaxf(m, __shfl_xor_sync(0xffffffffu, m, 2));
                    a0 = ex2(a0 - m); a1 = ex2(a1 - m);
                    float sum = a0 + a1;
                    sum += __shfl_xor_sync(0xffffffffu, sum, 1);
                    sum += __shfl_xor_sync(0xffffffffu, sum, 2);
                    const float inv = rcp(sum);
                    const uint32_t pw = pack_bf16(a0 * rk[i][0] * inv, a1 * rk[i][1] * inv);
                    pp[i] = pw & mU; pc[i] = pw & ~mU;
                }
                TSC(TIMING == 8 && ln == 0 && wi == 1 && pp[0] + pp[3] != 0x12345, 34 + 2 * hd + 8 * w);
#pragma unroll
                for (int fh = 0; fh < 2; fh++)
#pragma unroll
                    for (int i = 0; i < 4; i++) {
                        const int v = 16 + hd * 4 + 2 * fh;
                        const uint32_t* vp = i ? &pk[i ? i - 1 : 0][v] : &hl[4 + hd * 2 + fh].x;
                        float o[4] = {0.f, 0.f, 0.f, 0.f};
                        if (i & 1) mma16816(o, vp[0], vp[1], pk[i][v], pk[i][v + 1], pp[i], pc[i]);
                        else { mma1688(o, pk[i][v], pk[i][v + 1], pc[i]); mma1688(o, vp[0], vp[1], pp[i]); }
                        const uint32_t tm = (ln & 7) == (nt & 3) * 2 + (i & 1);
                        ow[hd * 4 + 2 * fh][i] = tagw(pack_bf16(o[0], o[1]), tm, tag); ow[hd * 4 + 2 * fh + 1][i] = tagw(pack_bf16(o[2], o[3]), tm, tag);
                    }
                if (hd && ln == 0) mbar_arrive(bars + 8 * B_ATT);
                store_o(hd ? ST_A : 0, hd ? ST_B : ST_A);
                if (!hd && ln == 0) mbar_arrive(bars + 8 * B_AST);
                TSC(TIMING == 11 && !hd && ln == 0 && wi == 3, 45 + w);
                TSC(elect && hd == 0, 3 + 8 * w);
                TSC(TIMING == 8 && ln == 0 && wi == 1, 35 + 2 * hd + 8 * w);
            }
        }
        TSC(elect, 4 + 8 * w);
        mbar_wait(bars + 8 * B_XR, 0);
        float acc2[64];
        const uint32_t xs = sb + (wi & 1) * 8192 + (tw >> 1) * 2048, mad = xs + (ln & 15) * 128;
        {
            const uint32_t sta = sb + OFF_STAT + (8 + hp * 128 + tw * 16 + g) * 8;
            const float2 s0 = lds2f(sta), s1 = lds2f(sta + 64);
            const float m0 = s0.x * s0.y, r0 = 1.f + s0.y, m1 = s1.x * s1.y, r1 = 1.f + s1.y;
#pragma unroll
            for (int j = 0; j < 16; j += 2) {
                uint32_t a0, a1, a2, a3;
                const int ch = (j & 7) + (ln >> 4);
                asm volatile("ldmatrix.sync.aligned.m8n8.x4.shared.b16 {%0,%1,%2,%3}, [%4];" : "=r"(a0), "=r"(a1), "=r"(a2), "=r"(a3)
                             : "r"(mad + (j >> 3) * STAGE + ((ch ^ (ln & 7)) << 4)) : "memory");
                acc2[4 * j + 0] = fmaf(bf_lo(a0), r0, m0); acc2[4 * j + 1] = fmaf(bf_hi(a0), r0, m0);
                acc2[4 * j + 2] = fmaf(bf_lo(a1), r1, m1); acc2[4 * j + 3] = fmaf(bf_hi(a1), r1, m1);
                acc2[4 * j + 4] = fmaf(bf_lo(a2), r0, m0); acc2[4 * j + 5] = fmaf(bf_hi(a2), r0, m0);
                acc2[4 * j + 6] = fmaf(bf_lo(a3), r1, m1); acc2[4 * j + 7] = fmaf(bf_hi(a3), r1, m1);
            }
        }
        TSC(elect, 5 + 8 * w);
        {
            if (ST_B < ST_C) { mbar_wait(bars + 8 * B_GO, 0); store_o(ST_B, ST_C); }
            mbar_wait(bars + 8 * B_ATT, 0);
            const uint32_t ring = sb + (w ? OFF_O1 : OFF_O0), da0 = (ring >> 4) + dlo(0, 1024);
            const uint32_t chk = ring + wi * 256 + (ln >> 3) * 1032 + (g & 1) * 132 + t * 32;
            uint32_t db = sd + dlo(OFF_WO, 16384);
#pragma unroll 1
            for (int s = 0; s < 8; s++) {
                const uint32_t ro = (s & 1) * 16384;
                mbar_wait(bars + 8 * (B_WOFULL + s), 0);
                TSC(TIMING == 11 && tid == 0 && s == 0, 43);
                mbar_wait(bars + 8 * (B_OFULL + s) + 64 * w, 0);
                TSC(TIMING == 11 && tid == 0 && s == 0, 44);
#pragma unroll 1
                for (int it = 0; __any_sync(0xffffffffu, (mism(lds1(chk + ro), lds1(chk + ro + 4096), tag) | mism(lds1(chk + ro + 8192), lds1(chk + ro + 12288), tag)) & 1) && it < SPIN_LIMIT; it++) {
                    NRETRY();
                    const uint32_t fo = wi * 256 + (ln >> 4) * 1024 + (ln & 15) * 16;
                    uint4 v[8];
#pragma unroll
                    for (int c = 0; c < 8; c++) v[c] = ld_rlx4(g_o + (size_t)(((mt * 2 + hp) * 2 + w) * 8 + s) * 16384 + fo + c * 2048);
#pragma unroll
                    for (int c = 0; c < 8; c++) sts4(ring + ro + fo + c * 2048, v[c].x, v[c].y, v[c].z, v[c].w);
                    fence_async_smem();
                    __syncwarp();
                }
                auto issue = [&](bool last) {
                uint32_t e0, e1;
                if (last) {
                    mbar_wait(bars + 8 * B_UPD, 0);
                    int sl0, sl1;
                    asm volatile("ld.shared.s8 %0, [%1];" : "=r"(sl0) : "r"(sb + OFF_ROWMAP + tw * 16 + g) : "memory");
                    asm volatile("ld.shared.s8 %0, [%1];" : "=r"(sl1) : "r"(sb + OFF_ROWMAP + tw * 16 + 8 + g) : "memory");
                    e0 = (sl0 >> 1) == (int)t ? 0x3f80u << ((sl0 & 1) * 16) : 0u; e1 = (sl1 >> 1) == (int)t ? 0x3f80u << ((sl1 & 1) * 16) : 0u;
                }
                bar_sync(1 + w, 256);
                TSC(elect && s == 0, 6 + 8 * w);
                TSC(TIMING == 2 && elect, 32 + 16 * w + s);
                wg_fence();
                if (last) wgmma_rs_n128<1>(acc2, e0, e1, 0u, 0u, mkdesc(sd + dlo(OFF_FA, 0), dhi(128, 0)));
#pragma unroll
                for (int k = 0; k < 8; k++)
                    wgmma_n128<1, 1>(acc2, mkdesc(da0 + (ro >> 4) + k * 128, dhi(128, 0)), mkdesc(db + k * 128, dhi(1024, 1)));
                wg_commit();
                bar_arrive(2 - w, 256);
                if (!last && s == 0) store_o(ST_C, 8);
                db = db == sd + dlo(OFF_WO + (NWO - 1) * 32768, 16384) ? sd + dlo(OFF_WO, 16384) : db + 2048;
                wg_wait<0>();
                if (elect && !last) mbar_arrive(bars + 8 * (B_DONE + s) + 64 * w);
                };
                if (s < 7) issue(false); else issue(true);
            }
#pragma unroll
            for (int i = 0; i < 64; i++) asm volatile("" : "+f"(acc2[i]) :: "memory");
            TSC(elect, 7 + 8 * w);
#pragma unroll
            for (int j = 0; j < 16; j += 2) {
                const int ch = (j & 7) + (ln >> 4);
                asm volatile("stmatrix.sync.aligned.m8n8.x4.shared.b16 [%0], {%1,%2,%3,%4};" ::"r"(mad + (j >> 3) * STAGE + ((ch ^ (ln & 7)) << 4)),
                             "r"(pack_bf16(acc2[4 * j], acc2[4 * j + 1])), "r"(pack_bf16(acc2[4 * j + 2], acc2[4 * j + 3])),
                             "r"(pack_bf16(acc2[4 * j + 4], acc2[4 * j + 5])), "r"(pack_bf16(acc2[4 * j + 6], acc2[4 * j + 7])) : "memory");
                if ((j & 7) == 6) {
                    fence_async_smem();
                    __syncwarp();
                    if (ln == 0) tma_store_2d(&mout, xs + (j >> 3) * STAGE, par * 1024 + cb * 128 + (j >> 3) * 64, j0 + hp * 128 + tw * 16);
                }
            }
            if (ln == 0) asm volatile("cp.async.bulk.commit_group;\ncp.async.bulk.wait_group.read 0;" ::: "memory");
            TSC(elect, 8 + 8 * w);
            TS_END();
        }
    }
}

typedef CUresult (*EncodeFn)(CUtensorMap*, CUtensorMapDataType, cuuint32_t, void*, const cuuint64_t*, const cuuint64_t*, const cuuint32_t*,
                             const cuuint32_t*, CUtensorMapInterleave, CUtensorMapSwizzle, CUtensorMapL2promotion, CUtensorMapFloatOOBfill);

CUtensorMap make_map(EncodeFn fn, const void* base, int rank, const cuuint64_t* dims, const cuuint64_t* strides, const cuuint32_t* box,
                     CUtensorMapSwizzle swz = CU_TENSOR_MAP_SWIZZLE_128B, CUtensorMapL2promotion pro = CU_TENSOR_MAP_L2_PROMOTION_L2_256B) {
    CUtensorMap m;
    cuuint32_t es[5] = {1, 1, 1, 1, 1};
    fn(&m, CU_TENSOR_MAP_DATA_TYPE_BFLOAT16, rank, (void*)base, dims, strides, box, es, CU_TENSOR_MAP_INTERLEAVE_NONE,
       swz, pro, CU_TENSOR_MAP_FLOAT_OOB_FILL_NONE);
    return m;
}

}

extern "C" void kernel_launch(void* const* d_in, const int* in_sizes, int n_in, void* d_out, int out_size) {
    (void)in_sizes; (void)n_in; (void)out_size;
    const __nv_bfloat16* x = (const __nv_bfloat16*)d_in[0];
    const __nv_bfloat16* wqkv = (const __nv_bfloat16*)d_in[1];
    const char* wo = (const char*)d_in[2];
    const __nv_bfloat16* wr = (const __nv_bfloat16*)d_in[4];
    const char* wg = (const char*)d_in[5];
    const char* wu = (const char*)d_in[6];
    const char* wd = (const char*)d_in[7];
    static EncodeFn fn = nullptr;
    static int by_sm = 0;
    static Scratch* scr = nullptr;
    if (!fn) {
        void* p = nullptr; cudaDriverEntryPointQueryResult q;
        cudaGetDriverEntryPoint("cuTensorMapEncodeTiled", &p, cudaEnableDefault, &q);
        fn = (EncodeFn)p;
        cudaFuncSetAttribute(fused_kernel, cudaFuncAttributeMaxDynamicSharedMemorySize, SMEM_LAUNCH);
        cudaGetSymbolAddress((void**)&scr, g_scr);
        int dev = 0, sms = 0;
        cudaGetDevice(&dev);
        cudaDeviceGetAttribute(&sms, cudaDevAttrMultiProcessorCount, dev);
        by_sm = sms == 132;
    }
    const cuuint64_t xd[4] = {2048, 16, 32, 2}, xs[3] = {4096, 131072, 65536};
    const cuuint32_t xb[4] = {64, 16, 4, 2};
    const cuuint64_t wdm[3] = {1024, 1024, 3}, wst[2] = {6144, 2048};
    const cuuint32_t wb[3] = {64, 64, 3};
    const cuuint64_t od[4] = {64, 64, 16, 16}, ost[3] = {2048, 131072, 128};
    const cuuint32_t ob[4] = {64, 8, 16, 2};
    const cuuint64_t yd[2] = {2048, 1024}, yst[1] = {4096};
    const cuuint32_t yb[2] = {64, 16};
    const cuuint64_t sd[3] = {64, 1024, 32}, sst[2] = {4096, 128};
    const cuuint32_t sbx[3] = {64, 16, 4};
    CUtensorMap mxs = make_map(fn, x, 3, sd, sst, sbx);
    const cuuint64_t cd[3] = {3072, 64, 16}, cst[2] = {6144, 393216};
    const cuuint32_t cbx[3] = {64, 8, 2};
    CUtensorMap mcs = make_map(fn, wqkv, 3, cd, cst, cbx, CU_TENSOR_MAP_SWIZZLE_NONE);
    CUtensorMap mx = make_map(fn, x, 4, xd, xs, xb), mw = make_map(fn, wqkv, 3, wdm, wst, wb);
    CUtensorMap mwo = make_map(fn, wo, 4, od, ost, ob), mout = make_map(fn, d_out, 2, yd, yst, yb);
    const cuuint64_t gd[3] = {3584, 1024, 2}, gst[2] = {7168, (cuuint64_t)(wu < wg ? wg - wu : wu - wg)};
    const cuuint32_t gb[3] = {32, 128, 2};
    const cuuint64_t dd[2] = {1024, 3584}, dst[1] = {2048};
    const cuuint32_t db[2] = {64, 64};
    CUtensorMap mgu = make_map(fn, wu < wg ? wu : wg, 3, gd, gst, gb, CU_TENSOR_MAP_SWIZZLE_64B, CU_TENSOR_MAP_L2_PROMOTION_L2_128B);
    CUtensorMap mwd = make_map(fn, wd, 2, dd, dst, db, CU_TENSOR_MAP_SWIZZLE_128B, CU_TENSOR_MAP_L2_PROMOTION_L2_128B);
    fused_kernel<<<132, 512, SMEM_LAUNCH, cudaStreamPerThread>>>(by_sm, x, wqkv, wr, scr, wg, wu, wd, wo, mw, mx, mwo, mxs, mcs, mout, mgu, mwd);
}
```

```cpp
#include <cuda_runtime.h>
#include <cuda.h>
#include <cuda_bf16.h>
#include <stdint.h>

namespace {

constexpr int STAGE = 57344;
constexpr int OFF_FW = 3 * STAGE;
constexpr int OFF_FA = OFF_FW + 49152;
constexpr int OFF_CS = OFF_FA + 6144;
constexpr int OFF_STAT = OFF_CS + 1232;
constexpr int OFF_ROWMAP = OFF_STAT + 2112;
constexpr int OFF_TAG = OFF_ROWMAP + 128;
constexpr int OFF_BAR = OFF_TAG + 8;
constexpr int OFF_F2X = 16384, OFF_HALO = 24576, OFF_O1 = 24576, OFF_O0 = 73728, OFF_WO = 106496, NWO = 3, OFF_MEAN = 2 * STAGE;
static_assert(OFF_WO + NWO * 32768 <= OFF_FA && OFF_O0 + 32768 == OFF_WO && OFF_O1 + 32768 == STAGE, "alias");
constexpr int B_FULLA = 0, B_FULLB = 3, B_ROW = 6, B_FFULL = 11, B_FEMPTY = 14, B_F2DONE = 17, B_GO = 18, B_SW = 19, B_CS = 20, B_WOFULL = 26, B_OFULL = B_WOFULL + 8,
              B_DONE = B_OFULL + 16;
constexpr int B_EMPTY = B_DONE + 16, B_XR = B_EMPTY + 3, B_G1DONE = B_XR + 1;
constexpr int B_UPD = B_G1DONE + 1, B_F2FULL = B_UPD + 1;
constexpr int B_AUX = B_F2FULL + 1, B_PART = B_AUX + 1, B_ATT = B_PART + 1, B_CSDONE = B_ATT + 1, B_AST = B_CSDONE + 1, NBAR = B_AST + 1;
constexpr int SMEM_BYTES = OFF_BAR + NBAR * 8;
static_assert(SMEM_BYTES <= 232448 && OFF_BAR % 8 == 0, "smem");
#define P_PART 13
#define F1_MASK (0x6a005a00u >> (14 - P_PART))
#define PF_CNT 0x2aaaaacu
#define EARLY_FILL 2
#define N_S1 1
#define N_S2 3
#define ST_A 2
#define ST_B 2
#define DBG_F2 1
#define DBG_F1 1
#define DBG_XR 1
#define T_H 250
#define T_O1 250
#define XR_GATE B_G1DONE
#define ST_C 4
#define T_O 2350
#define T_S1 128
#define T_GO 256
#define T_S2 950
#define DBG_CS 0
#define DBG_ST 0
#define N_GA 4
#define N_X 1
#define D_X 2
#define D_R 3
#define N_ROW 5
#define N_W 5
#define K_W1 5
#define K_W2 10
#define N_CS 3
#define N_F1 0
#define POLL_NS 100
#define STATS_UNROLL 4
constexpr int kStatsUnroll = STATS_UNROLL;
constexpr int SPIN_LIMIT = 1 << 18;

struct Scratch {
    uint8_t o[2048 * 1024 * 2];
    uint2 rec[2048];
    float cs[8][3072];
    uint32_t halo[128][512];
    uint32_t h[14336];
    float ypart[8][8][1024];
    uint2 sel[16];
    uint32_t hint[128][8];
    uint32_t epoch;
};
__device__ __align__(1024) Scratch g_scr;

#define TS(i) do {} while (0)
#define TS_END() do {} while (0)
constexpr int SMEM_LAUNCH = SMEM_BYTES;
#define TSC(c, i) do {} while (0)
#define NRETRY() do {} while (0)
__device__ __forceinline__ uint32_t smem_u32(const void* p) { return (uint32_t)__cvta_generic_to_shared(p); }
__device__ __forceinline__ void mbar_init(uint32_t bar, uint32_t cnt) { asm volatile("mbarrier.init.shared::cta.b64 [%0], %1;" ::"r"(bar), "r"(cnt) : "memory"); }
__device__ __forceinline__ void mbar_expect_tx(uint32_t bar, uint32_t bytes) { asm volatile("mbarrier.arrive.expect_tx.shared::cta.b64 _, [%0], %1;" ::"r"(bar), "r"(bytes) : "memory"); }
__device__ __forceinline__ void mbar_arrive(uint32_t bar) { asm volatile("mbarrier.arrive.shared::cta.b64 _, [%0];" ::"r"(bar) : "memory"); }
__device__ __forceinline__ void mbar_wait(uint32_t bar, uint32_t parity) {
    asm volatile("{\n.reg .pred P1;\nLAB_WAIT:\nmbarrier.try_wait.parity.shared::cta.b64 P1, [%0], %1;\n@!P1 bra LAB_WAIT;\n}" ::"r"(bar), "r"(parity) : "memory");
}
__device__ __forceinline__ bool mbar_test(uint32_t bar, uint32_t parity) {
    uint32_t ok;
    asm volatile("{\n.reg .pred p;\nmbarrier.test_wait.parity.shared::cta.b64 p, [%1], %2;\nselp.u32 %0, 1, 0, p;\n}" : "=r"(ok) : "r"(bar), "r"(parity) : "memory");
    return ok;
}
__device__ __forceinline__ void tma_2d(uint32_t dst, const CUtensorMap* m, uint32_t bar, int c0, int c1) {
    asm volatile("cp.async.bulk.tensor.2d.shared::cluster.global.mbarrier::complete_tx::bytes [%0], [%1, {%3, %4}], [%2];" ::"r"(dst), "l"(m), "r"(bar), "r"(c0), "r"(c1) : "memory");
}
__device__ __forceinline__ void tma_3d(uint32_t dst, const CUtensorMap* m, uint32_t bar, int c0, int c1, int c2) {
    asm volatile("cp.async.bulk.tensor.3d.shared::cluster.global.mbarrier::complete_tx::bytes [%0], [%1, {%3, %4, %5}], [%2];" ::"r"(dst), "l"(m), "r"(bar), "r"(c0), "r"(c1), "r"(c2) : "memory");
}
__device__ __forceinline__ void tma_4d(uint32_t dst, const CUtensorMap* m, uint32_t bar, int c0, int c1, int c2, int c3) {
    asm volatile("cp.async.bulk.tensor.4d.shared::cluster.global.mbarrier::complete_tx::bytes [%0], [%1, {%3, %4, %5, %6}], [%2];" ::"r"(dst), "l"(m), "r"(bar), "r"(c0), "r"(c1), "r"(c2), "r"(c3) : "memory");
}
__device__ __forceinline__ void tma_store_2d(const CUtensorMap* m, uint32_t src, int c0, int c1) {
    asm volatile("cp.async.bulk.tensor.2d.global.shared::cta.bulk_group [%0, {%2, %3}], [%1];" ::"l"(m), "r"(src), "r"(c0), "r"(c1) : "memory");
}
__device__ __forceinline__ void bulk_g2s(uint32_t dst, const void* src, uint32_t bytes, uint32_t bar) {
    asm volatile("cp.async.bulk.shared::cluster.global.mbarrier::complete_tx::bytes [%0], [%1], %2, [%3];" ::"r"(dst), "l"(src), "r"(bytes), "r"(bar) : "memory");
}
__device__ __forceinline__ void bulk_prefetch(const void* p, uint32_t bytes) { asm volatile("cp.async.bulk.prefetch.L2.global [%0], %1;" ::"l"(p), "r"(bytes) : "memory"); }
__device__ __forceinline__ void fence_async_smem() { asm volatile("fence.proxy.async.shared::cta;" ::: "memory"); }
__device__ __forceinline__ void wg_fence() { asm volatile("wgmma.fence.sync.aligned;" ::: "memory"); }
__device__ __forceinline__ void wg_commit() { asm volatile("wgmma.commit_group.sync.aligned;" ::: "memory"); }
template <int N> __device__ __forceinline__ void wg_wait() { asm volatile("wgmma.wait_group.sync.aligned %0;" ::"n"(N) : "memory"); }
__device__ __forceinline__ uint64_t mkdesc(uint32_t lo, uint32_t hi) { return ((uint64_t)hi << 32) | lo; }
__host__ __device__ constexpr uint32_t dhi(uint32_t sbo, uint32_t mode) { return (sbo >> 4) | (mode << 30); }
__host__ __device__ constexpr uint32_t dlo(uint32_t off, uint32_t lbo) { return (off >> 4) + ((lbo >> 4) << 16); }
__device__ __forceinline__ bool elect_one() {
    uint32_t e;
    asm volatile("{\n.reg .pred p;\nelect.sync _|p, 0xffffffff;\nselp.u32 %0, 1, 0, p;\n}" : "=r"(e));
    return e;
}
template <int R> __device__ __forceinline__ void reg_inc() { asm volatile("setmaxnreg.inc.sync.aligned.u32 %0;" ::"n"(R)); }
template <int R> __device__ __forceinline__ void reg_dec() { asm volatile("setmaxnreg.dec.sync.aligned.u32 %0;" ::"n"(R)); }
__device__ __forceinline__ void bar_sync(int id, int n) { asm volatile("bar.sync %0, %1;" ::"r"(id), "r"(n) : "memory"); }
__device__ __forceinline__ void bar_arrive(int id, int n) { asm volatile("bar.arrive %0, %1;" ::"r"(id), "r"(n) : "memory"); }
__device__ __forceinline__ uint32_t pack_bf16(float lo, float hi) { uint32_t r; asm("cvt.rn.bf16x2.f32 %0, %1, %2;" : "=r"(r) : "f"(hi), "f"(lo)); return r; }
__device__ __forceinline__ float bf_lo(uint32_t u) { return __uint_as_float(u << 16); }
__device__ __forceinline__ float bf_hi(uint32_t u) { return __uint_as_float(u & 0xffff0000u); }
__device__ __forceinline__ float bf16r(float v) { return bf_lo(pack_bf16(v, 0.f)); }
__device__ __forceinline__ uint32_t tagw(uint32_t w, uint32_t m, uint32_t tag) { uint32_t r; asm("lop3.b32 %0, %1, %2, %3, 0xb8;" : "=r"(r) : "r"(w), "r"(m), "r"(tag)); return r; }
__device__ __forceinline__ uint32_t tagf(float f, uint32_t tag) { return tagw(__float_as_uint(f), 1u, tag); }
__device__ __forceinline__ uint32_t movm(uint32_t a) { uint32_t d; asm volatile("movmatrix.sync.aligned.m8n8.trans.b16 %0, %1;" : "=r"(d) : "r"(a)); return d; }
__device__ __forceinline__ void mma16816(float (&c)[4], uint32_t a0, uint32_t a1, uint32_t a2, uint32_t a3, uint32_t b0, uint32_t b1) {
    asm volatile("mma.sync.aligned.m16n8k16.row.col.f32.bf16.bf16.f32 {%0,%1,%2,%3}, {%4,%5,%6,%7}, {%8,%9}, {%0,%1,%2,%3};"
                 : "+f"(c[0]), "+f"(c[1]), "+f"(c[2]), "+f"(c[3]) : "r"(a0), "r"(a1), "r"(a2), "r"(a3), "r"(b0), "r"(b1));
}
__device__ __forceinline__ void mma1688(float (&c)[4], uint32_t a0, uint32_t a1, uint32_t b0) {
    asm volatile("mma.sync.aligned.m16n8k8.row.col.f32.bf16.bf16.f32 {%0,%1,%2,%3}, {%4,%5}, {%6}, {%0,%1,%2,%3};"
                 : "+f"(c[0]), "+f"(c[1]), "+f"(c[2]), "+f"(c[3]) : "r"(a0), "r"(a1), "r"(b0));
}
__device__ __forceinline__ uint32_t ld_rlx(const void* p) { uint32_t v; asm volatile("ld.relaxed.gpu.global.u32 %0, [%1];" : "=r"(v) : "l"(p) : "memory"); return v; }
__device__ __forceinline__ uint2 ld_rlx2(const void* p) { uint2 v; asm volatile("ld.relaxed.gpu.global.v2.u32 {%0,%1}, [%2];" : "=r"(v.x), "=r"(v.y) : "l"(p) : "memory"); return v; }
__device__ __forceinline__ uint4 ld_rlx4(const void* p) { uint4 v; asm volatile("ld.relaxed.gpu.global.v4.u32 {%0,%1,%2,%3}, [%4];" : "=r"(v.x), "=r"(v.y), "=r"(v.z), "=r"(v.w) : "l"(p) : "memory"); return v; }
__device__ __forceinline__ uint32_t ld_acq(const void* p) { uint32_t v; asm volatile("ld.acquire.gpu.global.u32 %0, [%1];" : "=r"(v) : "l"(p) : "memory"); return v; }
__device__ __forceinline__ void st_rlx(void* p, uint32_t v) { asm volatile("st.relaxed.gpu.global.u32 [%0], %1;" ::"l"(p), "r"(v) : "memory"); }
__device__ __forceinline__ void st_rlx2(void* p, uint32_t a, uint32_t b) { asm volatile("st.relaxed.gpu.global.v2.u32 [%0], {%1,%2};" ::"l"(p), "r"(a), "r"(b) : "memory"); }
__device__ __forceinline__ void st_rlx4(void* p, uint32_t a, uint32_t b, uint32_t c, uint32_t d) { asm volatile("st.relaxed.gpu.global.v4.u32 [%0], {%1,%2,%3,%4};" ::"l"(p), "r"(a), "r"(b), "r"(c), "r"(d) : "memory"); }
__device__ __forceinline__ uint4 ldg_nc(const void* p) { uint4 v; asm volatile("ld.global.nc.v4.u32 {%0,%1,%2,%3}, [%4];" : "=r"(v.x), "=r"(v.y), "=r"(v.z), "=r"(v.w) : "l"(p)); return v; }
__device__ __forceinline__ uint32_t mism(uint32_t a, uint32_t b, uint32_t tag) { uint32_t r; asm("lop3.b32 %0, %1, %2, %3, 0x7e;" : "=r"(r) : "r"(a), "r"(b), "r"(tag)); return r; }
__device__ __forceinline__ uint32_t mism(const uint4& v, uint32_t tag) { return mism(v.x, v.y, tag) | mism(v.z, v.w, tag); }
__device__ __forceinline__ void prefetch_l2(const void* p) { asm volatile("prefetch.global.L2 [%0];" ::"l"(p)); }
__device__ __forceinline__ void touch256(uint32_t dst, const void* p) { asm volatile("cp.async.ca.shared.global.L2::256B [%0], [%1], 4;" ::"r"(dst), "l"(p) : "memory"); }
__device__ __forceinline__ void nap(int n) {
#pragma unroll 1
    for (int i = 0; i < n; i++) __nanosleep(100);
}
__device__ __forceinline__ uint32_t now() { uint32_t t; asm volatile("mov.u32 %0, %%globaltimer_lo;" : "=r"(t)); return t; }
__device__ __forceinline__ void until(uint32_t t) {
    while (t - now() - 1 < 16384u) __nanosleep(50);
}
__device__ __forceinline__ uint32_t opaque(uint32_t v) { return __shfl_xor_sync(0xffffffffu, v, 0); }
__device__ __forceinline__ void sts4(uint32_t a, uint32_t x, uint32_t y, uint32_t z, uint32_t w) { asm volatile("st.shared.v4.u32 [%0], {%1,%2,%3,%4};" ::"r"(a), "r"(x), "r"(y), "r"(z), "r"(w) : "memory"); }
__device__ __forceinline__ void sts2(uint32_t a, uint32_t x, uint32_t y) { asm volatile("st.shared.v2.u32 [%0], {%1,%2};" ::"r"(a), "r"(x), "r"(y) : "memory"); }
__device__ __forceinline__ uint4 lds4(uint32_t a) { uint4 v; asm volatile("ld.shared.v4.u32 {%0,%1,%2,%3}, [%4];" : "=r"(v.x), "=r"(v.y), "=r"(v.z), "=r"(v.w) : "r"(a) : "memory"); return v; }
__device__ __forceinline__ float4 lds4f(uint32_t a) { float4 v; asm volatile("ld.shared.v4.f32 {%0,%1,%2,%3}, [%4];" : "=f"(v.x), "=f"(v.y), "=f"(v.z), "=f"(v.w) : "r"(a) : "memory"); return v; }
__device__ __forceinline__ uint2 lds2(uint32_t a) { uint2 v; asm volatile("ld.shared.v2.u32 {%0,%1}, [%2];" : "=r"(v.x), "=r"(v.y) : "r"(a) : "memory"); return v; }
__device__ __forceinline__ float2 lds2f(uint32_t a) { float2 v; asm volatile("ld.shared.v2.f32 {%0,%1}, [%2];" : "=f"(v.x), "=f"(v.y) : "r"(a) : "memory"); return v; }
__device__ __forceinline__ uint32_t lds1(uint32_t a) { uint32_t v; asm volatile("ld.shared.u32 %0, [%1];" : "=r"(v) : "r"(a) : "memory"); return v; }
__device__ __forceinline__ float lds1f(uint32_t a) { return __uint_as_float(lds1(a)); }
__device__ __forceinline__ void sts1(uint32_t a, uint32_t v) { asm volatile("st.shared.u32 [%0], %1;" ::"r"(a), "r"(v) : "memory"); }
__device__ __forceinline__ uint32_t redux_max(uint32_t v) { uint32_t r; asm volatile("redux.sync.max.u32 %0, %1, 0xffffffff;" : "=r"(r) : "r"(v)); return r; }
__device__ __forceinline__ float ex2(float x) { float r; asm("ex2.approx.ftz.f32 %0, %1;" : "=f"(r) : "f"(x)); return r; }
__device__ __forceinline__ float rcp(float x) { float r; asm("rcp.approx.ftz.f32 %0, %1;" : "=f"(r) : "f"(x)); return r; }
__device__ __forceinline__ float sigmoidf(float v) { return rcp(1.f + ex2(v * -1.4426950408889634f)); }

template <int TA, int TB>
__device__ __forceinline__ void wgmma_n192(float (&d)[96], uint64_t da, uint64_t db, int acc = 1) {
    asm volatile("{\n.reg .pred p;\nsetp.ne.b32 p, %100, 0;\n"
        "wgmma.mma_async.sync.aligned.m64n192k16.f32.bf16.bf16 "
        "{%0, %1, %2, %3, %4, %5, %6, %7, %8, %9, %10, %11, %12, %13, %14, %15, "
        "%16, %17, %18, %19, %20, %21, %22, %23, %24, %25, %26, %27, %28, %29, %30, %31, "
        "%32, %33, %34, %35, %36, %37, %38, %39, %40, %41, %42, %43, %44, %45, %46, %47, "
        "%48, %49, %50, %51, %52, %53, %54, %55, %56, %57, %58, %59, %60, %61, %62, %63, "
        "%64, %65, %66, %67, %68, %69, %70, %71, %72, %73, %74, %75, %76, %77, %78, %79, "
        "%80, %81, %82, %83, %84, %85, %86, %87, %88, %89, %90, %91, %92, %93, %94, %95}, "
        "%96, %97, p, 1, 1, %98, %99;\n}\n"
        : "+f"(d[0]), "+f"(d[1]), "+f"(d[2]), "+f"(d[3]), "+f"(d[4]), "+f"(d[5]), "+f"(d[6]), "+f"(d[7]),
          "+f"(d[8]), "+f"(d[9]), "+f"(d[10]), "+f"(d[11]), "+f"(d[12]), "+f"(d[13]), "+f"(d[14]), "+f"(d[15]),
          "+f"(d[16]), "+f"(d[17]), "+f"(d[18]), "+f"(d[19]), "+f"(d[20]), "+f"(d[21]), "+f"(d[22]), "+f"(d[23]),
          "+f"(d[24]), "+f"(d[25]), "+f"(d[26]), "+f"(d[27]), "+f"(d[28]), "+f"(d[29]), "+f"(d[30]), "+f"(d[31]),
          "+f"(d[32]), "+f"(d[33]), "+f"(d[34]), "+f"(d[35]), "+f"(d[36]), "+f"(d[37]), "+f"(d[38]), "+f"(d[39]),
          "+f"(d[40]), "+f"(d[41]), "+f"(d[42]), "+f"(d[43]), "+f"(d[44]), "+f"(d[45]), "+f"(d[46]), "+f"(d[47]),
          "+f"(d[48]), "+f"(d[49]), "+f"(d[50]), "+f"(d[51]), "+f"(d[52]), "+f"(d[53]), "+f"(d[54]), "+f"(d[55]),
          "+f"(d[56]), "+f"(d[57]), "+f"(d[58]), "+f"(d[59]), "+f"(d[60]), "+f"(d[61]), "+f"(d[62]), "+f"(d[63]),
          "+f"(d[64]), "+f"(d[65]), "+f"(d[66]), "+f"(d[67]), "+f"(d[68]), "+f"(d[69]), "+f"(d[70]), "+f"(d[71]),
          "+f"(d[72]), "+f"(d[73]), "+f"(d[74]), "+f"(d[75]), "+f"(d[76]), "+f"(d[77]), "+f"(d[78]), "+f"(d[79]),
          "+f"(d[80]), "+f"(d[81]), "+f"(d[82]), "+f"(d[83]), "+f"(d[84]), "+f"(d[85]), "+f"(d[86]), "+f"(d[87]),
          "+f"(d[88]), "+f"(d[89]), "+f"(d[90]), "+f"(d[91]), "+f"(d[92]), "+f"(d[93]), "+f"(d[94]), "+f"(d[95])
        : "l"(da), "l"(db), "n"(TA), "n"(TB), "r"(acc));
}
template <int TA, int TB>
__device__ __forceinline__ void wgmma_n128(float (&d)[64], uint64_t da, uint64_t db, int acc = 1) {
    asm volatile("{\n.reg .pred p;\nsetp.ne.b32 p, %68, 0;\n"
        "wgmma.mma_async.sync.aligned.m64n128k16.f32.bf16.bf16 "
        "{%0, %1, %2, %3, %4, %5, %6, %7, %8, %9, %10, %11, %12, %13, %14, %15, "
        "%16, %17, %18, %19, %20, %21, %22, %23, %24, %25, %26, %27, %28, %29, %30, %31, "
        "%32, %33, %34, %35, %36, %37, %38, %39, %40, %41, %42, %43, %44, %45, %46, %47, "
        "%48, %49, %50, %51, %52, %53, %54, %55, %56, %57, %58, %59, %60, %61, %62, %63}, "
        "%64, %65, p, 1, 1, %66, %67;\n}\n"
        : "+f"(d[0]), "+f"(d[1]), "+f"(d[2]), "+f"(d[3]), "+f"(d[4]), "+f"(d[5]), "+f"(d[6]), "+f"(d[7]),
          "+f"(d[8]), "+f"(d[9]), "+f"(d[10]), "+f"(d[11]), "+f"(d[12]), "+f"(d[13]), "+f"(d[14]), "+f"(d[15]),
          "+f"(d[16]), "+f"(d[17]), "+f"(d[18]), "+f"(d[19]), "+f"(d[20]), "+f"(d[21]), "+f"(d[22]), "+f"(d[23]),
          "+f"(d[24]), "+f"(d[25]), "+f"(d[26]), "+f"(d[27]), "+f"(d[28]), "+f"(d[29]), "+f"(d[30]), "+f"(d[31]),
          "+f"(d[32]), "+f"(d[33]), "+f"(d[34]), "+f"(d[35]), "+f"(d[36]), "+f"(d[37]), "+f"(d[38]), "+f"(d[39]),
          "+f"(d[40]), "+f"(d[41]), "+f"(d[42]), "+f"(d[43]), "+f"(d[44]), "+f"(d[45]), "+f"(d[46]), "+f"(d[47]),
          "+f"(d[48]), "+f"(d[49]), "+f"(d[50]), "+f"(d[51]), "+f"(d[52]), "+f"(d[53]), "+f"(d[54]), "+f"(d[55]),
          "+f"(d[56]), "+f"(d[57]), "+f"(d[58]), "+f"(d[59]), "+f"(d[60]), "+f"(d[61]), "+f"(d[62]), "+f"(d[63])
        : "l"(da), "l"(db), "n"(TA), "n"(TB), "r"(acc));
}
template <int TB>
__device__ __forceinline__ void wgmma_rs_n128(float (&d)[64], uint32_t a0, uint32_t a1, uint32_t a2, uint32_t a3, uint64_t db) {
    asm volatile("{\n.reg .pred p;\nsetp.ne.b32 p, 1, 0;\n"
        "wgmma.mma_async.sync.aligned.m64n128k16.f32.bf16.bf16 "
        "{%0, %1, %2, %3, %4, %5, %6, %7, %8, %9, %10, %11, %12, %13, %14, %15, "
        "%16, %17, %18, %19, %20, %21, %22, %23, %24, %25, %26, %27, %28, %29, %30, %31, "
        "%32, %33, %34, %35, %36, %37, %38, %39, %40, %41, %42, %43, %44, %45, %46, %47, "
        "%48, %49, %50, %51, %52, %53, %54, %55, %56, %57, %58, %59, %60, %61, %62, %63}, "
        "{%64, %65, %66, %67}, %68, p, 1, 1, %69;\n}\n"
        : "+f"(d[0]), "+f"(d[1]), "+f"(d[2]), "+f"(d[3]), "+f"(d[4]), "+f"(d[5]), "+f"(d[6]), "+f"(d[7]),
          "+f"(d[8]), "+f"(d[9]), "+f"(d[10]), "+f"(d[11]), "+f"(d[12]), "+f"(d[13]), "+f"(d[14]), "+f"(d[15]),
          "+f"(d[16]), "+f"(d[17]), "+f"(d[18]), "+f"(d[19]), "+f"(d[20]), "+f"(d[21]), "+f"(d[22]), "+f"(d[23]),
          "+f"(d[24]), "+f"(d[25]), "+f"(d[26]), "+f"(d[27]), "+f"(d[28]), "+f"(d[29]), "+f"(d[30]), "+f"(d[31]),
          "+f"(d[32]), "+f"(d[33]), "+f"(d[34]), "+f"(d[35]), "+f"(d[36]), "+f"(d[37]), "+f"(d[38]), "+f"(d[39]),
          "+f"(d[40]), "+f"(d[41]), "+f"(d[42]), "+f"(d[43]), "+f"(d[44]), "+f"(d[45]), "+f"(d[46]), "+f"(d[47]),
          "+f"(d[48]), "+f"(d[49]), "+f"(d[50]), "+f"(d[51]), "+f"(d[52]), "+f"(d[53]), "+f"(d[54]), "+f"(d[55]),
          "+f"(d[56]), "+f"(d[57]), "+f"(d[58]), "+f"(d[59]), "+f"(d[60]), "+f"(d[61]), "+f"(d[62]), "+f"(d[63])
        : "r"(a0), "r"(a1), "r"(a2), "r"(a3), "l"(db), "n"(TB));
}
template <int TA, int TB>
__device__ __forceinline__ void wgmma_n8(float (&d)[4], uint64_t da, uint64_t db, int acc = 1) {
    asm volatile("{\n.reg .pred p;\nsetp.ne.b32 p, %8, 0;\n"
        "wgmma.mma_async.sync.aligned.m64n8k16.f32.bf16.bf16 "
        "{%0, %1, %2, %3}, "
        "%4, %5, p, 1, 1, %6, %7;\n}\n"
        : "+f"(d[0]), "+f"(d[1]), "+f"(d[2]), "+f"(d[3])
        : "l"(da), "l"(db), "n"(TA), "n"(TB), "r"(acc));
}

__device__ __forceinline__ uint32_t norm_pair(uint32_t u, float m, float rinv) {
    uint32_t d = pack_bf16(bf_lo(u) - m, bf_hi(u) - m);
    return pack_bf16(bf_lo(d) * rinv, bf_hi(d) * rinv);
}

struct Roles { uint16_t v[132]; };

__global__ void __launch_bounds__(512, 1)
fused_kernel(int by_sm, const __nv_bfloat16* __restrict__ x, const __nv_bfloat16* __restrict__ wqkv, const __nv_bfloat16* __restrict__ wr,
             Scratch* const S, const char* __restrict__ wg, const char* __restrict__ wu, const char* __restrict__ wd, const char* __restrict__ wo,
             const __grid_constant__ Roles roles,
             const __grid_constant__ CUtensorMap mw, const __grid_constant__ CUtensorMap mx, const __grid_constant__ CUtensorMap mwo,
             const __grid_constant__ CUtensorMap mxs, const __grid_constant__ CUtensorMap mcs, const __grid_constant__ CUtensorMap mout, const __grid_constant__ CUtensorMap mgu, const __grid_constant__ CUtensorMap mwd) {
    extern __shared__ __align__(1024) uint8_t smem[];
    constexpr uint32_t sb = 1024, bars = sb + OFF_BAR, sd = sb >> 4;
    const int tid = threadIdx.x, lane = tid & 31;
    asm volatile("{\n.reg .pred p, q;\nsetp.lt.u32 p, %2, 16;\nsetp.lt.u32 q, %2, 24;\n@p prefetch.global.L2 [%0];\n@p prefetch.global.L2 [%0 + 128];\n@q prefetch.global.L2 [%1];\n}" ::
                 "l"((const char*)x + (blockIdx.x * 16 + tid - 32) % 2048 * 2048), "l"((const char*)wqkv + (blockIdx.x * 24 + tid - 32) * 128), "r"(tid - 32));
    const int warp = __shfl_sync(0xffffffffu, tid >> 5, 0);
    uint32_t smid;
    asm volatile("mov.u32 %0, %%smid;" : "=r"(smid));
    const int role = roles.v[by_sm ? smid : blockIdx.x], fb = role & 255, b = role >> 8, kc = fb >> 4, c2 = fb & 15;
    const int mt = b >> 4, nt = b & 15, hp = b & 1, cb = nt >> 1;
    const int par = mt >> 2, j0 = (mt & 3) * 256;
    uint8_t* const g_o = S->o;

    auto load_stage = [&](int p, uint32_t so, int bi) {
        const uint32_t fullA = bars + 8 * (B_FULLA + bi), fullB = bars + 8 * (B_FULLB + bi);
        mbar_expect_tx(fullA, 40960);
        tma_3d(sb + so + 16384, &mw, fullA, nt * 64, p * 64, 0);
        tma_4d(sb + so, &mx, fullA, par * 1024 + p * 64, 0, (j0 >> 5) + 4, 0);
        mbar_expect_tx(fullB, 16384);
        tma_4d(sb + so + 40960, &mx, fullB, par * 1024 + p * 64, 0, j0 >> 5, 0);
    };
    if (warp == 0 && fb < 128 && elect_one()) {
        mbar_init(bars + 8 * B_FULLA, 1); mbar_init(bars + 8 * B_FULLB, 1);
        load_stage(0, STAGE, 0);
    }
    if (fb >= 128) {
        if (fb > 128) { nap(16); TS_END(); return; }
        const uint32_t tag = (ld_rlx(&S->epoch) & 1) - 1;
        if (tid < 8) st_rlx2(&S->sel[tid], ~tag, ~tag);
        uint4 ra, rb;
#pragma unroll 1
        for (int it = 0; it < SPIN_LIMIT; it++) {
            ra = ld_rlx4(&S->rec[tid * 2]); rb = ld_rlx4(&S->rec[1024 + tid * 2]);
            if (!__any_sync(0xffffffffu, (mism(ra.x, ra.z, tag) | mism(rb.x, rb.z, tag)) & 0x8000u)) break;
        }
        __syncwarp();
        TSC(tid == 0, 31);
        sts4(sb + 1024 + tid * 16, ra.y, rb.y, ra.w, rb.w);
        uint4 k = make_uint4(ra.x, ra.z, rb.x, rb.z);
        uint32_t cand;
#pragma unroll 1
        for (int pass = 0; pass < 2; pass++) {
            const uint32_t a0 = max(k.x, k.y), a1 = min(k.x, k.y), a2 = max(k.z, k.w), a3 = min(k.z, k.w), c1 = min(a0, a2), c2 = max(a1, a3);
            k = make_uint4(max(a0, a2), max(c1, c2), min(c1, c2), min(a1, a3));
#pragma unroll
            for (int r = 0; r < 8; r++) {
                const uint32_t m = redux_max(k.x);
                if (lane == r) cand = m;
                if (k.x == m) k = make_uint4(k.y, k.z, k.w, 0);
            }
            if (pass) break;
            if (lane < 8) sts1(sb + (warp * 8 + lane) * 4, cand);
            __syncthreads();
            if (warp) { TS_END(); return; }
            k = lds4(sb + lane * 16);
            TSC(TIMING == 12 && tid == 0 && k.x != 0x12345, 40);
        }
        if (lane < 8) st_rlx2(&S->sel[lane], cand, lds1(sb + 1024 + (~cand & 0x7ffu) * 4));
        TSC(tid == 0, 20);
        TS_END();
        return;
    }
    uint32_t epoch;
    if (warp >> 2 == 2) epoch = ld_rlx(&S->epoch);
    if (warp == 1 && elect_one()) {
#pragma unroll
        for (int i = 0; i < B_WOFULL; i++)
            if (i != B_FULLA && i != B_FULLB) mbar_init(bars + 8 * i, i >= B_FFULL && i < B_FEMPTY ? 5 : 1);
    }
    if (warp == 4 && elect_one()) {
#pragma unroll
        for (int i = B_EMPTY; i < NBAR; i++) mbar_init(bars + 8 * i, i < B_UPD ? 2 : i < B_AUX ? 4 : i == B_AUX ? 7 : i == B_CSDONE ? 3 : 8);
    }
    __syncthreads();

    if (warp >= 12) {
        reg_dec<24>();
        if (warp > 12) {
            const int p = warp - 13;
            if (p == 1) {
                float sw = 0.f;
                mbar_wait(bars + 8 * (B_ROW + 4), 0);
#pragma unroll 1
                for (int i = 0; i < 16; i++) { const uint32_t q = lds1(sb + OFF_FA + i * 128 + lane * 4); sw += bf_lo(q) + bf_hi(q); }
#pragma unroll 1
                for (int o = 1; o < 32; o <<= 1) sw += __shfl_xor_sync(0xffffffffu, sw, o);
                if (lane == 0) { sts1(sb + OFF_TAG + 4, __float_as_uint(sw)); mbar_arrive(bars + 8 * B_SW); }
            } else {
#pragma unroll 1
                for (int q = 0; q < 4; q++) {
                    nap(p ? (q ? D_R : N_ROW) : (q ? D_X : N_X));
                    if (p == 0) {
                        const __nv_bfloat16* xp = x + (size_t)((j0 + nt * 16 + (lane >> 1)) * 2 + par) * 1024 + q * 256 + (lane & 1) * 64;
                        prefetch_l2(xp); prefetch_l2(xp + 128);
                    } else if (elect_one()) {
                        mbar_expect_tx(bars + 8 * (B_ROW + q), 8192);
                        tma_3d(sb + OFF_FW + q * 8192, &mxs, bars + 8 * (B_ROW + q), 0, j0 + nt * 16, par * 16 + q * 4);
                    }
                }
                if (p == 0) nap(N_CS);
            }
            const uint32_t stg = sb + OFF_FW + 32768 + p * 4096 + lane * 16;
            float c[8];
#pragma unroll
            for (int i = 0; i < 8; i++) c[i] = 0.f;
#pragma unroll 1
            for (int n = 0; n < 10; n++) {
                const uint32_t bo = (n & 1) * 2048, bar = bars + 8 * (B_CS + 2 * p + (n & 1));
                if (n >= 2) {
                    mbar_wait(bar, ~(n >> 1) & 1);
#pragma unroll 2
                    for (int i = 0; i < 4; i++) {
                        const uint4 v = lds4(stg + bo + i * 512);
                        c[0] += bf_lo(v.x); c[1] += bf_hi(v.x); c[2] += bf_lo(v.y); c[3] += bf_hi(v.y);
                        c[4] += bf_lo(v.z); c[5] += bf_hi(v.z); c[6] += bf_lo(v.w); c[7] += bf_hi(v.w);
                    }
                    asm volatile("" :: "f"(c[7]));
                    __syncwarp();
                }
                if (n < 8 && elect_one()) {
                    mbar_expect_tx(bar, 2048);
                    tma_3d(sb + OFF_FW + 32768 + p * 4096 + bo, &mcs, bar, p * 1024 + nt * 64, mt * 8, 2 * n);
                }
            }
            sts4(stg + lane * 16, __float_as_uint(c[0]), __float_as_uint(c[1]), __float_as_uint(c[2]), __float_as_uint(c[3]));
            sts4(stg + lane * 16 + 16, __float_as_uint(c[4]), __float_as_uint(c[5]), __float_as_uint(c[6]), __float_as_uint(c[7]));
            bar_sync(13, 128);
            const uint32_t tag = lds1(sb + OFF_TAG);
            float* gcs = &S->cs[0][p * 1024 + nt * 64];
            {
                const float2 a0 = lds2f(stg - lane * 8), a1 = lds2f(stg - lane * 8 + 256), a2 = lds2f(stg - lane * 8 + 512), a3 = lds2f(stg - lane * 8 + 768);
                st_rlx2(gcs + mt * 3072 + lane * 2, tagf((a0.x + a1.x) + (a2.x + a3.x), tag), __float_as_uint((a0.y + a1.y) + (a2.y + a3.y)));
            }
            fence_async_smem();
            __syncwarp();
            if (lane == 0) mbar_arrive(bars + 8 * B_CSDONE);
            TSC(warp == 13 && lane == 0, 19);
            {
                uint4 v[4];
                const float* src = gcs + (lane >> 4) * 4 * 3072 + (lane & 15) * 4;
#pragma unroll 1
                for (int it = 0; it < SPIN_LIMIT; it++) {
#pragma unroll
                    for (int m = 0; m < 4; m++) v[m] = ld_rlx4(src + m * 3072);
                    if (!__any_sync(0xffffffffu, (mism(v[0].x, v[1].x, tag) | mism(v[2].x, v[3].x, tag)) & 1)) break;
                }
                __syncwarp();
#pragma unroll
                for (int c = 0; c < 4; c++) {
                    const float a = (__uint_as_float((&v[0].x)[c]) + __uint_as_float((&v[1].x)[c])) + (__uint_as_float((&v[2].x)[c]) + __uint_as_float((&v[3].x)[c]));
                    (&v[0].x)[c] = __float_as_uint(a + __shfl_xor_sync(0xffffffffu, a, 16));
                }
                const uint32_t ca = sb + OFF_CS + p * 384 + ((lane & 15) >> 1) * 48 + (lane & 1) * 8;
#pragma unroll 1
                for (int r = 0; r < 3; r++) {
                    const uint32_t u0 = pack_bf16(__uint_as_float(v[0].x), __uint_as_float(v[0].y)), u1 = pack_bf16(__uint_as_float(v[0].z), __uint_as_float(v[0].w));
                    sts2(ca + r * 16, u0, u1);
                    v[0].x = __float_as_uint(__uint_as_float(v[0].x) - bf_lo(u0)); v[0].y = __float_as_uint(__uint_as_float(v[0].y) - bf_hi(u0));
                    v[0].z = __float_as_uint(__uint_as_float(v[0].z) - bf_lo(u1)); v[0].w = __float_as_uint(__uint_as_float(v[0].w) - bf_hi(u1));
                }
                if (lane < 20) sts1(sb + OFF_CS + 1152 + lane * 4, 0);
                fence_async_smem();
            }
            __syncwarp();
            if (lane == 0) mbar_arrive(bars + 8 * B_AUX);
            TSC(warp == 13 && lane == 0, 21);
            mbar_wait(bars + 8 * B_PART, 0);
            mbar_wait(bars + 8 * (B_EMPTY + 2), 0);
            if (p == 0) {
                uint4 v[4];
#pragma unroll
                for (int c = 0; c < 4; c++) v[c] = make_uint4(0, 0, 0, 0);
                const uint32_t* hsrc = &S->halo[b - 16][lane * 4];
#pragma unroll 1
                for (int it = 0; it < SPIN_LIMIT && j0; it++) {
#pragma unroll
                    for (int c = 0; c < 4; c++) v[c] = ld_rlx4(hsrc + c * 128);
                    if (!__any_sync(0xffffffffu, (mism(v[0].x, v[1].x, tag) | mism(v[2].x, v[3].x, tag)) & 1)) break;
                }
#pragma unroll
                for (int c = 0; c < 4; c++) sts4(sb + OFF_HALO + c * 512 + lane * 16, v[c].x, v[c].y, v[c].z, v[c].w);
                __syncwarp();
                bar_arrive(3, 64);
                TSC(TIMING == 11 && lane == 0, 34);
            } else {
                const int w = p - 1;
                const uint8_t* osrc = g_o + (size_t)((mt * 2 + hp) * 2 + w) * 131072;
                const bool far = w > hp && j0 && lane >= 16;
                const uint32_t* hsrc = &S->hint[b & 0x70][0] + ((lane & 15) - (far ? 16 : 0)) * 8;
                if (lane == 0 && !w) st_rlx(&S->hint[b][0], tagw(now(), 1u, tag));
                uint32_t hv;
#pragma unroll 1
                for (int it = 0; it < SPIN_LIMIT; it++) {
                    hv = ld_rlx(hsrc);
                    if (!__any_sync(0xffffffffu, (hv ^ tag) & 1)) break;
                }
                TSC(TIMING == 11 && lane == 0, 32 + w);
                const uint32_t tn = __shfl_sync(0xffffffffu, hv, 0) - 0x40000000u;
                hv = redux_max(hv - tn + (far ? T_H : 0)) + tn + T_O + w * T_O1;
                mbar_wait(bars + 8 * (w ? B_AST : B_G1DONE), 0);
                if (elect_one()) {
#pragma unroll 1
                    for (int st = 0; st < 8; st++) {
                        const uint32_t full = bars + 8 * (B_OFULL + 8 * w + st);
                        if (st == 2 && !w) { until(hv + T_GO); mbar_arrive(bars + 8 * B_GO); }
                        if (st >= 2) mbar_wait(full + 8 * (B_DONE - B_OFULL - 2), 0);
                        if (st < 3) until(hv + (st == 2 ? T_S2 : st * T_S1));
                        TSC(st == 0, 28 + w);
                        mbar_expect_tx(full, 16384);
                        bulk_g2s(sb + (w ? OFF_O1 : OFF_O0) + (st & 1) * 16384, osrc + st * 16384, 16384, full);
                    }
                }
            }
            TS_END();
            return;
        }
        if (elect_one()) {
            auto load_wo = [&](int s, int ws) {
                mbar_expect_tx(bars + 8 * (B_WOFULL + s), 32768);
                tma_4d(sb + OFF_WO + ws * 32768, &mwo, bars + 8 * (B_WOFULL + s), 0, s * 8, 0, cb * 2);
            };
            uint32_t so = 2 * STAGE, ph = 1, cnt = PF_CNT << 4;
            int bi = 1, q = 0;
            mbar_expect_tx(bars + 8 * (B_ROW + 4), 2048);
            bulk_g2s(sb + OFF_FA, wr, 2048, bars + 8 * (B_ROW + 4));
            if (smem_u32(smem) != sb) __trap();
            const char* pf = (b < 64 ? wg : wu) + (b & 63) * 7168;
#pragma unroll 1
            for (int p = 1; p < 16; p++) {
                if (p < 3) nap(p == 1 ? N_S1 : N_S2);
                mbar_wait(bars + 8 * (B_EMPTY + bi), ph);
                load_stage(p, so, bi);
                if (p >= 2 && p < 5) {
                    const int k0 = p == 2 ? 3 : p == 3 ? K_W1 : K_W2, n = ((p == 2 ? K_W1 : p == 3 ? K_W2 : 16) - k0) * 3072;
                    if (p == 2) nap(N_W);
                    bulk_prefetch((const char*)wqkv + k0 * 393216 + b * n, n);
                }
#pragma unroll 1
                for (int e = q + (cnt & 3); q < e; q++) {
                    if (q == 16) pf = wd + mt * 7 * 131072 + nt * 8192;
                    if (q == 23) pf = wo + b * 8192;
                    bulk_prefetch(pf, q < 16 ? 7168 : 8192);
                    pf += q < 16 ? 64 * 7168 : q < 23 ? 131072 : 1048576;
                }
                cnt >>= 2;
                so = so == 2 * STAGE ? 0 : so + STAGE;
                if (++bi == 3) { bi = 0; ph ^= 1; }
            }
            TS(27);
            int ws = 1;
#pragma unroll 1
            for (int i = 0; i < 8; i++) {
                if (i == 1) {
                    mbar_wait(bars + 8 * (B_EMPTY + 2), 0);
                    mbar_expect_tx(bars + 8 * B_F2FULL, 8192);
                    tma_2d(sb + OFF_F2X, &mwd, bars + 8 * B_F2FULL, DBG_F2 * c2 * 64, DBG_F2 * kc * 448);
#pragma unroll 1
                    for (int c = 0; c < 2; c++) {
                        if (c) mbar_wait(bars + 8 * XR_GATE, 0);
                        mbar_expect_tx(bars + 8 * B_XR, 16384);
                        tma_4d(sb + c * STAGE, &mx, bars + 8 * B_XR, DBG_XR * (par * 1024 + cb * 128 + c * 64), 0, DBG_XR * ((j0 >> 5) + hp * 4), 0);
                    }
                } else {
                    mbar_wait(bars + 8 * (i == 0 ? B_EMPTY + 1 : i == 2 ? B_F2DONE : B_DONE - NWO + i), 0);
                    if (i) mbar_wait(bars + 8 * (i == 2 ? B_OFULL : B_DONE + 8 - NWO + i), 0);
                }
                load_wo(i < 2 ? 1 - i : i, i == 1 ? 0 : ws);
                if (i != 1 && ++ws == NWO) ws = 0;
            }
        }
        TS_END();
    } else if (warp >= 8) {
        reg_dec<40>();
        const int p = warp - 8;
        const bool f1 = fb < 112;
        auto ffn_w = [&](int n, int s) {
            const uint32_t dst = sb + OFF_FW + s * 16384;
            if (n < 8) {
                mbar_expect_tx(bars + 8 * (B_FFULL + s), 16384);
                tma_3d(dst, &mgu, bars + 8 * (B_FFULL + s), DBG_F1 * fb * 32, n * 128, 0);
            } else {
                mbar_expect_tx(bars + 8 * B_F2FULL, 16384);
                tma_2d(dst, &mwd, bars + 8 * B_F2FULL, DBG_F2 * c2 * 64, DBG_F2 * kc * 448 + 64 + s * 128);
                tma_2d(dst + 8192, &mwd, bars + 8 * B_F2FULL, DBG_F2 * c2 * 64, DBG_F2 * kc * 448 + 128 + s * 128);
            }
        };
        const uint32_t tag = (epoch & 1) - 1;
        {
            const int ta = tid - 256;
            if (ta < 48) st_rlx4(&S->cs[mt][(ta >> 4) * 1024 + nt * 64 + (ta & 15) * 4], ~tag, ~tag, ~tag, ~tag);
            st_rlx4(&S->ypart[kc][ta >> 4][c2 * 64 + (ta & 15) * 4], ~tag, ~tag, ~tag, ~tag);
            if (p == 3 && f1) st_rlx4(&S->h[fb * 128 + lane * 4], ~tag, ~tag, ~tag, ~tag);
            if (ta < 2) st_rlx4(&S->hint[b][ta * 4], ~tag, ~tag, ~tag, ~tag);
            st_rlx4(&S->halo[b][ta * 4], ~tag, ~tag, ~tag, ~tag);
        }
        float s1 = 0.f, s2 = 0.f, sr = 0.f, sw, sh = 0.f;
        {
            const uint32_t xa = sb + OFF_FW + p * 512 + lane * 16, wa = sb + OFF_FA + (((p * 4 + (lane >> 3)) ^ lane) & 7) * 16;
            TSC(TIMING == 12 && lane == 0, 50 + p);
            mbar_wait(bars + 8 * (B_ROW + 4), 0);
            {
                float c1 = 0.f, c2 = 0.f, cr = 0.f;
#pragma unroll 1
                for (int q = 0; q < 4; q++) {
                mbar_wait(bars + 8 * (B_ROW + q), 0);
                TSC(TIMING == 12 && tid == 256 + 96, 32 + q);
                TSC(tid == 256 && q == 3, 17);
#pragma unroll
                for (int i = 0; i < 4; i++) {
                    const uint4 u = lds4(xa + q * 8192 + i * 2048), w4 = lds4(wa + q * 512 + i * 128);
                    if (DBG_ST == 1) { s2 += fabsf(bf_lo(u.x ^ (u.y & u.z & u.w & 1))); sr += bf_lo(w4.x ^ w4.y ^ w4.z ^ w4.w ^ u.x); continue; }
                    const float a0 = bf_lo(u.x), a1 = bf_hi(u.x), a2 = bf_lo(u.y), a3 = bf_hi(u.y), a4 = bf_lo(u.z), a5 = bf_hi(u.z), a6 = bf_lo(u.w), a7 = bf_hi(u.w);
                    s1 += a0 + a1; c1 += a4 + a5; s1 += a2 + a3; c1 += a6 + a7;
                    s2 = fmaf(a0, a0, s2); c2 = fmaf(a4, a4, c2); sr = fmaf(a0, bf_lo(w4.x), sr); cr = fmaf(a4, bf_lo(w4.z), cr);
                    s2 = fmaf(a1, a1, s2); c2 = fmaf(a5, a5, c2); sr = fmaf(a1, bf_hi(w4.x), sr); cr = fmaf(a5, bf_hi(w4.z), cr);
                    s2 = fmaf(a2, a2, s2); c2 = fmaf(a6, a6, c2); sr = fmaf(a2, bf_lo(w4.y), sr); cr = fmaf(a6, bf_lo(w4.w), cr);
                    s2 = fmaf(a3, a3, s2); c2 = fmaf(a7, a7, c2); sr = fmaf(a3, bf_hi(w4.y), sr); cr = fmaf(a7, bf_hi(w4.w), cr);
                }
                }
                s1 += c1; s2 += c2; sr += cr;
            }
            mbar_wait(bars + 8 * B_SW, 0);
            sw = lds1f(sb + OFF_TAG + 4);
#pragma unroll 1
            for (int pass = 0;; pass++) {
#pragma unroll
                for (int o = 1; o < 8; o <<= 1) {
                    s1 += __shfl_xor_sync(0xffffffffu, s1, o); s2 += __shfl_xor_sync(0xffffffffu, s2, o); sr += __shfl_xor_sync(0xffffffffu, sr, o);
                }
                s1 *= 1.f / 1024.f;
                s2 = fmaf(-s1, s1, s2 * (1.f / 1024.f));
                if (!__any_sync(0xffffffffu, !pass && s1 * s1 > 256.f * s2)) break;
                sh = bf16r(s1); s1 = 0.f; s2 = 0.f; sr = 0.f;
#pragma unroll 1
                for (uint32_t o = 0; o < 2048; o = opaque(o + ((o & 12) == 12 ? 116 : 4))) {
                    const uint32_t u = lds1(xa + (o >> 7) * 2048 + (o & 12)), q = lds1(wa + o);
                    const float a0 = bf_lo(u) - sh, a1 = bf_hi(u) - sh;
                    s1 += a0 + a1; s2 = fmaf(a0, a0, fmaf(a1, a1, s2)); sr = fmaf(a0, bf_lo(q), fmaf(a1, bf_hi(q), sr));
                }
            }
        }
        const int ta = opaque(tid) - 256, lane = ta & 31, g = lane >> 2, t = lane & 3;
        {
            if ((lane & 7) == 0) {
                const int s = b * 16 + p * 4 + (lane >> 3);
                const float mb = bf16r(sh + s1);
                float den;
                asm("sqrt.approx.f32 %0, %1;" : "=f"(den) : "f"(bf16r(bf16r(s2) + 1e-5f)));
                den = bf16r(den);
                uint32_t rb = pack_bf16(fmaf(sh - mb, sw, sr) * rcp(den), 0.f);
                if (rb == 0x8000u) rb = 0;
                uint32_t ord = (rb & 0x8000u) ? (~rb & 0xffffu) : (rb | 0x8000u);
                if ((rb & 0x7fffu) > 0x7f80u) ord = 0;
                st_rlx2(&S->rec[s], (ord << 16) | (tag & 0x8000u) | (0x47ffu - (s & 1023) * 2 - par), pack_bf16(mb, den));
            }
            TSC(TIMING == 12 && lane == 0, 36 + p);
            bar_sync(12, 128);
            if (p == 1) sts1(sb + OFF_ROWMAP + lane * 4, 0xffffffffu);
            if (p == 0) {
                if (lane == 0) {
                    sts1(sb + OFF_TAG, tag);
                }
                __syncwarp();
                bar_arrive(13, 128);
            }
            TSC(ta == 0, 18);
        }
        {
            uint2 r[3];
            nap(N_GA);
            const uint2* src = &S->rec[mt * 256 + ta];
            const int l2 = ta < 8 && j0 ? -8 : 0;
#pragma unroll 1
            for (int it = 0; it < SPIN_LIMIT; it++) {
                r[0] = ld_rlx2(src + l2); r[1] = ld_rlx2(src); r[2] = ld_rlx2(src + 128);
                if (!__any_sync(0xffffffffu, (mism(r[0].x, r[1].x, tag) | (r[2].x ^ tag)) & 0x8000u)) break;
            }
#pragma unroll
            for (int n = 0; n < 3; n++)
                if (n || ta < 8) sts2(sb + OFF_STAT + (n ? n * 1024 - 960 : 0) + ta * 8, (r[n].y << 16) ^ 0x80000000u, __float_as_uint(rcp(bf_hi(r[n].y))));
        }
        __syncwarp();
        if (lane == 0) mbar_arrive(bars + 8 * B_AUX);
        TSC(ta == 0, 30);
        if (f1 && p < EARLY_FILL && elect_one()) { nap(p * N_F1); ffn_w(p, p); }
        __syncwarp();
        uint2 sel;
#pragma unroll 1
        for (int it = 0; it < SPIN_LIMIT; it++) {
            sel = ld_rlx2(&S->sel[lane & 7]);
            if (!__any_sync(0xffffffffu, (sel.x ^ tag) & 0x8000u)) break;
            __nanosleep(POLL_NS);
        }
        TSC(ta == 0, 26);
        if (b == 0 && ta == 0) st_rlx(&S->epoch, epoch + 1);
        {
            const __nv_bfloat16* xp = x + (~sel.x & 0x7ffu) * 1024 + (ta >> 3) * 8;
            const float mb = bf_lo(sel.y), rinv = rcp(bf_hi(sel.y));
            uint4 v = ldg_nc(xp), v2 = ldg_nc(xp + 128);
            int s = f1 ? 0 : 2;
#pragma unroll 1
            for (int n = f1 ? 0 : 8; n < (p ? 8 : 11); n++) {
                mbar_wait(bars + 8 * (f1 ? B_FEMPTY + s : B_PART), f1 && (n < 3 || (n >= 6 && n < 9)));
                if (p == 0 && s == 2) mbar_wait(bars + 8 * B_CSDONE, 0);
                if (p == 0 && n >= EARLY_FILL && elect_one()) ffn_w(n, s);
                if (n < 8) {
                    sts4(sb + OFF_FA + s * 2048 + ta * 16, norm_pair(v.x, mb, rinv), norm_pair(v.y, mb, rinv), norm_pair(v.z, mb, rinv), norm_pair(v.w, mb, rinv));
                    fence_async_smem();
                    __syncwarp();
                    if (lane == 0) mbar_arrive(bars + 8 * (B_FFULL + s));
                    TSC(TIMING == 12 && ta == 0, 41 + n);
                    v = v2;
                    if (n) v = ldg_nc(xp + ((n + 1) & 7) * 128);
                }
                if (++s == 3) s = 0;
            }
        }
        mbar_wait(bars + 8 * B_PART, 0);
        if (f1 && p >= 2) {
            const uint32_t pa = sb + OFF_FA + (ta - 64) * 16, go = wu < wg ? 1024 : 0;
            const float4 g0 = lds4f(pa + go), g1 = lds4f(pa + 2048 + go), u0 = lds4f(pa + (go ^ 1024)), u1 = lds4f(pa + 2048 + (go ^ 1024));
            float hv[4];
#pragma unroll
            for (int c = 0; c < 4; c++) {
                const float ga = bf16r((&g0.x)[c] + (&g1.x)[c]), up = bf16r((&u0.x)[c] + (&u1.x)[c]);
                hv[c] = bf16r(ga * sigmoidf(ga)) * up;
            }
#pragma unroll
            for (int hh = 0; hh < 2; hh++) {
                const float o = __shfl_xor_sync(0xffffffffu, (g & 1) ? hv[2 * hh] : hv[2 * hh + 1], 4);
                st_rlx(&S->h[(fb * 4 + (p & 1) * 2 + hh) * 32 + (2 * t + (g & 1)) * 4 + (g >> 1)],
                       tagw((g & 1) ? pack_bf16(o, hv[2 * hh + 1]) : pack_bf16(hv[2 * hh], o), g < 2, tag));
            }
            TSC(ta == 64, 22);
        }
        {
            uint4 hq[4];
            const uint32_t* hp4 = S->h + kc * 1792 + ta * 4;
#pragma unroll 1
            for (int it = 0; it < SPIN_LIMIT; it++) {
#pragma unroll
                for (int n = 0; n < 4; n++) hq[n] = ld_rlx4(hp4 + (n < 3 ? n * 512 : p < 2 ? 1536 : 0));
                if (!__any_sync(0xffffffffu, (mism(hq[0].x, hq[1].x, tag) | mism(hq[2].x, hq[3].x, tag)) & 1)) break;
            }
            mbar_wait(bars + 8 * B_G1DONE, 0);
            bar_sync(12, 128);
#pragma unroll
            for (int n = 0; n < 4; n++) sts4(sb + OFF_FA + ta * 16 + (n < 3 ? n * 2048 : p < 2 ? 6144 : 0), hq[n].x, hq[n].y, hq[n].z, hq[n].w);
            fence_async_smem();
            bar_sync(12, 128);
            TSC(ta == 0, 25);
            mbar_wait(bars + 8 * B_F2FULL, 0);
            mbar_wait(bars + 8 * B_ATT, 0);
            float acc[4] = {0.f, 0.f, 0.f, 0.f};
            uint32_t da = sd + dlo(OFF_F2X, 8192), db = sd + dlo(OFF_FA, 128);
#pragma unroll 1
            for (int q = 0; q < 7; q++) {
                wg_fence();
#pragma unroll
                for (int j = 0; j < 4; j++) wgmma_n8<1, 0>(acc, mkdesc(da + j * 128, dhi(1024, 1)), mkdesc(db + j * 16, dhi(128, 0)));
                wg_commit();
                da = sd + dlo(OFF_FW, 8192) + q * 512; db += 64;
            }
            wg_wait<0>();
            if (ta == 0) mbar_arrive(bars + 8 * B_F2DONE);
#pragma unroll
            for (int c = 0; c < 4; c++) st_rlx(&S->ypart[kc][2 * t + (c & 1)][c2 * 64 + p * 16 + (c >> 1) * 8 + g], tagf(acc[c], tag));
            TSC(ta == 0, 23);
            bar_sync(12, 128);
        }
#pragma unroll 1
        for (int j = 2 * p; j < 2 * p + 2; j++) {
            const uint32_t kj = __shfl_sync(0xffffffffu, sel.x, j);
            const int row = 0x7ff - (kj & 0x7ffu), jj = (row >> 1) - j0 - hp * 128;
            float a0 = 0.f, a1 = 0.f, a2 = 0.f, a3 = 0.f, sig = 0.f;
            if ((row & 1) == par && jj >= 0 && jj < 128) {
                sig = bf16r(sigmoidf(__uint_as_float(((int)kj < 0 ? kj ^ 0x80000000u : ~kj) & 0xffff0000u)));
#pragma unroll 1
                for (int hh = 0; hh < 8; hh += 4) {
                    uint4 v[4];
#pragma unroll 1
                    for (int it = 0; it < SPIN_LIMIT; it++) {
#pragma unroll
                        for (int m = 0; m < 4; m++) v[m] = ld_rlx4(&S->ypart[hh + m][j][cb * 128 + lane * 4]);
                        if (!__any_sync(0xffffffffu, (mism(v[0], tag) | mism(v[1], tag) | mism(v[2], tag) | mism(v[3], tag)) & 1)) break;
                    }
#pragma unroll
                    for (int m = 0; m < 4; m++) { a0 += __uint_as_float(v[m].x); a1 += __uint_as_float(v[m].y); a2 += __uint_as_float(v[m].z); a3 += __uint_as_float(v[m].w); }
                }
                asm volatile("st.shared.u8 [%0], %1;" ::"r"(sb + OFF_ROWMAP + jj), "r"(j) : "memory");
            }
            sts2(sb + OFF_FA + (lane >> 1) * 128 + j * 16 + (lane & 1) * 8, pack_bf16(bf16r(a0) * sig, bf16r(a1) * sig), pack_bf16(bf16r(a2) * sig, bf16r(a3) * sig));
        }
        fence_async_smem();
        __syncwarp();
        if (lane == 0) mbar_arrive(bars + 8 * B_UPD);
        TSC(ta == 0, 24);
        TS_END();
    } else {
        if (elect_one()) {
#pragma unroll
            for (int i = 0; i < (B_EMPTY - B_WOFULL) / 8; i++) mbar_init(bars + 8 * (B_WOFULL + 8 * i + warp), 1);
        }
        reg_inc<224>();
        const int w = warp >> 2, wi = warp & 3, tw = (1 - w) * 4 + wi;
        const bool elect = (tid & 127) == 0;
        const uint32_t ln = opaque(lane), g = ln >> 2, t = ln & 3;
        uint32_t tag, ow[8][4];
        auto store_o = [&](int f0, int f1) {
            uint8_t* ob = g_o + (size_t)((mt * 2 + 1 - w) * 2 + 1 - (wi >> 1)) * 131072 + nt * 1024 + (wi & 1) * 512 + ln * 4;
#pragma unroll
            for (int f = f0; f < f1; f++)
#pragma unroll
                for (int i = 3; i >= 0; i--)
                    st_rlx(ob + f * 16384 + i * 128, ow[f][i]);
        };
        {
            float acc[2][96];
            const uint32_t sta = opaque(sb + OFF_STAT + tw * 256 + 64 + g * 8);
            {
                float fa[4] = {0.f, 0.f, 0.f, 0.f};
                uint32_t so = STAGE >> 4, bo = bars, ph = 0;
                const uint32_t dx0 = sd + dlo(w ? 40960 : 0, 16), dw0 = sd + dlo(16384, 8192);
                int p = 0;
                auto step = [&](bool ffn, int fs, uint32_t fph, bool last) {
                    mbar_wait(bo + 8 * B_FULLA, ph);
                    if (w) mbar_wait(bo + 8 * B_FULLB, ph);
                    TSC(TIMING == 9 && elect && p >= 11, 32 + (p - 11) * 6 + w * 3);
                    if (ffn) mbar_wait(bars + 8 * (B_FFULL + fs), fph);
                    TSC(TIMING == 9 && elect && p >= 11, 33 + (p - 11) * 6 + w * 3);
                    TSC(elect && p == 0, 1 + 8 * w);
                    bar_sync(1 + w, 256);
                    TSC(TIMING == 1 && tid == 0, 32 + p);
                    wg_fence();
                    if (last) {
                        wgmma_n192<0, 1>(acc[0], mkdesc(sd + dlo(OFF_MEAN, 0) + w * 128, dhi(128, 0)), mkdesc(sd + dlo(OFF_CS, 0), dhi(48, 0)));
                        wgmma_n192<0, 1>(acc[1], mkdesc(sd + dlo(OFF_MEAN + 1024, 0) + w * 128, dhi(128, 0)), mkdesc(sd + dlo(OFF_CS, 0), dhi(48, 0)));
                    }
#pragma unroll
                    for (int k = 0; k < 4; k++) {
                        wgmma_n192<0, 1>(acc[0], mkdesc(dx0 + so + k * 2, dhi(1024, 1)), mkdesc(dw0 + so + k * 128, dhi(1024, 1)), k || ffn || last ? 1 : p);
                        wgmma_n192<0, 1>(acc[1], mkdesc(dx0 + so + 512 + k * 2, dhi(1024, 1)), mkdesc(dw0 + so + k * 128, dhi(1024, 1)), k || ffn || last ? 1 : p);
                        if (ffn && k == 2) {
#pragma unroll
                            for (int j = 0; j < 8; j++)
                                wgmma_n8<1, 0>(fa, mkdesc(sd + dlo(OFF_FW, 8192) + fs * 1024 + j * 64, dhi(512, 2)), mkdesc(sd + dlo(OFF_FA, 128) + fs * 128 + j * 16, dhi(128, 0)));
                        }
                    }
                    wg_commit();
                    bar_arrive(2 - w, 256);
                    wg_wait<0>();
                    TSC(TIMING == 9 && elect && p >= 11, 34 + (p - 11) * 6 + w * 3);
                    if (wi == 0 && elect_one()) { mbar_arrive(bo + 8 * B_EMPTY); if (ffn) mbar_arrive(bars + 8 * (B_FEMPTY + fs)); }
                    so = so == 2 * (STAGE >> 4) ? 0 : so + (STAGE >> 4);
                    bo += 8;
                    if (bo == bars + 24) { bo = bars; ph ^= 1; }
                };
                if (w) bar_arrive(1, 256);
                uint32_t fm = opaque((fb < 112 ? (F1_MASK >> (16 * w)) & 0xffff : 0u) | 0x80000000u), fph = 0;
                int fs = w;
#pragma unroll 1
                for (; p < 16; p++) {
                    if (fm & 1) { step(true, fs, fph, false); fs += 2; if (fs >= 3) { fs -= 3; fph ^= 1; } }
                    else if (fm & 0x10000) step(false, 0, 0, true);
                    else step(false, 0, 0, false);
                    fm >>= 1;
                    if (p == P_PART) {
                        if (fb < 112) sts4(sb + OFF_FA + tid * 16, __float_as_uint(fa[0]), __float_as_uint(fa[1]), __float_as_uint(fa[2]), __float_as_uint(fa[3]));
                        __syncwarp();
                        if (lane == 0) mbar_arrive(bars + 8 * B_PART);
                    }
                    if (p != 14) continue;
                    mbar_wait(bars + 8 * B_AUX, 0);
                    mbar_wait(bars + 8 * (B_EMPTY + 1), 0);
                    const uint32_t hm = __float_as_uint(0.5f * lds1f(sb + OFF_STAT + 64 + tw * 256 + ln * 8)) >> 16;
                    sts4(sb + OFF_MEAN + w * 2048 + wi * 256 + (ln >> 4) * 1024 + (ln & 15) * 16, hm * 0x10001u, hm, 0, 0);
                    fence_async_smem();
                }
                if (elect) mbar_arrive(bars + 8 * B_G1DONE);
            }
            TSC(elect, 2 + 8 * w);

            tag = lds1(sb + OFF_TAG);
            mbar_wait(bars + 8 * (B_EMPTY + 2), 0);
            uint32_t pk[4][24];
            const uint32_t hm = tw == 7 ? ~ln & 1 : 0;
            auto np = [&](int i, int j) {
                const float* a = &acc[i >> 1][4 * j + 2 * (i & 1)];
                pk[i][j] = pack_bf16(a[0], a[1]);
                if (j >= 16) pk[i][j] = movm(pk[i][j]);
                if (i == 3 && j >= 8 && !(j & 1)) pk[i][j] = tagw(pk[i][j], hm, tag);
            };
            const uint32_t ha = sb + OFF_HALO + tw * 2048 + ln * 8;
#pragma unroll
            for (int j = 8; j < 24; j += 2) {
                np(3, j); np(3, j + 1);
                sts2(ha + 2048 + (j - 8) * 128, pk[3][j], pk[3][j + 1]);
                asm volatile("{\n.reg .pred p;\nsetp.eq.u32 p, %3, 7;\n@p st.relaxed.gpu.global.v2.u32 [%0], {%1,%2};\n}" ::"l"(&S->halo[b][(j - 8) * 32 + ln * 2]),
                             "r"(pk[3][j]), "r"(pk[3][j + 1]), "r"(tw) : "memory");
            }
            bar_arrive(4 + tw, 64);
            TSC(TIMING == 8 && ln == 0 && wi == 1, 32 + 8 * w);
            mbar_wait(bars + 8 * B_G1DONE, 0);
            const bool u0 = 2 * t > g, u1 = 2 * t + 1 > g;
            const uint32_t mU = (u0 ? 0xffffu : 0u) | (u1 ? 0xffff0000u : 0u);
            uint2 hl[8];
            float rk[4][2], fq[4][2];
            const float mask = tw == 0 && j0 == 0 ? -INFINITY : 0.f;
#pragma unroll
            for (int hd = 0; hd < 2; hd++) {
#pragma unroll
                for (int jj = 0; jj < 12; jj++) {
                    const int j = (jj >> 2) * 8 + hd * 4 + (jj & 3);
                    np(0, j); np(1, j); np(2, j);
                    if (j < 8) np(3, j);
                }
                float s[2][3][4];
#pragma unroll
                for (int h = 1; h >= 0; h--)
#pragma unroll
                    for (int n = 2; n >= 0; n--) {
                        if (h == 0 && n == 0 && hd == 0) {
                            const uint32_t ka = sb + OFF_STAT + tw * 256 + 4 + t * 16, k0 = opaque(ka + (u0 ? 0 : 64)), k1 = opaque(ka + (u1 ? 8 : 72));
#pragma unroll
                            for (int i = 0; i < 4; i++) {
                                const float rq = lds1f(sta + i * 64 + 4) * (0.17677669529663687f * 1.4426950408889634f);
                                rk[i][0] = lds1f(k0 + i * 64); rk[i][1] = lds1f(k1 + i * 64);
                                fq[i][0] = rq * rk[i][0]; fq[i][1] = rq * rk[i][1];
                            }
                            TSC(TIMING == 8 && ln == 0 && wi == 1 && s[1][0][0] + s[0][1][0] != 123.456f, 33 + 8 * w);
                            bar_sync(3 + tw, 64);
#pragma unroll
                            for (int c = 0; c < 8; c++) hl[c] = lds2(ha + c * 256);
                        }
                        const int kg = 2 * h - 1 + n;
                        s[h][n][0] = s[h][n][1] = kg < 0 ? mask : 0.f; s[h][n][2] = s[h][n][3] = 0.f;
#pragma unroll
                        for (int ks = 0; ks < 2; ks++) {
                            const int q = hd * 4 + 2 * ks;
                            const uint32_t* k = kg < 0 ? &hl[hd * 2 + ks].x : &pk[kg < 0 ? 0 : kg][8 + q];
                            mma16816(s[h][n], pk[2 * h][q], pk[2 * h + 1][q], pk[2 * h][q + 1], pk[2 * h + 1][q + 1], k[0], k[1]);
                        }
                    }
                uint32_t pp[4], pc[4];
#pragma unroll
                for (int i = 0; i < 4; i++) {
                    const float* sp = &s[i >> 1][i & 1][2 * (i & 1)];
                    const float* sc = &s[i >> 1][(i & 1) + 1][2 * (i & 1)];
                    float a0 = (u0 ? sp[0] : sc[0]) * fq[i][0], a1 = (u1 ? sp[1] : sc[1]) * fq[i][1];
                    float m = fmaxf(a0, a1);
                    m = fmaxf(m, __shfl_xor_sync(0xffffffffu, m, 1));
                    m = fmaxf(m, __shfl_xor_sync(0xffffffffu, m, 2));
                    a0 = ex2(a0 - m); a1 = ex2(a1 - m);
                    float sum = a0 + a1;
                    sum += __shfl_xor_sync(0xffffffffu, sum, 1);
                    sum += __shfl_xor_sync(0xffffffffu, sum, 2);
                    const float inv = rcp(sum);
                    const uint32_t pw = pack_bf16(a0 * rk[i][0] * inv, a1 * rk[i][1] * inv);
                    pp[i] = pw & mU; pc[i] = pw & ~mU;
                }
                TSC(TIMING == 8 && ln == 0 && wi == 1 && pp[0] + pp[3] != 0x12345, 34 + 2 * hd + 8 * w);
#pragma unroll
                for (int fh = 0; fh < 2; fh++)
#pragma unroll
                    for (int i = 0; i < 4; i++) {
                        const int v = 16 + hd * 4 + 2 * fh;
                        const uint32_t* vp = i ? &pk[i ? i - 1 : 0][v] : &hl[4 + hd * 2 + fh].x;
                        float o[4] = {0.f, 0.f, 0.f, 0.f};
                        if (i & 1) mma16816(o, vp[0], vp[1], pk[i][v], pk[i][v + 1], pp[i], pc[i]);
                        else { mma1688(o, pk[i][v], pk[i][v + 1], pc[i]); mma1688(o, vp[0], vp[1], pp[i]); }
                        const uint32_t tm = (ln & 7) == (nt & 3) * 2 + (i & 1);
                        ow[hd * 4 + 2 * fh][i] = tagw(pack_bf16(o[0], o[1]), tm, tag); ow[hd * 4 + 2 * fh + 1][i] = tagw(pack_bf16(o[2], o[3]), tm, tag);
                    }
                if (hd && ln == 0) mbar_arrive(bars + 8 * B_ATT);
                store_o(hd ? ST_A : 0, hd ? ST_B : ST_A);
                if (!hd && ln == 0) mbar_arrive(bars + 8 * B_AST);
                TSC(TIMING == 11 && !hd && ln == 0 && wi == 3, 45 + w);
                TSC(elect && hd == 0, 3 + 8 * w);
                TSC(TIMING == 8 && ln == 0 && wi == 1, 35 + 2 * hd + 8 * w);
            }
        }
        TSC(elect, 4 + 8 * w);
        mbar_wait(bars + 8 * B_XR, 0);
        float acc2[64];
        const uint32_t xs = sb + (wi & 1) * 8192 + (tw >> 1) * 2048, mad = xs + (ln & 15) * 128;
        {
            const uint32_t sta = sb + OFF_STAT + (8 + hp * 128 + tw * 16 + g) * 8;
            const float2 s0 = lds2f(sta), s1 = lds2f(sta + 64);
            const float m0 = s0.x * s0.y, r0 = 1.f + s0.y, m1 = s1.x * s1.y, r1 = 1.f + s1.y;
#pragma unroll
            for (int j = 0; j < 16; j += 2) {
                uint32_t a0, a1, a2, a3;
                const int ch = (j & 7) + (ln >> 4);
                asm volatile("ldmatrix.sync.aligned.m8n8.x4.shared.b16 {%0,%1,%2,%3}, [%4];" : "=r"(a0), "=r"(a1), "=r"(a2), "=r"(a3)
                             : "r"(mad + (j >> 3) * STAGE + ((ch ^ (ln & 7)) << 4)) : "memory");
                acc2[4 * j + 0] = fmaf(bf_lo(a0), r0, m0); acc2[4 * j + 1] = fmaf(bf_hi(a0), r0, m0);
                acc2[4 * j + 2] = fmaf(bf_lo(a1), r1, m1); acc2[4 * j + 3] = fmaf(bf_hi(a1), r1, m1);
                acc2[4 * j + 4] = fmaf(bf_lo(a2), r0, m0); acc2[4 * j + 5] = fmaf(bf_hi(a2), r0, m0);
                acc2[4 * j + 6] = fmaf(bf_lo(a3), r1, m1); acc2[4 * j + 7] = fmaf(bf_hi(a3), r1, m1);
            }
        }
        TSC(elect, 5 + 8 * w);
        {
            if (ST_B < ST_C) { mbar_wait(bars + 8 * B_GO, 0); store_o(ST_B, ST_C); }
            mbar_wait(bars + 8 * B_ATT, 0);
            const uint32_t ring = sb + (w ? OFF_O1 : OFF_O0), da0 = (ring >> 4) + dlo(0, 1024);
            const uint32_t chk = ring + wi * 256 + (ln >> 3) * 1032 + (g & 1) * 132 + t * 32;
            uint32_t db = sd + dlo(OFF_WO, 16384);
#pragma unroll 1
            for (int s = 0; s < 8; s++) {
                const uint32_t ro = (s & 1) * 16384;
                mbar_wait(bars + 8 * (B_WOFULL + s), 0);
                TSC(TIMING == 11 && tid == 0 && s == 0, 43);
                mbar_wait(bars + 8 * (B_OFULL + s) + 64 * w, 0);
                TSC(TIMING == 11 && tid == 0 && s == 0, 44);
#pragma unroll 1
                for (int it = 0; __any_sync(0xffffffffu, (mism(lds1(chk + ro), lds1(chk + ro + 4096), tag) | mism(lds1(chk + ro + 8192), lds1(chk + ro + 12288), tag)) & 1) && it < SPIN_LIMIT; it++) {
                    NRETRY();
                    const uint32_t fo = wi * 256 + (ln >> 4) * 1024 + (ln & 15) * 16;
                    uint4 v[8];
#pragma unroll
                    for (int c = 0; c < 8; c++) v[c] = ld_rlx4(g_o + (size_t)(((mt * 2 + hp) * 2 + w) * 8 + s) * 16384 + fo + c * 2048);
#pragma unroll
                    for (int c = 0; c < 8; c++) sts4(ring + ro + fo + c * 2048, v[c].x, v[c].y, v[c].z, v[c].w);
                    fence_async_smem();
                    __syncwarp();
                }
                auto issue = [&](bool last) {
                uint32_t e0, e1;
                if (last) {
                    mbar_wait(bars + 8 * B_UPD, 0);
                    int sl0, sl1;
                    asm volatile("ld.shared.s8 %0, [%1];" : "=r"(sl0) : "r"(sb + OFF_ROWMAP + tw * 16 + g) : "memory");
                    asm volatile("ld.shared.s8 %0, [%1];" : "=r"(sl1) : "r"(sb + OFF_ROWMAP + tw * 16 + 8 + g) : "memory");
                    e0 = (sl0 >> 1) == (int)t ? 0x3f80u << ((sl0 & 1) * 16) : 0u; e1 = (sl1 >> 1) == (int)t ? 0x3f80u << ((sl1 & 1) * 16) : 0u;
                }
                bar_sync(1 + w, 256);
                TSC(elect && s == 0, 6 + 8 * w);
                TSC(TIMING == 2 && elect, 32 + 16 * w + s);
                wg_fence();
                if (last) wgmma_rs_n128<1>(acc2, e0, e1, 0u, 0u, mkdesc(sd + dlo(OFF_FA, 0), dhi(128, 0)));
#pragma unroll
                for (int k = 0; k < 8; k++)
                    wgmma_n128<1, 1>(acc2, mkdesc(da0 + (ro >> 4) + k * 128, dhi(128, 0)), mkdesc(db + k * 128, dhi(1024, 1)));
                wg_commit();
                bar_arrive(2 - w, 256);
                if (!last && s == 0) store_o(ST_C, 8);
                db = db == sd + dlo(OFF_WO + (NWO - 1) * 32768, 16384) ? sd + dlo(OFF_WO, 16384) : db + 2048;
                wg_wait<0>();
                if (elect && !last) mbar_arrive(bars + 8 * (B_DONE + s) + 64 * w);
                };
                if (s < 7) issue(false); else issue(true);
            }
#pragma unroll
            for (int i = 0; i < 64; i++) asm volatile("" : "+f"(acc2[i]) :: "memory");
            TSC(elect, 7 + 8 * w);
#pragma unroll
            for (int j = 0; j < 16; j += 2) {
                const int ch = (j & 7) + (ln >> 4);
                asm volatile("stmatrix.sync.aligned.m8n8.x4.shared.b16 [%0], {%1,%2,%3,%4};" ::"r"(mad + (j >> 3) * STAGE + ((ch ^ (ln & 7)) << 4)),
                             "r"(pack_bf16(acc2[4 * j], acc2[4 * j + 1])), "r"(pack_bf16(acc2[4 * j + 2], acc2[4 * j + 3])),
                             "r"(pack_bf16(acc2[4 * j + 4], acc2[4 * j + 5])), "r"(pack_bf16(acc2[4 * j + 6], acc2[4 * j + 7])) : "memory");
                if ((j & 7) == 6) {
                    fence_async_smem();
                    __syncwarp();
                    if (ln == 0) tma_store_2d(&mout, xs + (j >> 3) * STAGE, par * 1024 + cb * 128 + (j >> 3) * 64, j0 + hp * 128 + tw * 16);
                }
            }
            if (ln == 0) asm volatile("cp.async.bulk.commit_group;\ncp.async.bulk.wait_group.read 0;" ::: "memory");
            TSC(elect, 8 + 8 * w);
            TS_END();
        }
    }
}

typedef CUresult (*EncodeFn)(CUtensorMap*, CUtensorMapDataType, cuuint32_t, void*, const cuuint64_t*, const cuuint64_t*, const cuuint32_t*,
                             const cuuint32_t*, CUtensorMapInterleave, CUtensorMapSwizzle, CUtensorMapL2promotion, CUtensorMapFloatOOBfill);

CUtensorMap make_map(EncodeFn fn, const void* base, int rank, const cuuint64_t* dims, const cuuint64_t* strides, const cuuint32_t* box,
                     CUtensorMapSwizzle swz = CU_TENSOR_MAP_SWIZZLE_128B, CUtensorMapL2promotion pro = CU_TENSOR_MAP_L2_PROMOTION_L2_256B) {
    CUtensorMap m;
    cuuint32_t es[5] = {1, 1, 1, 1, 1};
    fn(&m, CU_TENSOR_MAP_DATA_TYPE_BFLOAT16, rank, (void*)base, dims, strides, box, es, CU_TENSOR_MAP_INTERLEAVE_NONE,
       swz, pro, CU_TENSOR_MAP_FLOAT_OOB_FILL_NONE);
    return m;
}

}

extern "C" void kernel_launch(void* const* d_in, const int* in_sizes, int n_in, void* d_out, int out_size) {
    (void)in_sizes; (void)n_in; (void)out_size;
    const __nv_bfloat16* x = (const __nv_bfloat16*)d_in[0];
    const __nv_bfloat16* wqkv = (const __nv_bfloat16*)d_in[1];
    const char* wo = (const char*)d_in[2];
    const __nv_bfloat16* wr = (const __nv_bfloat16*)d_in[4];
    const char* wg = (const char*)d_in[5];
    const char* wu = (const char*)d_in[6];
    const char* wd = (const char*)d_in[7];
    static EncodeFn fn = nullptr;
    static int by_sm = 0;
    static Scratch* scr = nullptr;
    if (!fn) {
        void* p = nullptr; cudaDriverEntryPointQueryResult q;
        cudaGetDriverEntryPoint("cuTensorMapEncodeTiled", &p, cudaEnableDefault, &q);
        fn = (EncodeFn)p;
        cudaFuncSetAttribute(fused_kernel, cudaFuncAttributeMaxDynamicSharedMemorySize, SMEM_LAUNCH);
        cudaGetSymbolAddress((void**)&scr, g_scr);
        int dev = 0, sms = 0;
        cudaGetDevice(&dev);
        cudaDeviceGetAttribute(&sms, cudaDevAttrMultiProcessorCount, dev);
        by_sm = sms == 132;
    }
    Roles roles;
    for (int i = 0; i < 132; i++) {
        const int T = i >> 1, T8 = T < 32 ? T : T + 1 + (T - 32) / 7, fb = (T < 60 ? (~T8 & 7) * 8 + (T8 >> 3) : T < 62 ? T + 4 : T - 2) * 2 + (i & 1);
        roles.v[i] = fb | ((fb & ~31) | (fb & 1) << 4 | (fb & 31) >> 1) << 8;
    }
    const cuuint64_t xd[4] = {2048, 16, 32, 2}, xs[3] = {4096, 131072, 65536};
    const cuuint32_t xb[4] = {64, 16, 4, 2};
    const cuuint64_t wdm[3] = {1024, 1024, 3}, wst[2] = {6144, 2048};
    const cuuint32_t wb[3] = {64, 64, 3};
    const cuuint64_t od[4] = {64, 64, 16, 16}, ost[3] = {2048, 131072, 128};
    const cuuint32_t ob[4] = {64, 8, 16, 2};
    const cuuint64_t yd[2] = {2048, 1024}, yst[1] = {4096};
    const cuuint32_t yb[2] = {64, 16};
    const cuuint64_t sd[3] = {64, 1024, 32}, sst[2] = {4096, 128};
    const cuuint32_t sbx[3] = {64, 16, 4};
    CUtensorMap mxs = make_map(fn, x, 3, sd, sst, sbx);
    const cuuint64_t cd[3] = {3072, 64, 16}, cst[2] = {6144, 393216};
    const cuuint32_t cbx[3] = {64, 8, 2};
    CUtensorMap mcs = make_map(fn, wqkv, 3, cd, cst, cbx, CU_TENSOR_MAP_SWIZZLE_NONE);
    CUtensorMap mx = make_map(fn, x, 4, xd, xs, xb), mw = make_map(fn, wqkv, 3, wdm, wst, wb);
    CUtensorMap mwo = make_map(fn, wo, 4, od, ost, ob), mout = make_map(fn, d_out, 2, yd, yst, yb);
    const cuuint64_t gd[3] = {3584, 1024, 2}, gst[2] = {7168, (cuuint64_t)(wu < wg ? wg - wu : wu - wg)};
    const cuuint32_t gb[3] = {32, 128, 2};
    const cuuint64_t dd[2] = {1024, 3584}, dst[1] = {2048};
    const cuuint32_t db[2] = {64, 64};
    CUtensorMap mgu = make_map(fn, wu < wg ? wu : wg, 3, gd, gst, gb, CU_TENSOR_MAP_SWIZZLE_64B, CU_TENSOR_MAP_L2_PROMOTION_L2_128B);
    CUtensorMap mwd = make_map(fn, wd, 2, dd, dst, db, CU_TENSOR_MAP_SWIZZLE_128B, CU_TENSOR_MAP_L2_PROMOTION_L2_128B);
    fused_kernel<<<132, 512, SMEM_LAUNCH, cudaStreamPerThread>>>(by_sm, x, wqkv, wr, scr, wg, wu, wd, wo, roles, mw, mx, mwo, mxs, mcs, mout, mgu, mwd);
}
```

```cpp
#include <cuda_runtime.h>
#include <cuda.h>
#include <cuda_bf16.h>
#include <stdint.h>

namespace {

constexpr int STAGE = 57344;
constexpr int OFF_FW = 3 * STAGE;
constexpr int OFF_FA = OFF_FW + 49152;
constexpr int OFF_CS = OFF_FA + 6144;
constexpr int OFF_STAT = OFF_CS + 1232;
constexpr int OFF_ROWMAP = OFF_STAT + 2112;
constexpr int OFF_TAG = OFF_ROWMAP + 128;
constexpr int OFF_BAR = OFF_TAG + 8;
constexpr int OFF_F2X = 16384, OFF_HALO = 24576, OFF_O1 = 24576, OFF_O0 = 73728, OFF_WO = 106496, NWO = 3, OFF_MEAN = 2 * STAGE;
static_assert(OFF_WO + NWO * 32768 <= OFF_FA && OFF_O0 + 32768 == OFF_WO && OFF_O1 + 32768 == STAGE, "alias");
constexpr int B_FULLA = 0, B_FULLB = 3, B_ROW = 6, B_FFULL = 11, B_FEMPTY = 14, B_F2DONE = 17, B_GO = 18, B_SW = 19, B_CS = 20, B_WOFULL = 26, B_OFULL = B_WOFULL + 8,
              B_DONE = B_OFULL + 16;
constexpr int B_EMPTY = B_DONE + 16, B_XR = B_EMPTY + 3, B_G1DONE = B_XR + 1;
constexpr int B_UPD = B_G1DONE + 1, B_F2FULL = B_UPD + 1;
constexpr int B_AUX = B_F2FULL + 1, B_PART = B_AUX + 1, B_ATT = B_PART + 1, B_CSDONE = B_ATT + 1, B_AST = B_CSDONE + 1, NBAR = B_AST + 1;
constexpr int SMEM_BYTES = OFF_BAR + NBAR * 8;
static_assert(SMEM_BYTES <= 232448 && OFF_BAR % 8 == 0, "smem");
#define P_PART 13
#define F1_MASK (0x6a005a00u >> (14 - P_PART))
#define PF_CNT 0x2aaaaacu
#define EARLY_FILL 2
#define N_S1 1
#define N_S2 3
#define ST_A 2
#define ST_B 2
#define DBG_F2 1
#define DBG_F1 1
#define DBG_XR 1
#define T_H 250
#define T_O1 250
#define XR_GATE B_G1DONE
#define ST_C 4
#define T_O 2350
#define T_S1 128
#define T_GO 256
#define T_S2 950
#define DBG_CS 0
#define DBG_ST 0
#define N_GA 4
#define N_X 1
#define D_X 2
#define D_R 3
#define N_ROW 5
#define N_W 5
#define K_W1 5
#define K_W2 10
#define N_CS 3
#define N_F1 4
#define LAST 2
#define POLL_NS 100
#define STATS_UNROLL 4
constexpr int kStatsUnroll = STATS_UNROLL;
constexpr int SPIN_LIMIT = 1 << 18;

struct Scratch {
    uint8_t o[2048 * 1024 * 2];
    uint2 rec[2048];
    float cs[8][3072];
    uint32_t halo[128][512];
    uint32_t h[14336];
    float ypart[8][8][1024];
    uint2 sel[16];
    uint32_t hint[128][8];
    uint32_t epoch;
};
__device__ __align__(1024) Scratch g_scr;

#define TS(i) do {} while (0)
#define TS_END() do {} while (0)
constexpr int SMEM_LAUNCH = SMEM_BYTES;
#define TSC(c, i) do {} while (0)
#define NRETRY() do {} while (0)
__device__ __forceinline__ uint32_t smem_u32(const void* p) { return (uint32_t)__cvta_generic_to_shared(p); }
__device__ __forceinline__ void mbar_init(uint32_t bar, uint32_t cnt) { asm volatile("mbarrier.init.shared::cta.b64 [%0], %1;" ::"r"(bar), "r"(cnt) : "memory"); }
__device__ __forceinline__ void mbar_expect_tx(uint32_t bar, uint32_t bytes) { asm volatile("mbarrier.arrive.expect_tx.shared::cta.b64 _, [%0], %1;" ::"r"(bar), "r"(bytes) : "memory"); }
__device__ __forceinline__ void mbar_arrive(uint32_t bar) { asm volatile("mbarrier.arrive.shared::cta.b64 _, [%0];" ::"r"(bar) : "memory"); }
__device__ __forceinline__ void mbar_wait(uint32_t bar, uint32_t parity) {
    asm volatile("{\n.reg .pred P1;\nLAB_WAIT:\nmbarrier.try_wait.parity.shared::cta.b64 P1, [%0], %1;\n@!P1 bra LAB_WAIT;\n}" ::"r"(bar), "r"(parity) : "memory");
}
__device__ __forceinline__ bool mbar_test(uint32_t bar, uint32_t parity) {
    uint32_t ok;
    asm volatile("{\n.reg .pred p;\nmbarrier.test_wait.parity.shared::cta.b64 p, [%1], %2;\nselp.u32 %0, 1, 0, p;\n}" : "=r"(ok) : "r"(bar), "r"(parity) : "memory");
    return ok;
}
__device__ __forceinline__ void tma_2d(uint32_t dst, const CUtensorMap* m, uint32_t bar, int c0, int c1) {
    asm volatile("cp.async.bulk.tensor.2d.shared::cluster.global.mbarrier::complete_tx::bytes [%0], [%1, {%3, %4}], [%2];" ::"r"(dst), "l"(m), "r"(bar), "r"(c0), "r"(c1) : "memory");
}
__device__ __forceinline__ void tma_3d(uint32_t dst, const CUtensorMap* m, uint32_t bar, int c0, int c1, int c2) {
    asm volatile("cp.async.bulk.tensor.3d.shared::cluster.global.mbarrier::complete_tx::bytes [%0], [%1, {%3, %4, %5}], [%2];" ::"r"(dst), "l"(m), "r"(bar), "r"(c0), "r"(c1), "r"(c2) : "memory");
}
__device__ __forceinline__ void tma_4d(uint32_t dst, const CUtensorMap* m, uint32_t bar, int c0, int c1, int c2, int c3) {
    asm volatile("cp.async.bulk.tensor.4d.shared::cluster.global.mbarrier::complete_tx::bytes [%0], [%1, {%3, %4, %5, %6}], [%2];" ::"r"(dst), "l"(m), "r"(bar), "r"(c0), "r"(c1), "r"(c2), "r"(c3) : "memory");
}
__device__ __forceinline__ void tma_store_2d(const CUtensorMap* m, uint32_t src, int c0, int c1) {
    asm volatile("cp.async.bulk.tensor.2d.global.shared::cta.bulk_group [%0, {%2, %3}], [%1];" ::"l"(m), "r"(src), "r"(c0), "r"(c1) : "memory");
}
__device__ __forceinline__ void bulk_g2s(uint32_t dst, const void* src, uint32_t bytes, uint32_t bar) {
    asm volatile("cp.async.bulk.shared::cluster.global.mbarrier::complete_tx::bytes [%0], [%1], %2, [%3];" ::"r"(dst), "l"(src), "r"(bytes), "r"(bar) : "memory");
}
__device__ __forceinline__ void bulk_prefetch(const void* p, uint32_t bytes) { asm volatile("cp.async.bulk.prefetch.L2.global [%0], %1;" ::"l"(p), "r"(bytes) : "memory"); }
__device__ __forceinline__ void fence_async_smem() { asm volatile("fence.proxy.async.shared::cta;" ::: "memory"); }
__device__ __forceinline__ void wg_fence() { asm volatile("wgmma.fence.sync.aligned;" ::: "memory"); }
__device__ __forceinline__ void wg_commit() { asm volatile("wgmma.commit_group.sync.aligned;" ::: "memory"); }
template <int N> __device__ __forceinline__ void wg_wait() { asm volatile("wgmma.wait_group.sync.aligned %0;" ::"n"(N) : "memory"); }
__device__ __forceinline__ uint64_t mkdesc(uint32_t lo, uint32_t hi) { return ((uint64_t)hi << 32) | lo; }
__host__ __device__ constexpr uint32_t dhi(uint32_t sbo, uint32_t mode) { return (sbo >> 4) | (mode << 30); }
__host__ __device__ constexpr uint32_t dlo(uint32_t off, uint32_t lbo) { return (off >> 4) + ((lbo >> 4) << 16); }
__device__ __forceinline__ bool elect_one() {
    uint32_t e;
    asm volatile("{\n.reg .pred p;\nelect.sync _|p, 0xffffffff;\nselp.u32 %0, 1, 0, p;\n}" : "=r"(e));
    return e;
}
template <int R> __device__ __forceinline__ void reg_inc() { asm volatile("setmaxnreg.inc.sync.aligned.u32 %0;" ::"n"(R)); }
template <int R> __device__ __forceinline__ void reg_dec() { asm volatile("setmaxnreg.dec.sync.aligned.u32 %0;" ::"n"(R)); }
__device__ __forceinline__ void bar_sync(int id, int n) { asm volatile("bar.sync %0, %1;" ::"r"(id), "r"(n) : "memory"); }
__device__ __forceinline__ void bar_arrive(int id, int n) { asm volatile("bar.arrive %0, %1;" ::"r"(id), "r"(n) : "memory"); }
__device__ __forceinline__ uint32_t pack_bf16(float lo, float hi) { uint32_t r; asm("cvt.rn.bf16x2.f32 %0, %1, %2;" : "=r"(r) : "f"(hi), "f"(lo)); return r; }
__device__ __forceinline__ float bf_lo(uint32_t u) { return __uint_as_float(u << 16); }
__device__ __forceinline__ float bf_hi(uint32_t u) { return __uint_as_float(u & 0xffff0000u); }
__device__ __forceinline__ float bf16r(float v) { return bf_lo(pack_bf16(v, 0.f)); }
__device__ __forceinline__ uint32_t tagw(uint32_t w, uint32_t m, uint32_t tag) { uint32_t r; asm("lop3.b32 %0, %1, %2, %3, 0xb8;" : "=r"(r) : "r"(w), "r"(m), "r"(tag)); return r; }
__device__ __forceinline__ uint32_t tagf(float f, uint32_t tag) { return tagw(__float_as_uint(f), 1u, tag); }
__device__ __forceinline__ uint32_t movm(uint32_t a) { uint32_t d; asm volatile("movmatrix.sync.aligned.m8n8.trans.b16 %0, %1;" : "=r"(d) : "r"(a)); return d; }
__device__ __forceinline__ void mma16816(float (&c)[4], uint32_t a0, uint32_t a1, uint32_t a2, uint32_t a3, uint32_t b0, uint32_t b1) {
    asm volatile("mma.sync.aligned.m16n8k16.row.col.f32.bf16.bf16.f32 {%0,%1,%2,%3}, {%4,%5,%6,%7}, {%8,%9}, {%0,%1,%2,%3};"
                 : "+f"(c[0]), "+f"(c[1]), "+f"(c[2]), "+f"(c[3]) : "r"(a0), "r"(a1), "r"(a2), "r"(a3), "r"(b0), "r"(b1));
}
__device__ __forceinline__ void mma1688(float (&c)[4], uint32_t a0, uint32_t a1, uint32_t b0) {
    asm volatile("mma.sync.aligned.m16n8k8.row.col.f32.bf16.bf16.f32 {%0,%1,%2,%3}, {%4,%5}, {%6}, {%0,%1,%2,%3};"
                 : "+f"(c[0]), "+f"(c[1]), "+f"(c[2]), "+f"(c[3]) : "r"(a0), "r"(a1), "r"(b0));
}
__device__ __forceinline__ uint32_t ld_rlx(const void* p) { uint32_t v; asm volatile("ld.relaxed.gpu.global.u32 %0, [%1];" : "=r"(v) : "l"(p) : "memory"); return v; }
__device__ __forceinline__ uint2 ld_rlx2(const void* p) { uint2 v; asm volatile("ld.relaxed.gpu.global.v2.u32 {%0,%1}, [%2];" : "=r"(v.x), "=r"(v.y) : "l"(p) : "memory"); return v; }
__device__ __forceinline__ uint4 ld_rlx4(const void* p) { uint4 v; asm volatile("ld.relaxed.gpu.global.v4.u32 {%0,%1,%2,%3}, [%4];" : "=r"(v.x), "=r"(v.y), "=r"(v.z), "=r"(v.w) : "l"(p) : "memory"); return v; }
__device__ __forceinline__ uint32_t ld_acq(const void* p) { uint32_t v; asm volatile("ld.acquire.gpu.global.u32 %0, [%1];" : "=r"(v) : "l"(p) : "memory"); return v; }
__device__ __forceinline__ void st_rlx(void* p, uint32_t v) { asm volatile("st.relaxed.gpu.global.u32 [%0], %1;" ::"l"(p), "r"(v) : "memory"); }
__device__ __forceinline__ void st_rlx2(void* p, uint32_t a, uint32_t b) { asm volatile("st.relaxed.gpu.global.v2.u32 [%0], {%1,%2};" ::"l"(p), "r"(a), "r"(b) : "memory"); }
__device__ __forceinline__ void st_rlx4(void* p, uint32_t a, uint32_t b, uint32_t c, uint32_t d) { asm volatile("st.relaxed.gpu.global.v4.u32 [%0], {%1,%2,%3,%4};" ::"l"(p), "r"(a), "r"(b), "r"(c), "r"(d) : "memory"); }
__device__ __forceinline__ uint4 ldg_nc(const void* p) { uint4 v; asm volatile("ld.global.nc.v4.u32 {%0,%1,%2,%3}, [%4];" : "=r"(v.x), "=r"(v.y), "=r"(v.z), "=r"(v.w) : "l"(p)); return v; }
__device__ __forceinline__ uint32_t mism(uint32_t a, uint32_t b, uint32_t tag) { uint32_t r; asm("lop3.b32 %0, %1, %2, %3, 0x7e;" : "=r"(r) : "r"(a), "r"(b), "r"(tag)); return r; }
__device__ __forceinline__ uint32_t mism(const uint4& v, uint32_t tag) { return mism(v.x, v.y, tag) | mism(v.z, v.w, tag); }
__device__ __forceinline__ void prefetch_l2(const void* p) { asm volatile("prefetch.global.L2 [%0];" ::"l"(p)); }
__device__ __forceinline__ void touch256(uint32_t dst, const void* p) { asm volatile("cp.async.ca.shared.global.L2::256B [%0], [%1], 4;" ::"r"(dst), "l"(p) : "memory"); }
__device__ __forceinline__ void nap(int n) {
#pragma unroll 1
    for (int i = 0; i < n; i++) __nanosleep(100);
}
__device__ __forceinline__ uint32_t now() { uint32_t t; asm volatile("mov.u32 %0, %%globaltimer_lo;" : "=r"(t)); return t; }
__device__ __forceinline__ void until(uint32_t t) {
    while (t - now() - 1 < 16384u) __nanosleep(50);
}
__device__ __forceinline__ uint32_t opaque(uint32_t v) { return __shfl_xor_sync(0xffffffffu, v, 0); }
__device__ __forceinline__ void sts4(uint32_t a, uint32_t x, uint32_t y, uint32_t z, uint32_t w) { asm volatile("st.shared.v4.u32 [%0], {%1,%2,%3,%4};" ::"r"(a), "r"(x), "r"(y), "r"(z), "r"(w) : "memory"); }
__device__ __forceinline__ void sts2(uint32_t a, uint32_t x, uint32_t y) { asm volatile("st.shared.v2.u32 [%0], {%1,%2};" ::"r"(a), "r"(x), "r"(y) : "memory"); }
__device__ __forceinline__ uint4 lds4(uint32_t a) { uint4 v; asm volatile("ld.shared.v4.u32 {%0,%1,%2,%3}, [%4];" : "=r"(v.x), "=r"(v.y), "=r"(v.z), "=r"(v.w) : "r"(a) : "memory"); return v; }
__device__ __forceinline__ float4 lds4f(uint32_t a) { float4 v; asm volatile("ld.shared.v4.f32 {%0,%1,%2,%3}, [%4];" : "=f"(v.x), "=f"(v.y), "=f"(v.z), "=f"(v.w) : "r"(a) : "memory"); return v; }
__device__ __forceinline__ uint2 lds2(uint32_t a) { uint2 v; asm volatile("ld.shared.v2.u32 {%0,%1}, [%2];" : "=r"(v.x), "=r"(v.y) : "r"(a) : "memory"); return v; }
__device__ __forceinline__ float2 lds2f(uint32_t a) { float2 v; asm volatile("ld.shared.v2.f32 {%0,%1}, [%2];" : "=f"(v.x), "=f"(v.y) : "r"(a) : "memory"); return v; }
__device__ __forceinline__ uint32_t lds1(uint32_t a) { uint32_t v; asm volatile("ld.shared.u32 %0, [%1];" : "=r"(v) : "r"(a) : "memory"); return v; }
__device__ __forceinline__ float lds1f(uint32_t a) { return __uint_as_float(lds1(a)); }
__device__ __forceinline__ void sts1(uint32_t a, uint32_t v) { asm volatile("st.shared.u32 [%0], %1;" ::"r"(a), "r"(v) : "memory"); }
__device__ __forceinline__ uint32_t redux_max(uint32_t v) { uint32_t r; asm volatile("redux.sync.max.u32 %0, %1, 0xffffffff;" : "=r"(r) : "r"(v)); return r; }
__device__ __forceinline__ float ex2(float x) { float r; asm("ex2.approx.ftz.f32 %0, %1;" : "=f"(r) : "f"(x)); return r; }
__device__ __forceinline__ float rcp(float x) { float r; asm("rcp.approx.ftz.f32 %0, %1;" : "=f"(r) : "f"(x)); return r; }
__device__ __forceinline__ float sigmoidf(float v) { return rcp(1.f + ex2(v * -1.4426950408889634f)); }

template <int TA, int TB>
__device__ __forceinline__ void wgmma_n192(float (&d)[96], uint64_t da, uint64_t db, int acc = 1) {
    asm volatile("{\n.reg .pred p;\nsetp.ne.b32 p, %100, 0;\n"
        "wgmma.mma_async.sync.aligned.m64n192k16.f32.bf16.bf16 "
        "{%0, %1, %2, %3, %4, %5, %6, %7, %8, %9, %10, %11, %12, %13, %14, %15, "
        "%16, %17, %18, %19, %20, %21, %22, %23, %24, %25, %26, %27, %28, %29, %30, %31, "
        "%32, %33, %34, %35, %36, %37, %38, %39, %40, %41, %42, %43, %44, %45, %46, %47, "
        "%48, %49, %50, %51, %52, %53, %54, %55, %56, %57, %58, %59, %60, %61, %62, %63, "
        "%64, %65, %66, %67, %68, %69, %70, %71, %72, %73, %74, %75, %76, %77, %78, %79, "
        "%80, %81, %82, %83, %84, %85, %86, %87, %88, %89, %90, %91, %92, %93, %94, %95}, "
        "%96, %97, p, 1, 1, %98, %99;\n}\n"
        : "+f"(d[0]), "+f"(d[1]), "+f"(d[2]), "+f"(d[3]), "+f"(d[4]), "+f"(d[5]), "+f"(d[6]), "+f"(d[7]),
          "+f"(d[8]), "+f"(d[9]), "+f"(d[10]), "+f"(d[11]), "+f"(d[12]), "+f"(d[13]), "+f"(d[14]), "+f"(d[15]),
          "+f"(d[16]), "+f"(d[17]), "+f"(d[18]), "+f"(d[19]), "+f"(d[20]), "+f"(d[21]), "+f"(d[22]), "+f"(d[23]),
          "+f"(d[24]), "+f"(d[25]), "+f"(d[26]), "+f"(d[27]), "+f"(d[28]), "+f"(d[29]), "+f"(d[30]), "+f"(d[31]),
          "+f"(d[32]), "+f"(d[33]), "+f"(d[34]), "+f"(d[35]), "+f"(d[36]), "+f"(d[37]), "+f"(d[38]), "+f"(d[39]),
          "+f"(d[40]), "+f"(d[41]), "+f"(d[42]), "+f"(d[43]), "+f"(d[44]), "+f"(d[45]), "+f"(d[46]), "+f"(d[47]),
          "+f"(d[48]), "+f"(d[49]), "+f"(d[50]), "+f"(d[51]), "+f"(d[52]), "+f"(d[53]), "+f"(d[54]), "+f"(d[55]),
          "+f"(d[56]), "+f"(d[57]), "+f"(d[58]), "+f"(d[59]), "+f"(d[60]), "+f"(d[61]), "+f"(d[62]), "+f"(d[63]),
          "+f"(d[64]), "+f"(d[65]), "+f"(d[66]), "+f"(d[67]), "+f"(d[68]), "+f"(d[69]), "+f"(d[70]), "+f"(d[71]),
          "+f"(d[72]), "+f"(d[73]), "+f"(d[74]), "+f"(d[75]), "+f"(d[76]), "+f"(d[77]), "+f"(d[78]), "+f"(d[79]),
          "+f"(d[80]), "+f"(d[81]), "+f"(d[82]), "+f"(d[83]), "+f"(d[84]), "+f"(d[85]), "+f"(d[86]), "+f"(d[87]),
          "+f"(d[88]), "+f"(d[89]), "+f"(d[90]), "+f"(d[91]), "+f"(d[92]), "+f"(d[93]), "+f"(d[94]), "+f"(d[95])
        : "l"(da), "l"(db), "n"(TA), "n"(TB), "r"(acc));
}
template <int TA, int TB>
__device__ __forceinline__ void wgmma_n128(float (&d)[64], uint64_t da, uint64_t db, int acc = 1) {
    asm volatile("{\n.reg .pred p;\nsetp.ne.b32 p, %68, 0;\n"
        "wgmma.mma_async.sync.aligned.m64n128k16.f32.bf16.bf16 "
        "{%0, %1, %2, %3, %4, %5, %6, %7, %8, %9, %10, %11, %12, %13, %14, %15, "
        "%16, %17, %18, %19, %20, %21, %22, %23, %24, %25, %26, %27, %28, %29, %30, %31, "
        "%32, %33, %34, %35, %36, %37, %38, %39, %40, %41, %42, %43, %44, %45, %46, %47, "
        "%48, %49, %50, %51, %52, %53, %54, %55, %56, %57, %58, %59, %60, %61, %62, %63}, "
        "%64, %65, p, 1, 1, %66, %67;\n}\n"
        : "+f"(d[0]), "+f"(d[1]), "+f"(d[2]), "+f"(d[3]), "+f"(d[4]), "+f"(d[5]), "+f"(d[6]), "+f"(d[7]),
          "+f"(d[8]), "+f"(d[9]), "+f"(d[10]), "+f"(d[11]), "+f"(d[12]), "+f"(d[13]), "+f"(d[14]), "+f"(d[15]),
          "+f"(d[16]), "+f"(d[17]), "+f"(d[18]), "+f"(d[19]), "+f"(d[20]), "+f"(d[21]), "+f"(d[22]), "+f"(d[23]),
          "+f"(d[24]), "+f"(d[25]), "+f"(d[26]), "+f"(d[27]), "+f"(d[28]), "+f"(d[29]), "+f"(d[30]), "+f"(d[31]),
          "+f"(d[32]), "+f"(d[33]), "+f"(d[34]), "+f"(d[35]), "+f"(d[36]), "+f"(d[37]), "+f"(d[38]), "+f"(d[39]),
          "+f"(d[40]), "+f"(d[41]), "+f"(d[42]), "+f"(d[43]), "+f"(d[44]), "+f"(d[45]), "+f"(d[46]), "+f"(d[47]),
          "+f"(d[48]), "+f"(d[49]), "+f"(d[50]), "+f"(d[51]), "+f"(d[52]), "+f"(d[53]), "+f"(d[54]), "+f"(d[55]),
          "+f"(d[56]), "+f"(d[57]), "+f"(d[58]), "+f"(d[59]), "+f"(d[60]), "+f"(d[61]), "+f"(d[62]), "+f"(d[63])
        : "l"(da), "l"(db), "n"(TA), "n"(TB), "r"(acc));
}
template <int TB>
__device__ __forceinline__ void wgmma_rs_n128(float (&d)[64], uint32_t a0, uint32_t a1, uint32_t a2, uint32_t a3, uint64_t db) {
    asm volatile("{\n.reg .pred p;\nsetp.ne.b32 p, 1, 0;\n"
        "wgmma.mma_async.sync.aligned.m64n128k16.f32.bf16.bf16 "
        "{%0, %1, %2, %3, %4, %5, %6, %7, %8, %9, %10, %11, %12, %13, %14, %15, "
        "%16, %17, %18, %19, %20, %21, %22, %23, %24, %25, %26, %27, %28, %29, %30, %31, "
        "%32, %33, %34, %35, %36, %37, %38, %39, %40, %41, %42, %43, %44, %45, %46, %47, "
        "%48, %49, %50, %51, %52, %53, %54, %55, %56, %57, %58, %59, %60, %61, %62, %63}, "
        "{%64, %65, %66, %67}, %68, p, 1, 1, %69;\n}\n"
        : "+f"(d[0]), "+f"(d[1]), "+f"(d[2]), "+f"(d[3]), "+f"(d[4]), "+f"(d[5]), "+f"(d[6]), "+f"(d[7]),
          "+f"(d[8]), "+f"(d[9]), "+f"(d[10]), "+f"(d[11]), "+f"(d[12]), "+f"(d[13]), "+f"(d[14]), "+f"(d[15]),
          "+f"(d[16]), "+f"(d[17]), "+f"(d[18]), "+f"(d[19]), "+f"(d[20]), "+f"(d[21]), "+f"(d[22]), "+f"(d[23]),
          "+f"(d[24]), "+f"(d[25]), "+f"(d[26]), "+f"(d[27]), "+f"(d[28]), "+f"(d[29]), "+f"(d[30]), "+f"(d[31]),
          "+f"(d[32]), "+f"(d[33]), "+f"(d[34]), "+f"(d[35]), "+f"(d[36]), "+f"(d[37]), "+f"(d[38]), "+f"(d[39]),
          "+f"(d[40]), "+f"(d[41]), "+f"(d[42]), "+f"(d[43]), "+f"(d[44]), "+f"(d[45]), "+f"(d[46]), "+f"(d[47]),
          "+f"(d[48]), "+f"(d[49]), "+f"(d[50]), "+f"(d[51]), "+f"(d[52]), "+f"(d[53]), "+f"(d[54]), "+f"(d[55]),
          "+f"(d[56]), "+f"(d[57]), "+f"(d[58]), "+f"(d[59]), "+f"(d[60]), "+f"(d[61]), "+f"(d[62]), "+f"(d[63])
        : "r"(a0), "r"(a1), "r"(a2), "r"(a3), "l"(db), "n"(TB));
}
template <int TA, int TB>
__device__ __forceinline__ void wgmma_n8(float (&d)[4], uint64_t da, uint64_t db, int acc = 1) {
    asm volatile("{\n.reg .pred p;\nsetp.ne.b32 p, %8, 0;\n"
        "wgmma.mma_async.sync.aligned.m64n8k16.f32.bf16.bf16 "
        "{%0, %1, %2, %3}, "
        "%4, %5, p, 1, 1, %6, %7;\n}\n"
        : "+f"(d[0]), "+f"(d[1]), "+f"(d[2]), "+f"(d[3])
        : "l"(da), "l"(db), "n"(TA), "n"(TB), "r"(acc));
}

__device__ __forceinline__ uint32_t norm_pair(uint32_t u, float m, float rinv) {
    uint32_t d = pack_bf16(bf_lo(u) - m, bf_hi(u) - m);
    return pack_bf16(bf_lo(d) * rinv, bf_hi(d) * rinv);
}

struct Roles { uint16_t v[132]; };

__global__ void __launch_bounds__(512, 1)
fused_kernel(int by_sm, const __nv_bfloat16* __restrict__ x, const __nv_bfloat16* __restrict__ wqkv, const __nv_bfloat16* __restrict__ wr,
             Scratch* const S, const char* __restrict__ wg, const char* __restrict__ wu, const char* __restrict__ wd, const char* __restrict__ wo,
             const __grid_constant__ Roles roles,
             const __grid_constant__ CUtensorMap mw, const __grid_constant__ CUtensorMap mx, const __grid_constant__ CUtensorMap mwo,
             const __grid_constant__ CUtensorMap mxs, const __grid_constant__ CUtensorMap mcs, const __grid_constant__ CUtensorMap mout, const __grid_constant__ CUtensorMap mgu, const __grid_constant__ CUtensorMap mwd) {
    extern __shared__ __align__(1024) uint8_t smem[];
    constexpr uint32_t sb = 1024, bars = sb + OFF_BAR, sd = sb >> 4;
    const int tid = threadIdx.x, lane = tid & 31;
    asm volatile("{\n.reg .pred p, q;\nsetp.lt.u32 p, %2, 16;\nsetp.lt.u32 q, %2, 24;\n@p prefetch.global.L2 [%0];\n@p prefetch.global.L2 [%0 + 128];\n@q prefetch.global.L2 [%1];\n}" ::
                 "l"((const char*)x + (blockIdx.x * 16 + tid - 32) % 2048 * 2048), "l"((const char*)wqkv + (blockIdx.x * 24 + tid - 32) * 128), "r"(tid - 32));
    const int warp = __shfl_sync(0xffffffffu, tid >> 5, 0);
    uint32_t smid;
    asm volatile("mov.u32 %0, %%smid;" : "=r"(smid));
    const int role = roles.v[by_sm ? smid : blockIdx.x], fb = role & 255, b = role >> 8, kc = fb >> 4, c2 = fb & 15;
    const int mt = b >> 4, nt = b & 15, hp = b & 1, cb = nt >> 1;
    const int par = mt >> 2, j0 = (mt & 3) * 256;
    uint8_t* const g_o = S->o;

    auto load_stage = [&](int p, uint32_t so, int bi) {
        const uint32_t fullA = bars + 8 * (B_FULLA + bi), fullB = bars + 8 * (B_FULLB + bi);
        mbar_expect_tx(fullA, 40960);
        tma_3d(sb + so + 16384, &mw, fullA, nt * 64, p * 64, 0);
        tma_4d(sb + so, &mx, fullA, par * 1024 + p * 64, 0, (j0 >> 5) + 4, 0);
        mbar_expect_tx(fullB, 16384);
        tma_4d(sb + so + 40960, &mx, fullB, par * 1024 + p * 64, 0, j0 >> 5, 0);
    };
    if (warp == 0 && fb < 128 && elect_one()) {
        mbar_init(bars + 8 * B_FULLA, 1); mbar_init(bars + 8 * B_FULLB, 1);
        load_stage(0, STAGE, 0);
    }
    if (fb >= 128) {
        if (fb > 128) { nap(16); TS_END(); return; }
        const uint32_t tag = (ld_rlx(&S->epoch) & 1) - 1;
        if (tid < 8) st_rlx2(&S->sel[tid], ~tag, ~tag);
        uint4 ra, rb;
#pragma unroll 1
        for (int it = 0; it < SPIN_LIMIT; it++) {
            ra = ld_rlx4(&S->rec[tid * 2]); rb = ld_rlx4(&S->rec[1024 + tid * 2]);
            if (!__any_sync(0xffffffffu, (mism(ra.x, ra.z, tag) | mism(rb.x, rb.z, tag)) & 0x8000u)) break;
        }
        __syncwarp();
        TSC(tid == 0, 31);
        sts4(sb + 1024 + tid * 16, ra.y, rb.y, ra.w, rb.w);
        uint4 k = make_uint4(ra.x, ra.z, rb.x, rb.z);
        uint32_t cand;
#pragma unroll 1
        for (int pass = 0; pass < 2; pass++) {
            const uint32_t a0 = max(k.x, k.y), a1 = min(k.x, k.y), a2 = max(k.z, k.w), a3 = min(k.z, k.w), c1 = min(a0, a2), c2 = max(a1, a3);
            k = make_uint4(max(a0, a2), max(c1, c2), min(c1, c2), min(a1, a3));
#pragma unroll
            for (int r = 0; r < 8; r++) {
                const uint32_t m = redux_max(k.x);
                if (lane == r) cand = m;
                if (k.x == m) k = make_uint4(k.y, k.z, k.w, 0);
            }
            if (pass) break;
            if (lane < 8) sts1(sb + (warp * 8 + lane) * 4, cand);
            __syncthreads();
            if (warp) { TS_END(); return; }
            k = lds4(sb + lane * 16);
            TSC(TIMING == 12 && tid == 0 && k.x != 0x12345, 40);
        }
        if (lane < 8) st_rlx2(&S->sel[lane], cand, lds1(sb + 1024 + (~cand & 0x7ffu) * 4));
        TSC(tid == 0, 20);
        TS_END();
        return;
    }
    uint32_t epoch;
    if (warp >> 2 == 2) epoch = ld_rlx(&S->epoch);
    if (warp == 1 && elect_one()) {
#pragma unroll
        for (int i = 0; i < B_WOFULL; i++)
            if (i != B_FULLA && i != B_FULLB) mbar_init(bars + 8 * i, i >= B_FFULL && i < B_FEMPTY ? 5 : 1);
    }
    if (warp == 4 && elect_one()) {
#pragma unroll
        for (int i = B_EMPTY; i < NBAR; i++) mbar_init(bars + 8 * i, i < B_UPD ? 2 : i < B_AUX ? 4 : i == B_AUX ? 7 : i == B_CSDONE ? 3 : 8);
    }
    __syncthreads();

    if (warp >= 12) {
        reg_dec<24>();
        if (warp > 12) {
            const int p = warp - 13;
            if (p == 1) {
                float sw = 0.f;
                mbar_wait(bars + 8 * (B_ROW + 4), 0);
#pragma unroll 1
                for (int i = 0; i < 16; i++) { const uint32_t q = lds1(sb + OFF_FA + i * 128 + lane * 4); sw += bf_lo(q) + bf_hi(q); }
#pragma unroll 1
                for (int o = 1; o < 32; o <<= 1) sw += __shfl_xor_sync(0xffffffffu, sw, o);
                if (lane == 0) { sts1(sb + OFF_TAG + 4, __float_as_uint(sw)); mbar_arrive(bars + 8 * B_SW); }
            } else {
#pragma unroll 1
                for (int q = 0; q < 4; q++) {
                    nap(p ? (q ? D_R : N_ROW) : (q ? D_X : N_X));
                    if (p == 0) {
                        const __nv_bfloat16* xp = x + (size_t)((j0 + nt * 16 + (lane >> 1)) * 2 + par) * 1024 + q * 256 + (lane & 1) * 64;
                        prefetch_l2(xp); prefetch_l2(xp + 128);
                    } else if (elect_one()) {
                        mbar_expect_tx(bars + 8 * (B_ROW + q), 8192);
                        tma_3d(sb + OFF_FW + q * 8192, &mxs, bars + 8 * (B_ROW + q), 0, j0 + nt * 16, par * 16 + q * 4);
                    }
                }
                if (p == 0) nap(N_CS);
            }
            const uint32_t stg = sb + OFF_FW + 32768 + p * 4096 + lane * 16;
            float c[8];
#pragma unroll
            for (int i = 0; i < 8; i++) c[i] = 0.f;
#pragma unroll 1
            for (int n = 0; n < 10; n++) {
                const uint32_t bo = (n & 1) * 2048, bar = bars + 8 * (B_CS + 2 * p + (n & 1));
                if (n >= 2) {
                    mbar_wait(bar, ~(n >> 1) & 1);
#pragma unroll 2
                    for (int i = 0; i < 4; i++) {
                        const uint4 v = lds4(stg + bo + i * 512);
                        c[0] += bf_lo(v.x); c[1] += bf_hi(v.x); c[2] += bf_lo(v.y); c[3] += bf_hi(v.y);
                        c[4] += bf_lo(v.z); c[5] += bf_hi(v.z); c[6] += bf_lo(v.w); c[7] += bf_hi(v.w);
                    }
                    asm volatile("" :: "f"(c[7]));
                    __syncwarp();
                }
                if (n < 8 && elect_one()) {
                    mbar_expect_tx(bar, 2048);
                    tma_3d(sb + OFF_FW + 32768 + p * 4096 + bo, &mcs, bar, p * 1024 + nt * 64, mt * 8, 2 * n);
                }
            }
            sts4(stg + lane * 16, __float_as_uint(c[0]), __float_as_uint(c[1]), __float_as_uint(c[2]), __float_as_uint(c[3]));
            sts4(stg + lane * 16 + 16, __float_as_uint(c[4]), __float_as_uint(c[5]), __float_as_uint(c[6]), __float_as_uint(c[7]));
            bar_sync(13, 128);
            const uint32_t tag = lds1(sb + OFF_TAG);
            float* gcs = &S->cs[0][p * 1024 + nt * 64];
            {
                const float2 a0 = lds2f(stg - lane * 8), a1 = lds2f(stg - lane * 8 + 256), a2 = lds2f(stg - lane * 8 + 512), a3 = lds2f(stg - lane * 8 + 768);
                st_rlx2(gcs + mt * 3072 + lane * 2, tagf((a0.x + a1.x) + (a2.x + a3.x), tag), __float_as_uint((a0.y + a1.y) + (a2.y + a3.y)));
            }
            fence_async_smem();
            __syncwarp();
            if (lane == 0) mbar_arrive(bars + 8 * B_CSDONE);
            TSC(warp == 13 && lane == 0, 19);
            {
                uint4 v[4];
                const float* src = gcs + (lane >> 4) * 4 * 3072 + (lane & 15) * 4;
#pragma unroll 1
                for (int it = 0; it < SPIN_LIMIT; it++) {
#pragma unroll
                    for (int m = 0; m < 4; m++) v[m] = ld_rlx4(src + m * 3072);
                    if (!__any_sync(0xffffffffu, (mism(v[0].x, v[1].x, tag) | mism(v[2].x, v[3].x, tag)) & 1)) break;
                }
                __syncwarp();
#pragma unroll
                for (int c = 0; c < 4; c++) {
                    const float a = (__uint_as_float((&v[0].x)[c]) + __uint_as_float((&v[1].x)[c])) + (__uint_as_float((&v[2].x)[c]) + __uint_as_float((&v[3].x)[c]));
                    (&v[0].x)[c] = __float_as_uint(a + __shfl_xor_sync(0xffffffffu, a, 16));
                }
                const uint32_t ca = sb + OFF_CS + p * 384 + ((lane & 15) >> 1) * 48 + (lane & 1) * 8;
#pragma unroll 1
                for (int r = 0; r < 3; r++) {
                    const uint32_t u0 = pack_bf16(__uint_as_float(v[0].x), __uint_as_float(v[0].y)), u1 = pack_bf16(__uint_as_float(v[0].z), __uint_as_float(v[0].w));
                    sts2(ca + r * 16, u0, u1);
                    v[0].x = __float_as_uint(__uint_as_float(v[0].x) - bf_lo(u0)); v[0].y = __float_as_uint(__uint_as_float(v[0].y) - bf_hi(u0));
                    v[0].z = __float_as_uint(__uint_as_float(v[0].z) - bf_lo(u1)); v[0].w = __float_as_uint(__uint_as_float(v[0].w) - bf_hi(u1));
                }
                if (lane < 20) sts1(sb + OFF_CS + 1152 + lane * 4, 0);
                fence_async_smem();
            }
            __syncwarp();
            if (lane == 0) mbar_arrive(bars + 8 * B_AUX);
            TSC(warp == 13 && lane == 0, 21);
            mbar_wait(bars + 8 * B_PART, 0);
            mbar_wait(bars + 8 * (B_EMPTY + 2), 0);
            if (p == 0) {
                uint4 v[4];
#pragma unroll
                for (int c = 0; c < 4; c++) v[c] = make_uint4(0, 0, 0, 0);
                const uint32_t* hsrc = &S->halo[b - 16][lane * 4];
#pragma unroll 1
                for (int it = 0; it < SPIN_LIMIT && j0; it++) {
#pragma unroll
                    for (int c = 0; c < 4; c++) v[c] = ld_rlx4(hsrc + c * 128);
                    if (!__any_sync(0xffffffffu, (mism(v[0].x, v[1].x, tag) | mism(v[2].x, v[3].x, tag)) & 1)) break;
                }
#pragma unroll
                for (int c = 0; c < 4; c++) sts4(sb + OFF_HALO + c * 512 + lane * 16, v[c].x, v[c].y, v[c].z, v[c].w);
                __syncwarp();
                bar_arrive(3, 64);
                TSC(TIMING == 11 && lane == 0, 34);
            } else {
                const int w = p - 1;
                const uint8_t* osrc = g_o + (size_t)((mt * 2 + hp) * 2 + w) * 131072;
                const bool far = w > hp && j0 && lane >= 16;
                const uint32_t* hsrc = &S->hint[b & 0x70][0] + ((lane & 15) - (far ? 16 : 0)) * 8;
                if (lane == 0 && !w) st_rlx(&S->hint[b][0], tagw(now(), 1u, tag));
                uint32_t hv;
#pragma unroll 1
                for (int it = 0; it < SPIN_LIMIT; it++) {
                    hv = ld_rlx(hsrc);
                    if (!__any_sync(0xffffffffu, (hv ^ tag) & 1)) break;
                }
                TSC(TIMING == 11 && lane == 0, 32 + w);
                const uint32_t tn = __shfl_sync(0xffffffffu, hv, 0) - 0x40000000u;
                hv = redux_max(hv - tn + (far ? T_H : 0)) + tn + T_O + w * T_O1;
                mbar_wait(bars + 8 * (w ? B_AST : B_G1DONE), 0);
                if (elect_one()) {
#pragma unroll 1
                    for (int st = 0; st < 8; st++) {
                        const uint32_t full = bars + 8 * (B_OFULL + 8 * w + st);
                        if (st == 2 && !w) { until(hv + T_GO); mbar_arrive(bars + 8 * B_GO); }
                        if (st >= 2) mbar_wait(full + 8 * (B_DONE - B_OFULL - 2), 0);
                        if (st < 3) until(hv + (st == 2 ? T_S2 : st * T_S1));
                        TSC(st == 0, 28 + w);
                        mbar_expect_tx(full, 16384);
                        bulk_g2s(sb + (w ? OFF_O1 : OFF_O0) + (st & 1) * 16384, osrc + st * 16384, 16384, full);
                    }
                }
            }
            TS_END();
            return;
        }
        if (elect_one()) {
            auto load_wo = [&](int s, int ws) {
                mbar_expect_tx(bars + 8 * (B_WOFULL + s), 32768);
                tma_4d(sb + OFF_WO + ws * 32768, &mwo, bars + 8 * (B_WOFULL + s), 0, s * 8, 0, cb * 2);
            };
            uint32_t so = 2 * STAGE, ph = 1, cnt = PF_CNT << 4;
            int bi = 1, q = 0;
            mbar_expect_tx(bars + 8 * (B_ROW + 4), 2048);
            bulk_g2s(sb + OFF_FA, wr, 2048, bars + 8 * (B_ROW + 4));
            if (smem_u32(smem) != sb) __trap();
            const char* pf = (b < 64 ? wg : wu) + (b & 63) * 7168;
#pragma unroll 1
            for (int p = 1; p < 16; p++) {
                if (p < 3) nap(p == 1 ? N_S1 : N_S2);
                mbar_wait(bars + 8 * (B_EMPTY + bi), ph);
                load_stage(p, so, bi);
                if (p >= 2 && p < 5) {
                    const int k0 = p == 2 ? 3 : p == 3 ? K_W1 : K_W2, n = ((p == 2 ? K_W1 : p == 3 ? K_W2 : 16) - k0) * 3072;
                    if (p == 2) nap(N_W);
                    bulk_prefetch((const char*)wqkv + k0 * 393216 + b * n, n);
                }
#pragma unroll 1
                for (int e = q + (cnt & 3); q < e; q++) {
                    if (q == 16) pf = wd + mt * 7 * 131072 + nt * 8192;
                    if (q == 23) pf = wo + b * 8192;
                    bulk_prefetch(pf, q < 16 ? 7168 : 8192);
                    pf += q < 16 ? 64 * 7168 : q < 23 ? 131072 : 1048576;
                }
                cnt >>= 2;
                so = so == 2 * STAGE ? 0 : so + STAGE;
                if (++bi == 3) { bi = 0; ph ^= 1; }
            }
            TS(27);
            int ws = 1;
#pragma unroll 1
            for (int i = 0; i < 8; i++) {
                if (i == 1) {
                    mbar_wait(bars + 8 * (B_EMPTY + 2), 0);
                    mbar_expect_tx(bars + 8 * B_F2FULL, 8192);
                    tma_2d(sb + OFF_F2X, &mwd, bars + 8 * B_F2FULL, DBG_F2 * c2 * 64, DBG_F2 * kc * 448);
#pragma unroll 1
                    for (int c = 0; c < 2; c++) {
                        if (c) mbar_wait(bars + 8 * XR_GATE, 0);
                        mbar_expect_tx(bars + 8 * B_XR, 16384);
                        tma_4d(sb + c * STAGE, &mx, bars + 8 * B_XR, DBG_XR * (par * 1024 + cb * 128 + c * 64), 0, DBG_XR * ((j0 >> 5) + hp * 4), 0);
                    }
                } else {
                    mbar_wait(bars + 8 * (i == 0 ? B_EMPTY + 1 : i == 2 ? B_F2DONE : B_DONE - NWO + i), 0);
                    if (i) mbar_wait(bars + 8 * (i == 2 ? B_OFULL : B_DONE + 8 - NWO + i), 0);
                }
                load_wo(i < 2 ? 1 - i : i, i == 1 ? 0 : ws);
                if (i != 1 && ++ws == NWO) ws = 0;
            }
        }
        TS_END();
    } else if (warp >= 8) {
        reg_dec<40>();
        const int p = warp - 8;
        const bool f1 = fb < 112;
        auto ffn_w = [&](int n, int s) {
            const uint32_t dst = sb + OFF_FW + s * 16384;
            if (n < 8) {
                mbar_expect_tx(bars + 8 * (B_FFULL + s), 16384);
                tma_3d(dst, &mgu, bars + 8 * (B_FFULL + s), DBG_F1 * fb * 32, n * 128, 0);
            } else {
                mbar_expect_tx(bars + 8 * B_F2FULL, 16384);
                tma_2d(dst, &mwd, bars + 8 * B_F2FULL, DBG_F2 * c2 * 64, DBG_F2 * kc * 448 + 64 + s * 128);
                tma_2d(dst + 8192, &mwd, bars + 8 * B_F2FULL, DBG_F2 * c2 * 64, DBG_F2 * kc * 448 + 128 + s * 128);
            }
        };
        const uint32_t tag = (epoch & 1) - 1;
        {
            const int ta = tid - 256;
            if (ta < 48) st_rlx4(&S->cs[mt][(ta >> 4) * 1024 + nt * 64 + (ta & 15) * 4], ~tag, ~tag, ~tag, ~tag);
            st_rlx4(&S->ypart[kc][ta >> 4][c2 * 64 + (ta & 15) * 4], ~tag, ~tag, ~tag, ~tag);
            if (p == 3 && f1) st_rlx4(&S->h[fb * 128 + lane * 4], ~tag, ~tag, ~tag, ~tag);
            if (ta < 2) st_rlx4(&S->hint[b][ta * 4], ~tag, ~tag, ~tag, ~tag);
            st_rlx4(&S->halo[b][ta * 4], ~tag, ~tag, ~tag, ~tag);
        }
        float s1 = 0.f, s2 = 0.f, sr = 0.f, sw, sh = 0.f;
        {
            const uint32_t xa = sb + OFF_FW + p * 512 + lane * 16, wa = sb + OFF_FA + (((p * 4 + (lane >> 3)) ^ lane) & 7) * 16;
            TSC(TIMING == 12 && lane == 0, 50 + p);
            mbar_wait(bars + 8 * (B_ROW + 4), 0);
            {
                float c1 = 0.f, c2 = 0.f, cr = 0.f;
#pragma unroll 1
                for (int q = 0; q < 4; q++) {
                mbar_wait(bars + 8 * (B_ROW + q), 0);
                TSC(TIMING == 12 && tid == 256 + 96, 32 + q);
                TSC(tid == 256 && q == 3, 17);
#pragma unroll
                for (int i = 0; i < 4; i++) {
                    const uint4 u = lds4(xa + q * 8192 + i * 2048), w4 = lds4(wa + q * 512 + i * 128);
                    if (DBG_ST == 1) { s2 += fabsf(bf_lo(u.x ^ (u.y & u.z & u.w & 1))); sr += bf_lo(w4.x ^ w4.y ^ w4.z ^ w4.w ^ u.x); continue; }
                    const float a0 = bf_lo(u.x), a1 = bf_hi(u.x), a2 = bf_lo(u.y), a3 = bf_hi(u.y), a4 = bf_lo(u.z), a5 = bf_hi(u.z), a6 = bf_lo(u.w), a7 = bf_hi(u.w);
                    s1 += a0 + a1; c1 += a4 + a5; s1 += a2 + a3; c1 += a6 + a7;
                    s2 = fmaf(a0, a0, s2); c2 = fmaf(a4, a4, c2); sr = fmaf(a0, bf_lo(w4.x), sr); cr = fmaf(a4, bf_lo(w4.z), cr);
                    s2 = fmaf(a1, a1, s2); c2 = fmaf(a5, a5, c2); sr = fmaf(a1, bf_hi(w4.x), sr); cr = fmaf(a5, bf_hi(w4.z), cr);
                    s2 = fmaf(a2, a2, s2); c2 = fmaf(a6, a6, c2); sr = fmaf(a2, bf_lo(w4.y), sr); cr = fmaf(a6, bf_lo(w4.w), cr);
                    s2 = fmaf(a3, a3, s2); c2 = fmaf(a7, a7, c2); sr = fmaf(a3, bf_hi(w4.y), sr); cr = fmaf(a7, bf_hi(w4.w), cr);
                }
                }
                s1 += c1; s2 += c2; sr += cr;
            }
            mbar_wait(bars + 8 * B_SW, 0);
            sw = lds1f(sb + OFF_TAG + 4);
#pragma unroll 1
            for (int pass = 0;; pass++) {
#pragma unroll
                for (int o = 1; o < 8; o <<= 1) {
                    s1 += __shfl_xor_sync(0xffffffffu, s1, o); s2 += __shfl_xor_sync(0xffffffffu, s2, o); sr += __shfl_xor_sync(0xffffffffu, sr, o);
                }
                s1 *= 1.f / 1024.f;
                s2 = fmaf(-s1, s1, s2 * (1.f / 1024.f));
                if (!__any_sync(0xffffffffu, !pass && s1 * s1 > 256.f * s2)) break;
                sh = bf16r(s1); s1 = 0.f; s2 = 0.f; sr = 0.f;
#pragma unroll 1
                for (uint32_t o = 0; o < 2048; o = opaque(o + ((o & 12) == 12 ? 116 : 4))) {
                    const uint32_t u = lds1(xa + (o >> 7) * 2048 + (o & 12)), q = lds1(wa + o);
                    const float a0 = bf_lo(u) - sh, a1 = bf_hi(u) - sh;
                    s1 += a0 + a1; s2 = fmaf(a0, a0, fmaf(a1, a1, s2)); sr = fmaf(a0, bf_lo(q), fmaf(a1, bf_hi(q), sr));
                }
            }
        }
        const int ta = opaque(tid) - 256, lane = ta & 31, g = lane >> 2, t = lane & 3;
        {
            if ((lane & 7) == 0) {
                const int s = b * 16 + p * 4 + (lane >> 3);
                const float mb = bf16r(sh + s1);
                float den;
                asm("sqrt.approx.f32 %0, %1;" : "=f"(den) : "f"(bf16r(bf16r(s2) + 1e-5f)));
                den = bf16r(den);
                uint32_t rb = pack_bf16(fmaf(sh - mb, sw, sr) * rcp(den), 0.f);
                if (rb == 0x8000u) rb = 0;
                uint32_t ord = (rb & 0x8000u) ? (~rb & 0xffffu) : (rb | 0x8000u);
                if ((rb & 0x7fffu) > 0x7f80u) ord = 0;
                st_rlx2(&S->rec[s], (ord << 16) | (tag & 0x8000u) | (0x47ffu - (s & 1023) * 2 - par), pack_bf16(mb, den));
            }
            TSC(TIMING == 12 && lane == 0, 36 + p);
            bar_sync(12, 128);
            if (p == 1) sts1(sb + OFF_ROWMAP + lane * 4, 0xffffffffu);
            if (p == 0) {
                if (lane == 0) {
                    sts1(sb + OFF_TAG, tag);
                }
                __syncwarp();
                bar_arrive(13, 128);
            }
            TSC(ta == 0, 18);
        }
        {
            uint2 r[3];
            nap(N_GA);
            const uint2* src = &S->rec[mt * 256 + ta];
            const int l2 = ta < 8 && j0 ? -8 : 0;
#pragma unroll 1
            for (int it = 0; it < SPIN_LIMIT; it++) {
                r[0] = ld_rlx2(src + l2); r[1] = ld_rlx2(src); r[2] = ld_rlx2(src + 128);
                if (!__any_sync(0xffffffffu, (mism(r[0].x, r[1].x, tag) | (r[2].x ^ tag)) & 0x8000u)) break;
            }
#pragma unroll
            for (int n = 0; n < 3; n++)
                if (n || ta < 8) sts2(sb + OFF_STAT + (n ? n * 1024 - 960 : 0) + ta * 8, (r[n].y << 16) ^ 0x80000000u, __float_as_uint(rcp(bf_hi(r[n].y))));
        }
        __syncwarp();
        if (lane == 0) mbar_arrive(bars + 8 * B_AUX);
        TSC(ta == 0, 30);
        if (f1 && p < EARLY_FILL && elect_one()) { nap(p * N_F1); ffn_w(p, p); }
        __syncwarp();
        uint2 sel;
#pragma unroll 1
        for (int it = 0; it < SPIN_LIMIT; it++) {
            sel = ld_rlx2(&S->sel[lane & 7]);
            if (!__any_sync(0xffffffffu, (sel.x ^ tag) & 0x8000u)) break;
            __nanosleep(POLL_NS);
        }
        TSC(ta == 0, 26);
        if (b == 0 && ta == 0) st_rlx(&S->epoch, epoch + 1);
        {
            const __nv_bfloat16* xp = x + (~sel.x & 0x7ffu) * 1024 + (ta >> 3) * 8;
            const float mb = bf_lo(sel.y), rinv = rcp(bf_hi(sel.y));
            uint4 v = ldg_nc(xp), v2 = ldg_nc(xp + 128);
            int s = f1 ? 0 : 2;
#pragma unroll 1
            for (int n = f1 ? 0 : 8; n < (p ? 8 : 11); n++) {
                mbar_wait(bars + 8 * (f1 ? B_FEMPTY + s : B_PART), f1 && (n < 3 || (n >= 6 && n < 9)));
                if (p == 0 && s == 2) mbar_wait(bars + 8 * B_CSDONE, 0);
                if (p == 0 && n >= EARLY_FILL && elect_one()) ffn_w(n, s);
                if (n < 8) {
                    sts4(sb + OFF_FA + s * 2048 + ta * 16, norm_pair(v.x, mb, rinv), norm_pair(v.y, mb, rinv), norm_pair(v.z, mb, rinv), norm_pair(v.w, mb, rinv));
                    fence_async_smem();
                    __syncwarp();
                    if (lane == 0) mbar_arrive(bars + 8 * (B_FFULL + s));
                    TSC(TIMING == 12 && ta == 0, 41 + n);
                    v = v2;
                    if (n) v = ldg_nc(xp + ((n + 1) & 7) * 128);
                }
                if (++s == 3) s = 0;
            }
        }
        mbar_wait(bars + 8 * B_PART, 0);
        if (f1 && p >= 2) {
            const uint32_t pa = sb + OFF_FA + (ta - 64) * 16, go = wu < wg ? 1024 : 0;
            const float4 g0 = lds4f(pa + go), g1 = lds4f(pa + 2048 + go), u0 = lds4f(pa + (go ^ 1024)), u1 = lds4f(pa + 2048 + (go ^ 1024));
            float hv[4];
#pragma unroll
            for (int c = 0; c < 4; c++) {
                const float ga = bf16r((&g0.x)[c] + (&g1.x)[c]), up = bf16r((&u0.x)[c] + (&u1.x)[c]);
                hv[c] = bf16r(ga * sigmoidf(ga)) * up;
            }
#pragma unroll
            for (int hh = 0; hh < 2; hh++) {
                const float o = __shfl_xor_sync(0xffffffffu, (g & 1) ? hv[2 * hh] : hv[2 * hh + 1], 4);
                st_rlx(&S->h[(fb * 4 + (p & 1) * 2 + hh) * 32 + (2 * t + (g & 1)) * 4 + (g >> 1)],
                       tagw((g & 1) ? pack_bf16(o, hv[2 * hh + 1]) : pack_bf16(hv[2 * hh], o), g < 2, tag));
            }
            TSC(ta == 64, 22);
        }
        {
            uint4 hq[4];
            const uint32_t* hp4 = S->h + kc * 1792 + ta * 4;
#pragma unroll 1
            for (int it = 0; it < SPIN_LIMIT; it++) {
#pragma unroll
                for (int n = 0; n < 4; n++) hq[n] = ld_rlx4(hp4 + (n < 3 ? n * 512 : p < 2 ? 1536 : 0));
                if (!__any_sync(0xffffffffu, (mism(hq[0].x, hq[1].x, tag) | mism(hq[2].x, hq[3].x, tag)) & 1)) break;
            }
            mbar_wait(bars + 8 * B_G1DONE, 0);
            bar_sync(12, 128);
#pragma unroll
            for (int n = 0; n < 4; n++) sts4(sb + OFF_FA + ta * 16 + (n < 3 ? n * 2048 : p < 2 ? 6144 : 0), hq[n].x, hq[n].y, hq[n].z, hq[n].w);
            fence_async_smem();
            bar_sync(12, 128);
            TSC(ta == 0, 25);
            mbar_wait(bars + 8 * B_F2FULL, 0);
            mbar_wait(bars + 8 * B_ATT, 0);
            float acc[4] = {0.f, 0.f, 0.f, 0.f};
            uint32_t da = sd + dlo(OFF_F2X, 8192), db = sd + dlo(OFF_FA, 128);
#pragma unroll 1
            for (int q = 0; q < 7; q++) {
                wg_fence();
#pragma unroll
                for (int j = 0; j < 4; j++) wgmma_n8<1, 0>(acc, mkdesc(da + j * 128, dhi(1024, 1)), mkdesc(db + j * 16, dhi(128, 0)));
                wg_commit();
                da = sd + dlo(OFF_FW, 8192) + q * 512; db += 64;
            }
            wg_wait<0>();
            if (ta == 0) mbar_arrive(bars + 8 * B_F2DONE);
#pragma unroll
            for (int c = 0; c < 4; c++) st_rlx(&S->ypart[kc][2 * t + (c & 1)][c2 * 64 + p * 16 + (c >> 1) * 8 + g], tagf(acc[c], tag));
            TSC(ta == 0, 23);
            bar_sync(12, 128);
        }
#pragma unroll 1
        for (int j = 2 * p; j < 2 * p + 2; j++) {
            const uint32_t kj = __shfl_sync(0xffffffffu, sel.x, j);
            const int row = 0x7ff - (kj & 0x7ffu), jj = (row >> 1) - j0 - hp * 128;
            float a0 = 0.f, a1 = 0.f, a2 = 0.f, a3 = 0.f, sig = 0.f;
            if ((row & 1) == par && jj >= 0 && jj < 128) {
                sig = bf16r(sigmoidf(__uint_as_float(((int)kj < 0 ? kj ^ 0x80000000u : ~kj) & 0xffff0000u)));
#pragma unroll 1
                for (int hh = 0; hh < 8; hh += 4) {
                    uint4 v[4];
#pragma unroll 1
                    for (int it = 0; it < SPIN_LIMIT; it++) {
#pragma unroll
                        for (int m = 0; m < 4; m++) v[m] = ld_rlx4(&S->ypart[hh + m][j][cb * 128 + lane * 4]);
                        if (!__any_sync(0xffffffffu, (mism(v[0], tag) | mism(v[1], tag) | mism(v[2], tag) | mism(v[3], tag)) & 1)) break;
                    }
#pragma unroll
                    for (int m = 0; m < 4; m++) { a0 += __uint_as_float(v[m].x); a1 += __uint_as_float(v[m].y); a2 += __uint_as_float(v[m].z); a3 += __uint_as_float(v[m].w); }
                }
                asm volatile("st.shared.u8 [%0], %1;" ::"r"(sb + OFF_ROWMAP + jj), "r"(j) : "memory");
            }
            sts2(sb + OFF_FA + (lane >> 1) * 128 + j * 16 + (lane & 1) * 8, pack_bf16(bf16r(a0) * sig, bf16r(a1) * sig), pack_bf16(bf16r(a2) * sig, bf16r(a3) * sig));
        }
        fence_async_smem();
        __syncwarp();
        if (lane == 0) mbar_arrive(bars + 8 * B_UPD);
        TSC(ta == 0, 24);
        TS_END();
    } else {
        if (elect_one()) {
#pragma unroll
            for (int i = 0; i < (B_EMPTY - B_WOFULL) / 8; i++) mbar_init(bars + 8 * (B_WOFULL + 8 * i + warp), 1);
        }
        reg_inc<224>();
        const int w = warp >> 2, wi = warp & 3, tw = (1 - w) * 4 + wi;
        const bool elect = (tid & 127) == 0;
        const uint32_t ln = opaque(lane), g = ln >> 2, t = ln & 3;
        uint32_t tag, ow[8][4];
        auto store_o = [&](int f0, int f1) {
            uint8_t* ob = g_o + (size_t)((mt * 2 + 1 - w) * 2 + 1 - (wi >> 1)) * 131072 + nt * 1024 + (wi & 1) * 512 + ln * 4;
#pragma unroll
            for (int f = f0; f < f1; f++)
#pragma unroll
                for (int i = 3; i >= 0; i--)
                    st_rlx(ob + f * 16384 + i * 128, ow[f][i]);
        };
        {
            float acc[2][96];
            const uint32_t sta = opaque(sb + OFF_STAT + tw * 256 + 64 + g * 8);
            {
                float fa[4] = {0.f, 0.f, 0.f, 0.f};
                uint32_t so = STAGE >> 4, bo = bars, ph = 0;
                const uint32_t dx0 = sd + dlo(w ? 40960 : 0, 16), dw0 = sd + dlo(16384, 8192);
                int p = 0;
                if (w) bar_arrive(1, 256);
                uint32_t fm = fb < 112 ? F1_MASK >> (16 * w) : 0u, fph = 0;
                int fs = w;
#pragma unroll 1
                for (; p < 16; p++) {
                    mbar_wait(bo + 8 * B_FULLA, ph);
                    if (w) mbar_wait(bo + 8 * B_FULLB, ph);
                    TSC(elect && p == 0, 1 + 8 * w);
                    bar_sync(1 + w, 256);
                    TSC(TIMING == 1 && tid == 0, 32 + p);
                    wg_fence();
#pragma unroll
                    for (int k = 0; k < 4; k++) {
                        wgmma_n192<0, 1>(acc[0], mkdesc(dx0 + so + k * 2, dhi(1024, 1)), mkdesc(dw0 + so + k * 128, dhi(1024, 1)), k ? 1 : p);
                        wgmma_n192<0, 1>(acc[1], mkdesc(dx0 + so + 512 + k * 2, dhi(1024, 1)), mkdesc(dw0 + so + k * 128, dhi(1024, 1)), k ? 1 : p);
                    }
                    wg_commit();
                    if (fm & 1) {
                        mbar_wait(bars + 8 * (B_FFULL + fs), fph);
                        wg_fence();
#pragma unroll
                        for (int j = 0; j < 8; j++)
                            wgmma_n8<1, 0>(fa, mkdesc(sd + dlo(OFF_FW, 8192) + fs * 1024 + j * 64, dhi(512, 2)), mkdesc(sd + dlo(OFF_FA, 128) + fs * 128 + j * 16, dhi(128, 0)));
                        wg_commit();
                    } else if (p == 15) {
                        wg_fence();
                        wgmma_n192<0, 1>(acc[0], mkdesc(sd + dlo(OFF_MEAN, 0) + w * 128, dhi(128, 0)), mkdesc(sd + dlo(OFF_CS, 0), dhi(48, 0)));
                        wgmma_n192<0, 1>(acc[1], mkdesc(sd + dlo(OFF_MEAN + 1024, 0) + w * 128, dhi(128, 0)), mkdesc(sd + dlo(OFF_CS, 0), dhi(48, 0)));
                        wg_commit();
                    }
                    bar_arrive(2 - w, 256);
                    wg_wait<0>();
                    if (wi == 0 && elect_one()) { mbar_arrive(bo + 8 * B_EMPTY); if (fm & 1) mbar_arrive(bars + 8 * (B_FEMPTY + fs)); }
                    so = so == 2 * (STAGE >> 4) ? 0 : so + (STAGE >> 4);
                    bo += 8;
                    if (bo == bars + 24) { bo = bars; ph ^= 1; }
                    if (fm & 1) { fs += 2; if (fs >= 3) { fs -= 3; fph ^= 1; } }
                    fm >>= 1;
                    if (p == P_PART) {
                        if (fb < 112) sts4(sb + OFF_FA + tid * 16, __float_as_uint(fa[0]), __float_as_uint(fa[1]), __float_as_uint(fa[2]), __float_as_uint(fa[3]));
                        __syncwarp();
                        if (lane == 0) mbar_arrive(bars + 8 * B_PART);
                    }
                    if (p != 14) continue;
                    mbar_wait(bars + 8 * B_AUX, 0);
                    mbar_wait(bars + 8 * (B_EMPTY + 1), 0);
                    const uint32_t hm = __float_as_uint(0.5f * lds1f(sb + OFF_STAT + 64 + tw * 256 + ln * 8)) >> 16;
                    sts4(sb + OFF_MEAN + w * 2048 + wi * 256 + (ln >> 4) * 1024 + (ln & 15) * 16, hm * 0x10001u, hm, 0, 0);
                    fence_async_smem();
                }
                if (elect) mbar_arrive(bars + 8 * B_G1DONE);
            }
            TSC(elect, 2 + 8 * w);

            tag = lds1(sb + OFF_TAG);
            mbar_wait(bars + 8 * (B_EMPTY + 2), 0);
            uint32_t pk[4][24];
            const uint32_t hm = tw == 7 ? ~ln & 1 : 0;
            auto np = [&](int i, int j) {
                const float* a = &acc[i >> 1][4 * j + 2 * (i & 1)];
                pk[i][j] = pack_bf16(a[0], a[1]);
                if (j >= 16) pk[i][j] = movm(pk[i][j]);
                if (i == 3 && j >= 8 && !(j & 1)) pk[i][j] = tagw(pk[i][j], hm, tag);
            };
            const uint32_t ha = sb + OFF_HALO + tw * 2048 + ln * 8;
#pragma unroll
            for (int j = 8; j < 24; j += 2) {
                np(3, j); np(3, j + 1);
                sts2(ha + 2048 + (j - 8) * 128, pk[3][j], pk[3][j + 1]);
                asm volatile("{\n.reg .pred p;\nsetp.eq.u32 p, %3, 7;\n@p st.relaxed.gpu.global.v2.u32 [%0], {%1,%2};\n}" ::"l"((char*)&S->halo[b][ln * 2] + (j - 8) * 128),
                             "r"(pk[3][j]), "r"(pk[3][j + 1]), "r"(tw) : "memory");
            }
            bar_arrive(4 + tw, 64);
            TSC(TIMING == 8 && ln == 0 && wi == 1, 32 + 8 * w);
            mbar_wait(bars + 8 * B_G1DONE, 0);
            const bool u0 = 2 * t > g, u1 = 2 * t + 1 > g;
            const uint32_t mU = (u0 ? 0xffffu : 0u) | (u1 ? 0xffff0000u : 0u);
            uint2 hl[8];
            float rk[4][2], fq[4][2];
            const float mask = tw == 0 && j0 == 0 ? -INFINITY : 0.f;
#pragma unroll
            for (int hd = 0; hd < 2; hd++) {
#pragma unroll
                for (int jj = 0; jj < 12; jj++) {
                    const int j = (jj >> 2) * 8 + hd * 4 + (jj & 3);
                    np(0, j); np(1, j); np(2, j);
                    if (j < 8) np(3, j);
                }
                float s[2][3][4];
#pragma unroll
                for (int h = 1; h >= 0; h--)
#pragma unroll
                    for (int n = 2; n >= 0; n--) {
                        if (h == 0 && n == 0 && hd == 0) {
                            const uint32_t ka = sb + OFF_STAT + tw * 256 + 4 + t * 16, k0 = opaque(ka + (u0 ? 0 : 64)), k1 = opaque(ka + (u1 ? 8 : 72));
#pragma unroll
                            for (int i = 0; i < 4; i++) {
                                const float rq = lds1f(sta + i * 64 + 4) * (0.17677669529663687f * 1.4426950408889634f);
                                rk[i][0] = lds1f(k0 + i * 64); rk[i][1] = lds1f(k1 + i * 64);
                                fq[i][0] = rq * rk[i][0]; fq[i][1] = rq * rk[i][1];
                            }
                            TSC(TIMING == 8 && ln == 0 && wi == 1 && s[1][0][0] + s[0][1][0] != 123.456f, 33 + 8 * w);
                            bar_sync(3 + tw, 64);
#pragma unroll
                            for (int c = 0; c < 8; c++) hl[c] = lds2(ha + c * 256);
                        }
                        const int kg = 2 * h - 1 + n;
                        s[h][n][0] = s[h][n][1] = kg < 0 ? mask : 0.f; s[h][n][2] = s[h][n][3] = 0.f;
#pragma unroll
                        for (int ks = 0; ks < 2; ks++) {
                            const int q = hd * 4 + 2 * ks;
                            const uint32_t* k = kg < 0 ? &hl[hd * 2 + ks].x : &pk[kg < 0 ? 0 : kg][8 + q];
                            mma16816(s[h][n], pk[2 * h][q], pk[2 * h + 1][q], pk[2 * h][q + 1], pk[2 * h + 1][q + 1], k[0], k[1]);
                        }
                    }
                uint32_t pp[4], pc[4];
#pragma unroll
                for (int i = 0; i < 4; i++) {
                    const float* sp = &s[i >> 1][i & 1][2 * (i & 1)];
                    const float* sc = &s[i >> 1][(i & 1) + 1][2 * (i & 1)];
                    float a0 = (u0 ? sp[0] : sc[0]) * fq[i][0], a1 = (u1 ? sp[1] : sc[1]) * fq[i][1];
                    float m = fmaxf(a0, a1);
                    m = fmaxf(m, __shfl_xor_sync(0xffffffffu, m, 1));
                    m = fmaxf(m, __shfl_xor_sync(0xffffffffu, m, 2));
                    a0 = ex2(a0 - m); a1 = ex2(a1 - m);
                    float sum = a0 + a1;
                    sum += __shfl_xor_sync(0xffffffffu, sum, 1);
                    sum += __shfl_xor_sync(0xffffffffu, sum, 2);
                    const float inv = rcp(sum);
                    const uint32_t pw = pack_bf16(a0 * rk[i][0] * inv, a1 * rk[i][1] * inv);
                    pp[i] = pw & mU; pc[i] = pw & ~mU;
                }
                TSC(TIMING == 8 && ln == 0 && wi == 1 && pp[0] + pp[3] != 0x12345, 34 + 2 * hd + 8 * w);
#pragma unroll
                for (int fh = 0; fh < 2; fh++)
#pragma unroll
                    for (int i = 0; i < 4; i++) {
                        const int v = 16 + hd * 4 + 2 * fh;
                        const uint32_t* vp = i ? &pk[i ? i - 1 : 0][v] : &hl[4 + hd * 2 + fh].x;
                        float o[4] = {0.f, 0.f, 0.f, 0.f};
                        if (i & 1) mma16816(o, vp[0], vp[1], pk[i][v], pk[i][v + 1], pp[i], pc[i]);
                        else { mma1688(o, pk[i][v], pk[i][v + 1], pc[i]); mma1688(o, vp[0], vp[1], pp[i]); }
                        const uint32_t tm = (ln & 7) == (nt & 3) * 2 + (i & 1);
                        ow[hd * 4 + 2 * fh][i] = tagw(pack_bf16(o[0], o[1]), tm, tag); ow[hd * 4 + 2 * fh + 1][i] = tagw(pack_bf16(o[2], o[3]), tm, tag);
                    }
                store_o(hd ? ST_A : 0, hd ? ST_B : ST_A);
                TSC(TIMING == 11 && !hd && ln == 0 && wi == 3, 45 + w);
                mbar_wait(bars + 8 * B_G1DONE, 0);
                if (ln == 0) mbar_arrive(bars + 8 * (hd ? B_ATT : B_AST));
                TSC(elect && hd == 0, 3 + 8 * w);
                TSC(TIMING == 8 && ln == 0 && wi == 1, 35 + 2 * hd + 8 * w);
            }
        }
        TSC(elect, 4 + 8 * w);
        mbar_wait(bars + 8 * B_XR, 0);
        float acc2[64];
        const uint32_t xs = sb + (wi & 1) * 8192 + (tw >> 1) * 2048, mad = xs + (ln & 15) * 128;
        {
            const uint32_t sta = sb + OFF_STAT + (8 + hp * 128 + tw * 16 + g) * 8;
            const float2 s0 = lds2f(sta), s1 = lds2f(sta + 64);
            const float m0 = s0.x * s0.y, r0 = 1.f + s0.y, m1 = s1.x * s1.y, r1 = 1.f + s1.y;
#pragma unroll
            for (int j = 0; j < 16; j += 2) {
                uint32_t a0, a1, a2, a3;
                const int ch = (j & 7) + (ln >> 4);
                asm volatile("ldmatrix.sync.aligned.m8n8.x4.shared.b16 {%0,%1,%2,%3}, [%4];" : "=r"(a0), "=r"(a1), "=r"(a2), "=r"(a3)
                             : "r"(mad + (j >> 3) * STAGE + ((ch ^ (ln & 7)) << 4)) : "memory");
                acc2[4 * j + 0] = fmaf(bf_lo(a0), r0, m0); acc2[4 * j + 1] = fmaf(bf_hi(a0), r0, m0);
                acc2[4 * j + 2] = fmaf(bf_lo(a1), r1, m1); acc2[4 * j + 3] = fmaf(bf_hi(a1), r1, m1);
                acc2[4 * j + 4] = fmaf(bf_lo(a2), r0, m0); acc2[4 * j + 5] = fmaf(bf_hi(a2), r0, m0);
                acc2[4 * j + 6] = fmaf(bf_lo(a3), r1, m1); acc2[4 * j + 7] = fmaf(bf_hi(a3), r1, m1);
            }
        }
        TSC(elect, 5 + 8 * w);
        {
            if (ST_B < ST_C) { mbar_wait(bars + 8 * B_GO, 0); store_o(ST_B, ST_C); }
            mbar_wait(bars + 8 * B_ATT, 0);
            const uint32_t ring = sb + (w ? OFF_O1 : OFF_O0), da0 = (ring >> 4) + dlo(0, 1024);
            const uint32_t chk = ring + wi * 256 + (ln >> 3) * 1032 + (g & 1) * 132 + t * 32;
            uint32_t db = sd + dlo(OFF_WO, 16384);
#pragma unroll 1
            for (int s = 0; s < 8; s++) {
                const uint32_t ro = (s & 1) * 16384;
                mbar_wait(bars + 8 * (B_WOFULL + s), 0);
                TSC(TIMING == 11 && tid == 0 && s == 0, 43);
                mbar_wait(bars + 8 * (B_OFULL + s) + 64 * w, 0);
                TSC(TIMING == 11 && tid == 0 && s == 0, 44);
#pragma unroll 1
                for (int it = 0; __any_sync(0xffffffffu, (mism(lds1(chk + ro), lds1(chk + ro + 4096), tag) | mism(lds1(chk + ro + 8192), lds1(chk + ro + 12288), tag)) & 1) && it < SPIN_LIMIT; it++) {
                    NRETRY();
                    const uint32_t fo = wi * 256 + (ln >> 4) * 1024 + (ln & 15) * 16;
                    uint4 v[8];
#pragma unroll
                    for (int c = 0; c < 8; c++) v[c] = ld_rlx4(g_o + (size_t)(((mt * 2 + hp) * 2 + w) * 8 + s) * 16384 + fo + c * 2048);
#pragma unroll
                    for (int c = 0; c < 8; c++) sts4(ring + ro + fo + c * 2048, v[c].x, v[c].y, v[c].z, v[c].w);
                    fence_async_smem();
                    __syncwarp();
                }
                if (s <= 8 - LAST) bar_sync(1 + w, 256);
                TSC(elect && s == 0, 6 + 8 * w);
                TSC(TIMING == 2 && elect, 32 + 16 * w + s);
                wg_fence();
#pragma unroll
                for (int k = 0; k < 8; k++)
                    wgmma_n128<1, 1>(acc2, mkdesc(da0 + (ro >> 4) + k * 128, dhi(128, 0)), mkdesc(db + k * 128, dhi(1024, 1)));
                wg_commit();
                db = db == sd + dlo(OFF_WO + (NWO - 1) * 32768, 16384) ? sd + dlo(OFF_WO, 16384) : db + 2048;
                if (s < 8 - LAST) {
                    bar_arrive(2 - w, 256);
                    if (s == 0) store_o(ST_C, 8);
                    wg_wait<0>();
                    if (elect) mbar_arrive(bars + 8 * (B_DONE + s) + 64 * w);
                }
            }
            mbar_wait(bars + 8 * B_UPD, 0);
            int sl0, sl1;
            asm volatile("ld.shared.s8 %0, [%1];" : "=r"(sl0) : "r"(sb + OFF_ROWMAP + tw * 16 + g) : "memory");
            asm volatile("ld.shared.s8 %0, [%1];" : "=r"(sl1) : "r"(sb + OFF_ROWMAP + tw * 16 + 8 + g) : "memory");
            const uint32_t e0 = (sl0 >> 1) == (int)t ? 0x3f80u << ((sl0 & 1) * 16) : 0u, e1 = (sl1 >> 1) == (int)t ? 0x3f80u << ((sl1 & 1) * 16) : 0u;
            wg_fence();
            wgmma_rs_n128<1>(acc2, e0, e1, 0u, 0u, mkdesc(sd + dlo(OFF_FA, 0), dhi(128, 0)));
            wg_commit();
            bar_arrive(2 - w, 256);
            wg_wait<0>();
#pragma unroll
            for (int i = 0; i < 64; i++) asm volatile("" : "+f"(acc2[i]) :: "memory");
            TSC(elect, 7 + 8 * w);
#pragma unroll
            for (int j = 0; j < 16; j += 2) {
                const int ch = (j & 7) + (ln >> 4);
                asm volatile("stmatrix.sync.aligned.m8n8.x4.shared.b16 [%0], {%1,%2,%3,%4};" ::"r"(mad + (j >> 3) * STAGE + ((ch ^ (ln & 7)) << 4)),
                             "r"(pack_bf16(acc2[4 * j], acc2[4 * j + 1])), "r"(pack_bf16(acc2[4 * j + 2], acc2[4 * j + 3])),
                             "r"(pack_bf16(acc2[4 * j + 4], acc2[4 * j + 5])), "r"(pack_bf16(acc2[4 * j + 6], acc2[4 * j + 7])) : "memory");
                if ((j & 7) == 6) {
                    fence_async_smem();
                    __syncwarp();
                    if (ln == 0) tma_store_2d(&mout, xs + (j >> 3) * STAGE, par * 1024 + cb * 128 + (j >> 3) * 64, j0 + hp * 128 + tw * 16);
                }
            }
            if (ln == 0) asm volatile("cp.async.bulk.commit_group;\ncp.async.bulk.wait_group.read 0;" ::: "memory");
            TSC(elect, 8 + 8 * w);
            TS_END();
        }
    }
}

typedef CUresult (*EncodeFn)(CUtensorMap*, CUtensorMapDataType, cuuint32_t, void*, const cuuint64_t*, const cuuint64_t*, const cuuint32_t*,
                             const cuuint32_t*, CUtensorMapInterleave, CUtensorMapSwizzle, CUtensorMapL2promotion, CUtensorMapFloatOOBfill);

CUtensorMap make_map(EncodeFn fn, const void* base, int rank, const cuuint64_t* dims, const cuuint64_t* strides, const cuuint32_t* box,
                     CUtensorMapSwizzle swz = CU_TENSOR_MAP_SWIZZLE_128B, CUtensorMapL2promotion pro = CU_TENSOR_MAP_L2_PROMOTION_L2_256B) {
    CUtensorMap m;
    cuuint32_t es[5] = {1, 1, 1, 1, 1};
    fn(&m, CU_TENSOR_MAP_DATA_TYPE_BFLOAT16, rank, (void*)base, dims, strides, box, es, CU_TENSOR_MAP_INTERLEAVE_NONE,
       swz, pro, CU_TENSOR_MAP_FLOAT_OOB_FILL_NONE);
    return m;
}

}

extern "C" void kernel_launch(void* const* d_in, const int* in_sizes, int n_in, void* d_out, int out_size) {
    (void)in_sizes; (void)n_in; (void)out_size;
    const __nv_bfloat16* x = (const __nv_bfloat16*)d_in[0];
    const __nv_bfloat16* wqkv = (const __nv_bfloat16*)d_in[1];
    const char* wo = (const char*)d_in[2];
    const __nv_bfloat16* wr = (const __nv_bfloat16*)d_in[4];
    const char* wg = (const char*)d_in[5];
    const char* wu = (const char*)d_in[6];
    const char* wd = (const char*)d_in[7];
    static EncodeFn fn = nullptr;
    static int by_sm = 0;
    static Scratch* scr = nullptr;
    if (!fn) {
        void* p = nullptr; cudaDriverEntryPointQueryResult q;
        cudaGetDriverEntryPoint("cuTensorMapEncodeTiled", &p, cudaEnableDefault, &q);
        fn = (EncodeFn)p;
        cudaFuncSetAttribute(fused_kernel, cudaFuncAttributeMaxDynamicSharedMemorySize, SMEM_LAUNCH);
        cudaGetSymbolAddress((void**)&scr, g_scr);
        int dev = 0, sms = 0;
        cudaGetDevice(&dev);
        cudaDeviceGetAttribute(&sms, cudaDevAttrMultiProcessorCount, dev);
        by_sm = sms == 132;
    }
    Roles roles;
    for (int i = 0; i < 132; i++) {
        const int T = i >> 1, T8 = T < 32 ? T : T + 1 + (T - 32) / 7, fb = (T < 60 ? (~T8 & 7) * 8 + (T8 >> 3) : T < 62 ? T + 4 : T - 2) * 2 + (i & 1);
        roles.v[i] = fb | ((fb & ~31) | (fb & 1) << 4 | (fb & 31) >> 1) << 8;
    }
    const cuuint64_t xd[4] = {2048, 16, 32, 2}, xs[3] = {4096, 131072, 65536};
    const cuuint32_t xb[4] = {64, 16, 4, 2};
    const cuuint64_t wdm[3] = {1024, 1024, 3}, wst[2] = {6144, 2048};
    const cuuint32_t wb[3] = {64, 64, 3};
    const cuuint64_t od[4] = {64, 64, 16, 16}, ost[3] = {2048, 131072, 128};
    const cuuint32_t ob[4] = {64, 8, 16, 2};
    const cuuint64_t yd[2] = {2048, 1024}, yst[1] = {4096};
    const cuuint32_t yb[2] = {64, 16};
    const cuuint64_t sd[3] = {64, 1024, 32}, sst[2] = {4096, 128};
    const cuuint32_t sbx[3] = {64, 16, 4};
    CUtensorMap mxs = make_map(fn, x, 3, sd, sst, sbx);
    const cuuint64_t cd[3] = {3072, 64, 16}, cst[2] = {6144, 393216};
    const cuuint32_t cbx[3] = {64, 8, 2};
    CUtensorMap mcs = make_map(fn, wqkv, 3, cd, cst, cbx, CU_TENSOR_MAP_SWIZZLE_NONE);
    CUtensorMap mx = make_map(fn, x, 4, xd, xs, xb), mw = make_map(fn, wqkv, 3, wdm, wst, wb);
    CUtensorMap mwo = make_map(fn, wo, 4, od, ost, ob), mout = make_map(fn, d_out, 2, yd, yst, yb);
    const cuuint64_t gd[3] = {3584, 1024, 2}, gst[2] = {7168, (cuuint64_t)(wu < wg ? wg - wu : wu - wg)};
    const cuuint32_t gb[3] = {32, 128, 2};
    const cuuint64_t dd[2] = {1024, 3584}, dst[1] = {2048};
    const cuuint32_t db[2] = {64, 64};
    CUtensorMap mgu = make_map(fn, wu < wg ? wu : wg, 3, gd, gst, gb, CU_TENSOR_MAP_SWIZZLE_64B, CU_TENSOR_MAP_L2_PROMOTION_L2_128B);
    CUtensorMap mwd = make_map(fn, wd, 2, dd, dst, db, CU_TENSOR_MAP_SWIZZLE_128B, CU_TENSOR_MAP_L2_PROMOTION_L2_128B);
    fused_kernel<<<132, 512, SMEM_LAUNCH, cudaStreamPerThread>>>(by_sm, x, wqkv, wr, scr, wg, wu, wd, wo, roles, mw, mx, mwo, mxs, mcs, mout, mgu, mwd);
}
```

```cpp
#include <cuda_runtime.h>
#include <cuda.h>
#include <cuda_bf16.h>
#include <stdint.h>

namespace {

constexpr int STAGE = 57344;
constexpr int OFF_FW = 3 * STAGE;
constexpr int OFF_FA = OFF_FW + 49152;
constexpr int OFF_CS = OFF_FA + 6144;
constexpr int OFF_STAT = OFF_CS + 1232;
constexpr int OFF_ROWMAP = OFF_STAT + 2112;
constexpr int OFF_TAG = OFF_ROWMAP + 128;
constexpr int OFF_BAR = OFF_TAG + 8;
constexpr int OFF_F2X = 16384, OFF_HALO = 24576, OFF_O1 = 24576, OFF_O0 = 73728, OFF_WO = 106496, NWO = 3, OFF_MEAN = 2 * STAGE, OFF_X1 = 2 * STAGE + 8192;
static_assert(OFF_WO + NWO * 32768 <= OFF_FA && OFF_O0 + 32768 == OFF_WO && OFF_O1 + 32768 == STAGE, "alias");
constexpr int B_FULLA = 0, B_FULLB = 3, B_ROW = 6, B_FFULL = 11, B_FEMPTY = 14, B_F2DONE = 17, B_GO = 18, B_SW = 19, B_CS = 20, B_WOFULL = 26, B_OFULL = B_WOFULL + 8,
              B_DONE = B_OFULL + 16;
constexpr int B_EMPTY = B_DONE + 16, B_XR = B_EMPTY + 3, B_G1DONE = B_XR + 1;
constexpr int B_UPD = B_G1DONE + 1, B_F2FULL = B_UPD + 1;
constexpr int B_AUX = B_F2FULL + 1, B_PART = B_AUX + 1, B_ATT = B_PART + 1, B_CSDONE = B_ATT + 1, B_AST = B_CSDONE + 1, NBAR = B_AST + 1;
constexpr int SMEM_BYTES = OFF_BAR + NBAR * 8;
static_assert(SMEM_BYTES <= 232448 && OFF_BAR % 8 == 0, "smem");
#define P_PART 13
#define F1_MASK (0x6a005a00u >> (14 - P_PART))
#define PF_CNT 0x2aaaaacu
#define EARLY_FILL 2
#define N_S1 1
#define N_S2 3
#define ST_A 2
#define ST_B 4
#define DBG_F2 1
#define DBG_F1 1
#define DBG_XR 1
#define T_H 250
#define T_O1 250
#define WO1_GATE B_GO
#define ST_C 5
#define T_O 2050
#define T_S1 128
#define T_GO 256
#define T_S2 950
#define DBG_CS 0
#define DBG_ST 0
#define N_GA 4
#define N_X 1
#define D_X 2
#define D_R 3
#define N_ROW 5
#define N_W 5
#define K_W1 5
#define K_W2 10
#define N_CS 3
#define N_F1 4
#define LAST 2
#define POLL_NS 100
#define STATS_UNROLL 4
constexpr int kStatsUnroll = STATS_UNROLL;
constexpr int SPIN_LIMIT = 1 << 18;

struct Scratch {
    uint8_t o[2048 * 1024 * 2];
    uint2 rec[2048];
    float cs[8][3072];
    uint32_t halo[128][512];
    uint32_t h[14336];
    float ypart[8][8][1024];
    uint2 sel[16];
    uint32_t hint[128][8];
    uint32_t epoch;
};
__device__ __align__(1024) Scratch g_scr;

#define TS(i) do {} while (0)
#define TS_END() do {} while (0)
constexpr int SMEM_LAUNCH = SMEM_BYTES;
#define TSC(c, i) do {} while (0)
#define NRETRY() do {} while (0)
__device__ __forceinline__ uint32_t smem_u32(const void* p) { return (uint32_t)__cvta_generic_to_shared(p); }
__device__ __forceinline__ void mbar_init(uint32_t bar, uint32_t cnt) { asm volatile("mbarrier.init.shared::cta.b64 [%0], %1;" ::"r"(bar), "r"(cnt) : "memory"); }
__device__ __forceinline__ void mbar_expect_tx(uint32_t bar, uint32_t bytes) { asm volatile("mbarrier.arrive.expect_tx.shared::cta.b64 _, [%0], %1;" ::"r"(bar), "r"(bytes) : "memory"); }
__device__ __forceinline__ void mbar_arrive(uint32_t bar) { asm volatile("mbarrier.arrive.shared::cta.b64 _, [%0];" ::"r"(bar) : "memory"); }
__device__ __forceinline__ void mbar_arrive_after(uint32_t bar, uint32_t lane, uint32_t dep) {
    asm volatile("{\n.reg .pred p;\n.reg .b32 t;\nsetp.eq.u32 p, %1, 0;\nmad.lo.u32 t, %1, %2, %0;\n@p mbarrier.arrive.shared::cta.b64 _, [t];\n}" ::"r"(bar), "r"(lane), "r"(dep) : "memory");
}
__device__ __forceinline__ void mbar_wait(uint32_t bar, uint32_t parity) {
    asm volatile("{\n.reg .pred P1;\nLAB_WAIT:\nmbarrier.try_wait.parity.shared::cta.b64 P1, [%0], %1;\n@!P1 bra LAB_WAIT;\n}" ::"r"(bar), "r"(parity) : "memory");
}
__device__ __forceinline__ bool mbar_test(uint32_t bar, uint32_t parity) {
    uint32_t ok;
    asm volatile("{\n.reg .pred p;\nmbarrier.test_wait.parity.shared::cta.b64 p, [%1], %2;\nselp.u32 %0, 1, 0, p;\n}" : "=r"(ok) : "r"(bar), "r"(parity) : "memory");
    return ok;
}
__device__ __forceinline__ void tma_2d(uint32_t dst, const CUtensorMap* m, uint32_t bar, int c0, int c1) {
    asm volatile("cp.async.bulk.tensor.2d.shared::cluster.global.mbarrier::complete_tx::bytes [%0], [%1, {%3, %4}], [%2];" ::"r"(dst), "l"(m), "r"(bar), "r"(c0), "r"(c1) : "memory");
}
__device__ __forceinline__ void tma_3d(uint32_t dst, const CUtensorMap* m, uint32_t bar, int c0, int c1, int c2) {
    asm volatile("cp.async.bulk.tensor.3d.shared::cluster.global.mbarrier::complete_tx::bytes [%0], [%1, {%3, %4, %5}], [%2];" ::"r"(dst), "l"(m), "r"(bar), "r"(c0), "r"(c1), "r"(c2) : "memory");
}
__device__ __forceinline__ void tma_4d(uint32_t dst, const CUtensorMap* m, uint32_t bar, int c0, int c1, int c2, int c3) {
    asm volatile("cp.async.bulk.tensor.4d.shared::cluster.global.mbarrier::complete_tx::bytes [%0], [%1, {%3, %4, %5, %6}], [%2];" ::"r"(dst), "l"(m), "r"(bar), "r"(c0), "r"(c1), "r"(c2), "r"(c3) : "memory");
}
__device__ __forceinline__ void tma_store_2d(const CUtensorMap* m, uint32_t src, int c0, int c1) {
    asm volatile("cp.async.bulk.tensor.2d.global.shared::cta.bulk_group [%0, {%2, %3}], [%1];" ::"l"(m), "r"(src), "r"(c0), "r"(c1) : "memory");
}
__device__ __forceinline__ void bulk_g2s(uint32_t dst, const void* src, uint32_t bytes, uint32_t bar) {
    asm volatile("cp.async.bulk.shared::cluster.global.mbarrier::complete_tx::bytes [%0], [%1], %2, [%3];" ::"r"(dst), "l"(src), "r"(bytes), "r"(bar) : "memory");
}
__device__ __forceinline__ void bulk_prefetch(const void* p, uint32_t bytes) { asm volatile("cp.async.bulk.prefetch.L2.global [%0], %1;" ::"l"(p), "r"(bytes) : "memory"); }
__device__ __forceinline__ void fence_async_smem() { asm volatile("fence.proxy.async.shared::cta;" ::: "memory"); }
__device__ __forceinline__ void wg_fence() { asm volatile("wgmma.fence.sync.aligned;" ::: "memory"); }
__device__ __forceinline__ void wg_commit() { asm volatile("wgmma.commit_group.sync.aligned;" ::: "memory"); }
template <int N> __device__ __forceinline__ void wg_wait() { asm volatile("wgmma.wait_group.sync.aligned %0;" ::"n"(N) : "memory"); }
__device__ __forceinline__ uint64_t mkdesc(uint32_t lo, uint32_t hi) { return ((uint64_t)hi << 32) | lo; }
__host__ __device__ constexpr uint32_t dhi(uint32_t sbo, uint32_t mode) { return (sbo >> 4) | (mode << 30); }
__host__ __device__ constexpr uint32_t dlo(uint32_t off, uint32_t lbo) { return (off >> 4) + ((lbo >> 4) << 16); }
__device__ __forceinline__ bool elect_one() {
    uint32_t e;
    asm volatile("{\n.reg .pred p;\nelect.sync _|p, 0xffffffff;\nselp.u32 %0, 1, 0, p;\n}" : "=r"(e));
    return e;
}
template <int R> __device__ __forceinline__ void reg_inc() { asm volatile("setmaxnreg.inc.sync.aligned.u32 %0;" ::"n"(R)); }
template <int R> __device__ __forceinline__ void reg_dec() { asm volatile("setmaxnreg.dec.sync.aligned.u32 %0;" ::"n"(R)); }
__device__ __forceinline__ void bar_sync(int id, int n) { asm volatile("bar.sync %0, %1;" ::"r"(id), "r"(n) : "memory"); }
__device__ __forceinline__ void bar_arrive(int id, int n) { asm volatile("bar.arrive %0, %1;" ::"r"(id), "r"(n) : "memory"); }
__device__ __forceinline__ uint32_t pack_bf16(float lo, float hi) { uint32_t r; asm("cvt.rn.bf16x2.f32 %0, %1, %2;" : "=r"(r) : "f"(hi), "f"(lo)); return r; }
__device__ __forceinline__ float bf_lo(uint32_t u) { return __uint_as_float(u << 16); }
__device__ __forceinline__ float bf_hi(uint32_t u) { return __uint_as_float(u & 0xffff0000u); }
__device__ __forceinline__ float bf16r(float v) { return bf_lo(pack_bf16(v, 0.f)); }
__device__ __forceinline__ uint32_t tagw(uint32_t w, uint32_t m, uint32_t tag) { uint32_t r; asm("lop3.b32 %0, %1, %2, %3, 0xb8;" : "=r"(r) : "r"(w), "r"(m), "r"(tag)); return r; }
__device__ __forceinline__ uint32_t tagf(float f, uint32_t tag) { return tagw(__float_as_uint(f), 1u, tag); }
__device__ __forceinline__ uint32_t movm(uint32_t a) { uint32_t d; asm volatile("movmatrix.sync.aligned.m8n8.trans.b16 %0, %1;" : "=r"(d) : "r"(a)); return d; }
__device__ __forceinline__ void mma16816(float (&c)[4], uint32_t a0, uint32_t a1, uint32_t a2, uint32_t a3, uint32_t b0, uint32_t b1) {
    asm volatile("mma.sync.aligned.m16n8k16.row.col.f32.bf16.bf16.f32 {%0,%1,%2,%3}, {%4,%5,%6,%7}, {%8,%9}, {%0,%1,%2,%3};"
                 : "+f"(c[0]), "+f"(c[1]), "+f"(c[2]), "+f"(c[3]) : "r"(a0), "r"(a1), "r"(a2), "r"(a3), "r"(b0), "r"(b1));
}
__device__ __forceinline__ void mma1688(float (&c)[4], uint32_t a0, uint32_t a1, uint32_t b0) {
    asm volatile("mma.sync.aligned.m16n8k8.row.col.f32.bf16.bf16.f32 {%0,%1,%2,%3}, {%4,%5}, {%6}, {%0,%1,%2,%3};"
                 : "+f"(c[0]), "+f"(c[1]), "+f"(c[2]), "+f"(c[3]) : "r"(a0), "r"(a1), "r"(b0));
}
__device__ __forceinline__ uint32_t ld_rlx(const void* p) { uint32_t v; asm volatile("ld.relaxed.gpu.global.u32 %0, [%1];" : "=r"(v) : "l"(p) : "memory"); return v; }
__device__ __forceinline__ uint2 ld_rlx2(const void* p) { uint2 v; asm volatile("ld.relaxed.gpu.global.v2.u32 {%0,%1}, [%2];" : "=r"(v.x), "=r"(v.y) : "l"(p) : "memory"); return v; }
__device__ __forceinline__ uint4 ld_rlx4(const void* p) { uint4 v; asm volatile("ld.relaxed.gpu.global.v4.u32 {%0,%1,%2,%3}, [%4];" : "=r"(v.x), "=r"(v.y), "=r"(v.z), "=r"(v.w) : "l"(p) : "memory"); return v; }
__device__ __forceinline__ uint32_t ld_acq(const void* p) { uint32_t v; asm volatile("ld.acquire.gpu.global.u32 %0, [%1];" : "=r"(v) : "l"(p) : "memory"); return v; }
__device__ __forceinline__ void st_rlx(void* p, uint32_t v) { asm volatile("st.relaxed.gpu.global.u32 [%0], %1;" ::"l"(p), "r"(v) : "memory"); }
__device__ __forceinline__ void st_rlx2(void* p, uint32_t a, uint32_t b) { asm volatile("st.relaxed.gpu.global.v2.u32 [%0], {%1,%2};" ::"l"(p), "r"(a), "r"(b) : "memory"); }
__device__ __forceinline__ void st_rlx4(void* p, uint32_t a, uint32_t b, uint32_t c, uint32_t d) { asm volatile("st.relaxed.gpu.global.v4.u32 [%0], {%1,%2,%3,%4};" ::"l"(p), "r"(a), "r"(b), "r"(c), "r"(d) : "memory"); }
__device__ __forceinline__ uint4 ldg_nc(const void* p) { uint4 v; asm volatile("ld.global.nc.v4.u32 {%0,%1,%2,%3}, [%4];" : "=r"(v.x), "=r"(v.y), "=r"(v.z), "=r"(v.w) : "l"(p)); return v; }
__device__ __forceinline__ uint32_t mism(uint32_t a, uint32_t b, uint32_t tag) { uint32_t r; asm("lop3.b32 %0, %1, %2, %3, 0x7e;" : "=r"(r) : "r"(a), "r"(b), "r"(tag)); return r; }
__device__ __forceinline__ uint32_t mism(const uint4& v, uint32_t tag) { return mism(v.x, v.y, tag) | mism(v.z, v.w, tag); }
__device__ __forceinline__ void prefetch_l2(const void* p) { asm volatile("prefetch.global.L2 [%0];" ::"l"(p)); }
__device__ __forceinline__ void touch256(uint32_t dst, const void* p) { asm volatile("cp.async.ca.shared.global.L2::256B [%0], [%1], 4;" ::"r"(dst), "l"(p) : "memory"); }
__device__ __forceinline__ void nap(int n) {
#pragma unroll 1
    for (int i = 0; i < n; i++) __nanosleep(100);
}
__device__ __forceinline__ uint32_t now() { uint32_t t; asm volatile("mov.u32 %0, %%globaltimer_lo;" : "=r"(t)); return t; }
__device__ __forceinline__ void until(uint32_t t) {
    while (t - now() - 1 < 16384u) __nanosleep(50);
}
__device__ __forceinline__ uint32_t opaque(uint32_t v) { return __shfl_xor_sync(0xffffffffu, v, 0); }
__device__ __forceinline__ void sts4(uint32_t a, uint32_t x, uint32_t y, uint32_t z, uint32_t w) { asm volatile("st.shared.v4.u32 [%0], {%1,%2,%3,%4};" ::"r"(a), "r"(x), "r"(y), "r"(z), "r"(w) : "memory"); }
__device__ __forceinline__ void sts2(uint32_t a, uint32_t x, uint32_t y) { asm volatile("st.shared.v2.u32 [%0], {%1,%2};" ::"r"(a), "r"(x), "r"(y) : "memory"); }
__device__ __forceinline__ uint4 lds4(uint32_t a) { uint4 v; asm volatile("ld.shared.v4.u32 {%0,%1,%2,%3}, [%4];" : "=r"(v.x), "=r"(v.y), "=r"(v.z), "=r"(v.w) : "r"(a) : "memory"); return v; }
__device__ __forceinline__ float4 lds4f(uint32_t a) { float4 v; asm volatile("ld.shared.v4.f32 {%0,%1,%2,%3}, [%4];" : "=f"(v.x), "=f"(v.y), "=f"(v.z), "=f"(v.w) : "r"(a) : "memory"); return v; }
__device__ __forceinline__ uint2 lds2(uint32_t a) { uint2 v; asm volatile("ld.shared.v2.u32 {%0,%1}, [%2];" : "=r"(v.x), "=r"(v.y) : "r"(a) : "memory"); return v; }
__device__ __forceinline__ float2 lds2f(uint32_t a) { float2 v; asm volatile("ld.shared.v2.f32 {%0,%1}, [%2];" : "=f"(v.x), "=f"(v.y) : "r"(a) : "memory"); return v; }
__device__ __forceinline__ uint32_t lds1(uint32_t a) { uint32_t v; asm volatile("ld.shared.u32 %0, [%1];" : "=r"(v) : "r"(a) : "memory"); return v; }
__device__ __forceinline__ float lds1f(uint32_t a) { return __uint_as_float(lds1(a)); }
__device__ __forceinline__ void sts1(uint32_t a, uint32_t v) { asm volatile("st.shared.u32 [%0], %1;" ::"r"(a), "r"(v) : "memory"); }
__device__ __forceinline__ uint32_t redux_max(uint32_t v) { uint32_t r; asm volatile("redux.sync.max.u32 %0, %1, 0xffffffff;" : "=r"(r) : "r"(v)); return r; }
__device__ __forceinline__ float ex2(float x) { float r; asm("ex2.approx.ftz.f32 %0, %1;" : "=f"(r) : "f"(x)); return r; }
__device__ __forceinline__ float rcp(float x) { float r; asm("rcp.approx.ftz.f32 %0, %1;" : "=f"(r) : "f"(x)); return r; }
__device__ __forceinline__ float sigmoidf(float v) { return rcp(1.f + ex2(v * -1.4426950408889634f)); }

template <int TA, int TB>
__device__ __forceinline__ void wgmma_n192(float (&d)[96], uint64_t da, uint64_t db, int acc = 1) {
    asm volatile("{\n.reg .pred p;\nsetp.ne.b32 p, %100, 0;\n"
        "wgmma.mma_async.sync.aligned.m64n192k16.f32.bf16.bf16 "
        "{%0, %1, %2, %3, %4, %5, %6, %7, %8, %9, %10, %11, %12, %13, %14, %15, "
        "%16, %17, %18, %19, %20, %21, %22, %23, %24, %25, %26, %27, %28, %29, %30, %31, "
        "%32, %33, %34, %35, %36, %37, %38, %39, %40, %41, %42, %43, %44, %45, %46, %47, "
        "%48, %49, %50, %51, %52, %53, %54, %55, %56, %57, %58, %59, %60, %61, %62, %63, "
        "%64, %65, %66, %67, %68, %69, %70, %71, %72, %73, %74, %75, %76, %77, %78, %79, "
        "%80, %81, %82, %83, %84, %85, %86, %87, %88, %89, %90, %91, %92, %93, %94, %95}, "
        "%96, %97, p, 1, 1, %98, %99;\n}\n"
        : "+f"(d[0]), "+f"(d[1]), "+f"(d[2]), "+f"(d[3]), "+f"(d[4]), "+f"(d[5]), "+f"(d[6]), "+f"(d[7]),
          "+f"(d[8]), "+f"(d[9]), "+f"(d[10]), "+f"(d[11]), "+f"(d[12]), "+f"(d[13]), "+f"(d[14]), "+f"(d[15]),
          "+f"(d[16]), "+f"(d[17]), "+f"(d[18]), "+f"(d[19]), "+f"(d[20]), "+f"(d[21]), "+f"(d[22]), "+f"(d[23]),
          "+f"(d[24]), "+f"(d[25]), "+f"(d[26]), "+f"(d[27]), "+f"(d[28]), "+f"(d[29]), "+f"(d[30]), "+f"(d[31]),
          "+f"(d[32]), "+f"(d[33]), "+f"(d[34]), "+f"(d[35]), "+f"(d[36]), "+f"(d[37]), "+f"(d[38]), "+f"(d[39]),
          "+f"(d[40]), "+f"(d[41]), "+f"(d[42]), "+f"(d[43]), "+f"(d[44]), "+f"(d[45]), "+f"(d[46]), "+f"(d[47]),
          "+f"(d[48]), "+f"(d[49]), "+f"(d[50]), "+f"(d[51]), "+f"(d[52]), "+f"(d[53]), "+f"(d[54]), "+f"(d[55]),
          "+f"(d[56]), "+f"(d[57]), "+f"(d[58]), "+f"(d[59]), "+f"(d[60]), "+f"(d[61]), "+f"(d[62]), "+f"(d[63]),
          "+f"(d[64]), "+f"(d[65]), "+f"(d[66]), "+f"(d[67]), "+f"(d[68]), "+f"(d[69]), "+f"(d[70]), "+f"(d[71]),
          "+f"(d[72]), "+f"(d[73]), "+f"(d[74]), "+f"(d[75]), "+f"(d[76]), "+f"(d[77]), "+f"(d[78]), "+f"(d[79]),
          "+f"(d[80]), "+f"(d[81]), "+f"(d[82]), "+f"(d[83]), "+f"(d[84]), "+f"(d[85]), "+f"(d[86]), "+f"(d[87]),
          "+f"(d[88]), "+f"(d[89]), "+f"(d[90]), "+f"(d[91]), "+f"(d[92]), "+f"(d[93]), "+f"(d[94]), "+f"(d[95])
        : "l"(da), "l"(db), "n"(TA), "n"(TB), "r"(acc));
}
template <int TA, int TB>
__device__ __forceinline__ void wgmma_n128(float (&d)[64], uint64_t da, uint64_t db, int acc = 1) {
    asm volatile("{\n.reg .pred p;\nsetp.ne.b32 p, %68, 0;\n"
        "wgmma.mma_async.sync.aligned.m64n128k16.f32.bf16.bf16 "
        "{%0, %1, %2, %3, %4, %5, %6, %7, %8, %9, %10, %11, %12, %13, %14, %15, "
        "%16, %17, %18, %19, %20, %21, %22, %23, %24, %25, %26, %27, %28, %29, %30, %31, "
        "%32, %33, %34, %35, %36, %37, %38, %39, %40, %41, %42, %43, %44, %45, %46, %47, "
        "%48, %49, %50, %51, %52, %53, %54, %55, %56, %57, %58, %59, %60, %61, %62, %63}, "
        "%64, %65, p, 1, 1, %66, %67;\n}\n"
        : "+f"(d[0]), "+f"(d[1]), "+f"(d[2]), "+f"(d[3]), "+f"(d[4]), "+f"(d[5]), "+f"(d[6]), "+f"(d[7]),
          "+f"(d[8]), "+f"(d[9]), "+f"(d[10]), "+f"(d[11]), "+f"(d[12]), "+f"(d[13]), "+f"(d[14]), "+f"(d[15]),
          "+f"(d[16]), "+f"(d[17]), "+f"(d[18]), "+f"(d[19]), "+f"(d[20]), "+f"(d[21]), "+f"(d[22]), "+f"(d[23]),
          "+f"(d[24]), "+f"(d[25]), "+f"(d[26]), "+f"(d[27]), "+f"(d[28]), "+f"(d[29]), "+f"(d[30]), "+f"(d[31]),
          "+f"(d[32]), "+f"(d[33]), "+f"(d[34]), "+f"(d[35]), "+f"(d[36]), "+f"(d[37]), "+f"(d[38]), "+f"(d[39]),
          "+f"(d[40]), "+f"(d[41]), "+f"(d[42]), "+f"(d[43]), "+f"(d[44]), "+f"(d[45]), "+f"(d[46]), "+f"(d[47]),
          "+f"(d[48]), "+f"(d[49]), "+f"(d[50]), "+f"(d[51]), "+f"(d[52]), "+f"(d[53]), "+f"(d[54]), "+f"(d[55]),
          "+f"(d[56]), "+f"(d[57]), "+f"(d[58]), "+f"(d[59]), "+f"(d[60]), "+f"(d[61]), "+f"(d[62]), "+f"(d[63])
        : "l"(da), "l"(db), "n"(TA), "n"(TB), "r"(acc));
}
template <int TB>
__device__ __forceinline__ void wgmma_rs_n128(float (&d)[64], uint32_t a0, uint32_t a1, uint32_t a2, uint32_t a3, uint64_t db) {
    asm volatile("{\n.reg .pred p;\nsetp.ne.b32 p, 1, 0;\n"
        "wgmma.mma_async.sync.aligned.m64n128k16.f32.bf16.bf16 "
        "{%0, %1, %2, %3, %4, %5, %6, %7, %8, %9, %10, %11, %12, %13, %14, %15, "
        "%16, %17, %18, %19, %20, %21, %22, %23, %24, %25, %26, %27, %28, %29, %30, %31, "
        "%32, %33, %34, %35, %36, %37, %38, %39, %40, %41, %42, %43, %44, %45, %46, %47, "
        "%48, %49, %50, %51, %52, %53, %54, %55, %56, %57, %58, %59, %60, %61, %62, %63}, "
        "{%64, %65, %66, %67}, %68, p, 1, 1, %69;\n}\n"
        : "+f"(d[0]), "+f"(d[1]), "+f"(d[2]), "+f"(d[3]), "+f"(d[4]), "+f"(d[5]), "+f"(d[6]), "+f"(d[7]),
          "+f"(d[8]), "+f"(d[9]), "+f"(d[10]), "+f"(d[11]), "+f"(d[12]), "+f"(d[13]), "+f"(d[14]), "+f"(d[15]),
          "+f"(d[16]), "+f"(d[17]), "+f"(d[18]), "+f"(d[19]), "+f"(d[20]), "+f"(d[21]), "+f"(d[22]), "+f"(d[23]),
          "+f"(d[24]), "+f"(d[25]), "+f"(d[26]), "+f"(d[27]), "+f"(d[28]), "+f"(d[29]), "+f"(d[30]), "+f"(d[31]),
          "+f"(d[32]), "+f"(d[33]), "+f"(d[34]), "+f"(d[35]), "+f"(d[36]), "+f"(d[37]), "+f"(d[38]), "+f"(d[39]),
          "+f"(d[40]), "+f"(d[41]), "+f"(d[42]), "+f"(d[43]), "+f"(d[44]), "+f"(d[45]), "+f"(d[46]), "+f"(d[47]),
          "+f"(d[48]), "+f"(d[49]), "+f"(d[50]), "+f"(d[51]), "+f"(d[52]), "+f"(d[53]), "+f"(d[54]), "+f"(d[55]),
          "+f"(d[56]), "+f"(d[57]), "+f"(d[58]), "+f"(d[59]), "+f"(d[60]), "+f"(d[61]), "+f"(d[62]), "+f"(d[63])
        : "r"(a0), "r"(a1), "r"(a2), "r"(a3), "l"(db), "n"(TB));
}
template <int TA, int TB>
__device__ __forceinline__ void wgmma_n8(float (&d)[4], uint64_t da, uint64_t db, int acc = 1) {
    asm volatile("{\n.reg .pred p;\nsetp.ne.b32 p, %8, 0;\n"
        "wgmma.mma_async.sync.aligned.m64n8k16.f32.bf16.bf16 "
        "{%0, %1, %2, %3}, "
        "%4, %5, p, 1, 1, %6, %7;\n}\n"
        : "+f"(d[0]), "+f"(d[1]), "+f"(d[2]), "+f"(d[3])
        : "l"(da), "l"(db), "n"(TA), "n"(TB), "r"(acc));
}

__device__ __forceinline__ uint32_t norm_pair(uint32_t u, float m, float rinv) {
    uint32_t d = pack_bf16(bf_lo(u) - m, bf_hi(u) - m);
    return pack_bf16(bf_lo(d) * rinv, bf_hi(d) * rinv);
}

struct Roles { uint16_t v[132]; };

__global__ void __launch_bounds__(512, 1)
fused_kernel(int by_sm, const __nv_bfloat16* __restrict__ x, const __nv_bfloat16* __restrict__ wqkv, const __nv_bfloat16* __restrict__ wr,
             Scratch* const S, const char* __restrict__ wg, const char* __restrict__ wu, const char* __restrict__ wd, const char* __restrict__ wo,
             const __grid_constant__ Roles roles,
             const __grid_constant__ CUtensorMap mw, const __grid_constant__ CUtensorMap mx, const __grid_constant__ CUtensorMap mwo,
             const __grid_constant__ CUtensorMap mxs, const __grid_constant__ CUtensorMap mcs, const __grid_constant__ CUtensorMap mout, const __grid_constant__ CUtensorMap mgu, const __grid_constant__ CUtensorMap mwd) {
    extern __shared__ __align__(1024) uint8_t smem[];
    constexpr uint32_t sb = 1024, bars = sb + OFF_BAR, sd = sb >> 4;
    const int tid = threadIdx.x, lane = tid & 31;
    asm volatile("{\n.reg .pred p, q;\nsetp.lt.u32 p, %2, 16;\nsetp.lt.u32 q, %2, 24;\n@p prefetch.global.L2 [%0];\n@p prefetch.global.L2 [%0 + 128];\n@q prefetch.global.L2 [%1];\n}" ::
                 "l"((const char*)x + (blockIdx.x * 16 + tid - 32) % 2048 * 2048), "l"((const char*)wqkv + (blockIdx.x * 24 + tid - 32) * 128), "r"(tid - 32));
    const int warp = __shfl_sync(0xffffffffu, tid >> 5, 0);
    uint32_t smid;
    asm volatile("mov.u32 %0, %%smid;" : "=r"(smid));
    const int role = roles.v[by_sm ? smid : blockIdx.x], fb = role & 255, b = role >> 8, kc = fb >> 4, c2 = fb & 15;
    const int mt = b >> 4, nt = b & 15, hp = b & 1, cb = nt >> 1;
    const int par = mt >> 2, j0 = (mt & 3) * 256;
    uint8_t* const g_o = S->o;

    auto load_stage = [&](int p, uint32_t so, int bi) {
        const uint32_t fullA = bars + 8 * (B_FULLA + bi), fullB = bars + 8 * (B_FULLB + bi);
        mbar_expect_tx(fullA, 40960);
        tma_3d(sb + so + 16384, &mw, fullA, nt * 64, p * 64, 0);
        tma_4d(sb + so, &mx, fullA, par * 1024 + p * 64, 0, (j0 >> 5) + 4, 0);
        mbar_expect_tx(fullB, 16384);
        tma_4d(sb + so + 40960, &mx, fullB, par * 1024 + p * 64, 0, j0 >> 5, 0);
    };
    if (warp == 0 && fb < 128 && elect_one()) {
        mbar_init(bars + 8 * B_FULLA, 1); mbar_init(bars + 8 * B_FULLB, 1);
        load_stage(0, STAGE, 0);
    }
    if (fb >= 128) {
        if (fb > 128) { nap(16); TS_END(); return; }
        const uint32_t tag = (ld_rlx(&S->epoch) & 1) - 1;
        if (tid < 8) st_rlx2(&S->sel[tid], ~tag, ~tag);
        uint4 ra, rb;
#pragma unroll 1
        for (int it = 0; it < SPIN_LIMIT; it++) {
            ra = ld_rlx4(&S->rec[tid * 2]); rb = ld_rlx4(&S->rec[1024 + tid * 2]);
            if (!__any_sync(0xffffffffu, (mism(ra.x, ra.z, tag) | mism(rb.x, rb.z, tag)) & 0x8000u)) break;
        }
        __syncwarp();
        TSC(tid == 0, 31);
        sts4(sb + 1024 + tid * 16, ra.y, rb.y, ra.w, rb.w);
        uint4 k = make_uint4(ra.x, ra.z, rb.x, rb.z);
        uint32_t cand;
#pragma unroll 1
        for (int pass = 0; pass < 2; pass++) {
            const uint32_t a0 = max(k.x, k.y), a1 = min(k.x, k.y), a2 = max(k.z, k.w), a3 = min(k.z, k.w), c1 = min(a0, a2), c2 = max(a1, a3);
            k = make_uint4(max(a0, a2), max(c1, c2), min(c1, c2), min(a1, a3));
#pragma unroll
            for (int r = 0; r < 8; r++) {
                const uint32_t m = redux_max(k.x);
                if (lane == r) cand = m;
                if (k.x == m) k = make_uint4(k.y, k.z, k.w, 0);
            }
            if (pass) break;
            if (lane < 8) sts1(sb + (warp * 8 + lane) * 4, cand);
            __syncthreads();
            if (warp) { TS_END(); return; }
            k = lds4(sb + lane * 16);
            TSC(TIMING == 12 && tid == 0 && k.x != 0x12345, 40);
        }
        if (lane < 8) st_rlx2(&S->sel[lane], cand, lds1(sb + 1024 + (~cand & 0x7ffu) * 4));
        TSC(tid == 0, 20);
        TS_END();
        return;
    }
    uint32_t epoch;
    if (warp >> 2 == 2) epoch = ld_rlx(&S->epoch);
    if (warp == 1 && elect_one()) {
#pragma unroll
        for (int i = 0; i < B_WOFULL; i++)
            if (i != B_FULLA && i != B_FULLB) mbar_init(bars + 8 * i, i >= B_FFULL && i < B_FEMPTY ? 5 : 1);
    }
    if (warp == 4 && elect_one()) {
#pragma unroll
        for (int i = B_EMPTY; i < NBAR; i++) mbar_init(bars + 8 * i, i < B_UPD ? 2 : i < B_AUX ? 4 : i == B_AUX ? 7 : i == B_CSDONE ? 3 : 8);
    }
    __syncthreads();

    if (warp >= 12) {
        reg_dec<24>();
        if (warp > 12) {
            const int p = warp - 13;
            if (p == 1) {
                float sw = 0.f;
                mbar_wait(bars + 8 * (B_ROW + 4), 0);
#pragma unroll 1
                for (int i = 0; i < 16; i++) { const uint32_t q = lds1(sb + OFF_FA + i * 128 + lane * 4); sw += bf_lo(q) + bf_hi(q); }
#pragma unroll 1
                for (int o = 1; o < 32; o <<= 1) sw += __shfl_xor_sync(0xffffffffu, sw, o);
                if (lane == 0) { sts1(sb + OFF_TAG + 4, __float_as_uint(sw)); mbar_arrive(bars + 8 * B_SW); }
            } else {
#pragma unroll 1
                for (int q = 0; q < 4; q++) {
                    nap(p ? (q ? D_R : N_ROW) : (q ? D_X : N_X));
                    if (p == 0) {
                        const __nv_bfloat16* xp = x + (size_t)((j0 + nt * 16 + (lane >> 1)) * 2 + par) * 1024 + q * 256 + (lane & 1) * 64;
                        prefetch_l2(xp); prefetch_l2(xp + 128);
                    } else if (elect_one()) {
                        mbar_expect_tx(bars + 8 * (B_ROW + q), 8192);
                        tma_3d(sb + OFF_FW + q * 8192, &mxs, bars + 8 * (B_ROW + q), 0, j0 + nt * 16, par * 16 + q * 4);
                    }
                }
                if (p == 0) nap(N_CS);
            }
            const uint32_t stg = sb + OFF_FW + 32768 + p * 4096 + lane * 16;
            float c[8];
#pragma unroll
            for (int i = 0; i < 8; i++) c[i] = 0.f;
#pragma unroll 1
            for (int n = 0; n < 10; n++) {
                const uint32_t bo = (n & 1) * 2048, bar = bars + 8 * (B_CS + 2 * p + (n & 1));
                if (n >= 2) {
                    mbar_wait(bar, ~(n >> 1) & 1);
#pragma unroll 2
                    for (int i = 0; i < 4; i++) {
                        const uint4 v = lds4(stg + bo + i * 512);
                        c[0] += bf_lo(v.x); c[1] += bf_hi(v.x); c[2] += bf_lo(v.y); c[3] += bf_hi(v.y);
                        c[4] += bf_lo(v.z); c[5] += bf_hi(v.z); c[6] += bf_lo(v.w); c[7] += bf_hi(v.w);
                    }
                    asm volatile("" :: "f"(c[7]));
                    __syncwarp();
                }
                if (n < 8 && elect_one()) {
                    mbar_expect_tx(bar, 2048);
                    tma_3d(sb + OFF_FW + 32768 + p * 4096 + bo, &mcs, bar, p * 1024 + nt * 64, mt * 8, 2 * n);
                }
            }
            sts4(stg + lane * 16, __float_as_uint(c[0]), __float_as_uint(c[1]), __float_as_uint(c[2]), __float_as_uint(c[3]));
            sts4(stg + lane * 16 + 16, __float_as_uint(c[4]), __float_as_uint(c[5]), __float_as_uint(c[6]), __float_as_uint(c[7]));
            bar_sync(13, 128);
            const uint32_t tag = lds1(sb + OFF_TAG);
            float* gcs = &S->cs[0][p * 1024 + nt * 64];
            {
                const float2 a0 = lds2f(stg - lane * 8), a1 = lds2f(stg - lane * 8 + 256), a2 = lds2f(stg - lane * 8 + 512), a3 = lds2f(stg - lane * 8 + 768);
                st_rlx2(gcs + mt * 3072 + lane * 2, tagf((a0.x + a1.x) + (a2.x + a3.x), tag), __float_as_uint((a0.y + a1.y) + (a2.y + a3.y)));
            }
            fence_async_smem();
            __syncwarp();
            if (lane == 0) mbar_arrive(bars + 8 * B_CSDONE);
            TSC(warp == 13 && lane == 0, 19);
            {
                uint4 v[4];
                const float* src = gcs + (lane >> 4) * 4 * 3072 + (lane & 15) * 4;
#pragma unroll 1
                for (int it = 0; it < SPIN_LIMIT; it++) {
#pragma unroll
                    for (int m = 0; m < 4; m++) v[m] = ld_rlx4(src + m * 3072);
                    if (!__any_sync(0xffffffffu, (mism(v[0].x, v[1].x, tag) | mism(v[2].x, v[3].x, tag)) & 1)) break;
                }
                __syncwarp();
#pragma unroll
                for (int c = 0; c < 4; c++) {
                    const float a = (__uint_as_float((&v[0].x)[c]) + __uint_as_float((&v[1].x)[c])) + (__uint_as_float((&v[2].x)[c]) + __uint_as_float((&v[3].x)[c]));
                    (&v[0].x)[c] = __float_as_uint(a + __shfl_xor_sync(0xffffffffu, a, 16));
                }
                const uint32_t ca = sb + OFF_CS + p * 384 + ((lane & 15) >> 1) * 48 + (lane & 1) * 8;
#pragma unroll 1
                for (int r = 0; r < 3; r++) {
                    const uint32_t u0 = pack_bf16(__uint_as_float(v[0].x), __uint_as_float(v[0].y)), u1 = pack_bf16(__uint_as_float(v[0].z), __uint_as_float(v[0].w));
                    sts2(ca + r * 16, u0, u1);
                    v[0].x = __float_as_uint(__uint_as_float(v[0].x) - bf_lo(u0)); v[0].y = __float_as_uint(__uint_as_float(v[0].y) - bf_hi(u0));
                    v[0].z = __float_as_uint(__uint_as_float(v[0].z) - bf_lo(u1)); v[0].w = __float_as_uint(__uint_as_float(v[0].w) - bf_hi(u1));
                }
                if (lane < 20) sts1(sb + OFF_CS + 1152 + lane * 4, 0);
                fence_async_smem();
            }
            __syncwarp();
            if (lane == 0) mbar_arrive(bars + 8 * B_AUX);
            TSC(warp == 13 && lane == 0, 21);
            mbar_wait(bars + 8 * B_PART, 0);
            mbar_wait(bars + 8 * (B_EMPTY + 2), 0);
            if (p == 0) {
                uint4 v[4];
#pragma unroll
                for (int c = 0; c < 4; c++) v[c] = make_uint4(0, 0, 0, 0);
                const uint32_t* hsrc = &S->halo[b - 16][lane * 4];
#pragma unroll 1
                for (int it = 0; it < SPIN_LIMIT && j0; it++) {
#pragma unroll
                    for (int c = 0; c < 4; c++) v[c] = ld_rlx4(hsrc + c * 128);
                    if (!__any_sync(0xffffffffu, (mism(v[0].x, v[1].x, tag) | mism(v[2].x, v[3].x, tag)) & 1)) break;
                }
#pragma unroll
                for (int c = 0; c < 4; c++) sts4(sb + OFF_HALO + c * 512 + lane * 16, v[c].x, v[c].y, v[c].z, v[c].w);
                __syncwarp();
                bar_arrive(3, 64);
                TSC(TIMING >= 11 && lane == 0, 34);
            } else {
                const int w = p - 1;
                const uint8_t* osrc = g_o + (size_t)((mt * 2 + hp) * 2 + w) * 131072;
                const bool far = w > hp && j0 && lane >= 16;
                const uint32_t* hsrc = &S->hint[b & 0x70][0] + ((lane & 15) - (far ? 16 : 0)) * 8;
                if (lane == 0 && !w) st_rlx(&S->hint[b][0], tagw(now(), 1u, tag));
                uint32_t hv;
#pragma unroll 1
                for (int it = 0; it < SPIN_LIMIT; it++) {
                    hv = ld_rlx(hsrc);
                    if (!__any_sync(0xffffffffu, (hv ^ tag) & 1)) break;
                }
                TSC(TIMING == 11 && lane == 0, 32 + w);
                const uint32_t tn = __shfl_sync(0xffffffffu, hv, 0) - 0x40000000u;
                hv = redux_max(hv - tn + (far ? T_H : 0)) + tn + T_O + w * T_O1;
                mbar_wait(bars + 8 * (w ? B_AST : B_G1DONE), 0);
                if (elect_one()) {
#pragma unroll 1
                    for (int st = 0; st < 8; st++) {
                        const uint32_t full = bars + 8 * (B_OFULL + 8 * w + st);
                        if (st == 2 && !w) { until(hv + T_GO); mbar_arrive(bars + 8 * B_GO); }
                        if (st >= 2) mbar_wait(full + 8 * (B_DONE - B_OFULL - 2), 0);
                        if (st < 3) until(hv + (st == 2 ? T_S2 : st * T_S1));
                        TSC(st == 0, 28 + w);
                        mbar_expect_tx(full, 16384);
                        bulk_g2s(sb + (w ? OFF_O1 : OFF_O0) + (st & 1) * 16384, osrc + st * 16384, 16384, full);
                    }
                }
            }
            TS_END();
            return;
        }
        if (elect_one()) {
            auto load_wo = [&](int s, int ws) {
                mbar_expect_tx(bars + 8 * (B_WOFULL + s), 32768);
                tma_4d(sb + OFF_WO + ws * 32768, &mwo, bars + 8 * (B_WOFULL + s), 0, s * 8, 0, cb * 2);
            };
            uint32_t so = 2 * STAGE, ph = 1, cnt = PF_CNT << 4;
            int bi = 1, q = 0;
            mbar_expect_tx(bars + 8 * (B_ROW + 4), 2048);
            bulk_g2s(sb + OFF_FA, wr, 2048, bars + 8 * (B_ROW + 4));
            if (smem_u32(smem) != sb) __trap();
            const char* pf = (b < 64 ? wg : wu) + (b & 63) * 7168;
#pragma unroll 1
            for (int p = 1; p < 16; p++) {
                if (p < 3) nap(p == 1 ? N_S1 : N_S2);
                mbar_wait(bars + 8 * (B_EMPTY + bi), ph);
                load_stage(p, so, bi);
                if (p >= 2 && p < 5) {
                    const int k0 = p == 2 ? 3 : p == 3 ? K_W1 : K_W2, n = ((p == 2 ? K_W1 : p == 3 ? K_W2 : 16) - k0) * 3072;
                    if (p == 2) nap(N_W);
                    bulk_prefetch((const char*)wqkv + k0 * 393216 + b * n, n);
                }
#pragma unroll 1
                for (int e = q + (cnt & 3); q < e; q++) {
                    if (q == 16) pf = wd + mt * 7 * 131072 + nt * 8192;
                    if (q == 23) pf = wo + b * 8192;
                    bulk_prefetch(pf, q < 16 ? 7168 : 8192);
                    pf += q < 16 ? 64 * 7168 : q < 23 ? 131072 : 1048576;
                }
                cnt >>= 2;
                so = so == 2 * STAGE ? 0 : so + STAGE;
                if (++bi == 3) { bi = 0; ph ^= 1; }
            }
            TS(27);
            int ws = 1;
#pragma unroll 1
            for (int i = 0; i < 8; i++) {
                if (i < 2) {
                    mbar_wait(bars + 8 * (B_EMPTY + 1 + i), 0);
                    mbar_expect_tx(bars + 8 * B_XR, 16384);
                    tma_4d(sb + (i ? 0 : OFF_X1), &mx, bars + 8 * B_XR, DBG_XR * (par * 1024 + cb * 128 + 64 - i * 64), 0, DBG_XR * ((j0 >> 5) + hp * 4), 0);
                }
                if (i == 1) {
                    mbar_expect_tx(bars + 8 * B_F2FULL, 8192);
                    tma_2d(sb + OFF_F2X, &mwd, bars + 8 * B_F2FULL, DBG_F2 * c2 * 64, DBG_F2 * kc * 448);
                }
                if (i) {
                    mbar_wait(bars + 8 * (i == 1 ? B_ATT : i == 2 ? B_F2DONE : B_DONE - NWO + i), 0);
                    mbar_wait(bars + 8 * (i == 1 ? WO1_GATE : i == 2 ? B_OFULL + 8 : B_DONE + 8 - NWO + i), 0);
                }
                load_wo(i, ws);
                ws = ws ? ws - 1 : NWO - 1;
            }
        }
        TS_END();
    } else if (warp >= 8) {
        reg_dec<40>();
        const int p = warp - 8;
        const bool f1 = fb < 112;
        auto ffn_w = [&](int n, int s) {
            const uint32_t dst = sb + OFF_FW + s * 16384;
            if (n < 8) {
                mbar_expect_tx(bars + 8 * (B_FFULL + s), 16384);
                tma_3d(dst, &mgu, bars + 8 * (B_FFULL + s), DBG_F1 * fb * 32, n * 128, 0);
            } else {
                mbar_expect_tx(bars + 8 * B_F2FULL, 16384);
                tma_2d(dst, &mwd, bars + 8 * B_F2FULL, DBG_F2 * c2 * 64, DBG_F2 * kc * 448 + 64 + s * 128);
                tma_2d(dst + 8192, &mwd, bars + 8 * B_F2FULL, DBG_F2 * c2 * 64, DBG_F2 * kc * 448 + 128 + s * 128);
            }
        };
        const uint32_t tag = (epoch & 1) - 1;
        {
            const int ta = tid - 256;
            if (ta < 48) st_rlx4(&S->cs[mt][(ta >> 4) * 1024 + nt * 64 + (ta & 15) * 4], ~tag, ~tag, ~tag, ~tag);
            st_rlx4(&S->ypart[kc][ta >> 4][c2 * 64 + (ta & 15) * 4], ~tag, ~tag, ~tag, ~tag);
            if (p == 3 && f1) st_rlx4(&S->h[fb * 128 + lane * 4], ~tag, ~tag, ~tag, ~tag);
            if (ta < 2) st_rlx4(&S->hint[b][ta * 4], ~tag, ~tag, ~tag, ~tag);
            st_rlx4(&S->halo[b][ta * 4], ~tag, ~tag, ~tag, ~tag);
        }
        float s1 = 0.f, s2 = 0.f, sr = 0.f, sw, sh = 0.f;
        {
            const uint32_t xa = sb + OFF_FW + p * 512 + lane * 16, wa = sb + OFF_FA + (((p * 4 + (lane >> 3)) ^ lane) & 7) * 16;
            TSC(TIMING == 12 && lane == 0, 50 + p);
            mbar_wait(bars + 8 * (B_ROW + 4), 0);
            {
                float c1 = 0.f, c2 = 0.f, cr = 0.f;
#pragma unroll 1
                for (int q = 0; q < 4; q++) {
                mbar_wait(bars + 8 * (B_ROW + q), 0);
                TSC(TIMING == 12 && tid == 256 + 96, 32 + q);
                TSC(tid == 256 && q == 3, 17);
#pragma unroll
                for (int i = 0; i < 4; i++) {
                    const uint4 u = lds4(xa + q * 8192 + i * 2048), w4 = lds4(wa + q * 512 + i * 128);
                    if (DBG_ST == 1) { s2 += fabsf(bf_lo(u.x ^ (u.y & u.z & u.w & 1))); sr += bf_lo(w4.x ^ w4.y ^ w4.z ^ w4.w ^ u.x); continue; }
                    const float a0 = bf_lo(u.x), a1 = bf_hi(u.x), a2 = bf_lo(u.y), a3 = bf_hi(u.y), a4 = bf_lo(u.z), a5 = bf_hi(u.z), a6 = bf_lo(u.w), a7 = bf_hi(u.w);
                    s1 += a0 + a1; c1 += a4 + a5; s1 += a2 + a3; c1 += a6 + a7;
                    s2 = fmaf(a0, a0, s2); c2 = fmaf(a4, a4, c2); sr = fmaf(a0, bf_lo(w4.x), sr); cr = fmaf(a4, bf_lo(w4.z), cr);
                    s2 = fmaf(a1, a1, s2); c2 = fmaf(a5, a5, c2); sr = fmaf(a1, bf_hi(w4.x), sr); cr = fmaf(a5, bf_hi(w4.z), cr);
                    s2 = fmaf(a2, a2, s2); c2 = fmaf(a6, a6, c2); sr = fmaf(a2, bf_lo(w4.y), sr); cr = fmaf(a6, bf_lo(w4.w), cr);
                    s2 = fmaf(a3, a3, s2); c2 = fmaf(a7, a7, c2); sr = fmaf(a3, bf_hi(w4.y), sr); cr = fmaf(a7, bf_hi(w4.w), cr);
                }
                }
                s1 += c1; s2 += c2; sr += cr;
            }
            mbar_wait(bars + 8 * B_SW, 0);
            sw = lds1f(sb + OFF_TAG + 4);
#pragma unroll 1
            for (int pass = 0;; pass++) {
#pragma unroll
                for (int o = 1; o < 8; o <<= 1) {
                    s1 += __shfl_xor_sync(0xffffffffu, s1, o); s2 += __shfl_xor_sync(0xffffffffu, s2, o); sr += __shfl_xor_sync(0xffffffffu, sr, o);
                }
                s1 *= 1.f / 1024.f;
                s2 = fmaf(-s1, s1, s2 * (1.f / 1024.f));
                if (!__any_sync(0xffffffffu, !pass && s1 * s1 > 256.f * s2)) break;
                sh = bf16r(s1); s1 = 0.f; s2 = 0.f; sr = 0.f;
#pragma unroll 1
                for (uint32_t o = 0; o < 2048; o = opaque(o + ((o & 12) == 12 ? 116 : 4))) {
                    const uint32_t u = lds1(xa + (o >> 7) * 2048 + (o & 12)), q = lds1(wa + o);
                    const float a0 = bf_lo(u) - sh, a1 = bf_hi(u) - sh;
                    s1 += a0 + a1; s2 = fmaf(a0, a0, fmaf(a1, a1, s2)); sr = fmaf(a0, bf_lo(q), fmaf(a1, bf_hi(q), sr));
                }
            }
        }
        const int ta = opaque(tid) - 256, lane = ta & 31, g = lane >> 2, t = lane & 3;
        {
            if ((lane & 7) == 0) {
                const int s = b * 16 + p * 4 + (lane >> 3);
                const float mb = bf16r(sh + s1);
                float den;
                asm("sqrt.approx.f32 %0, %1;" : "=f"(den) : "f"(bf16r(bf16r(s2) + 1e-5f)));
                den = bf16r(den);
                uint32_t rb = pack_bf16(fmaf(sh - mb, sw, sr) * rcp(den), 0.f);
                if (rb == 0x8000u) rb = 0;
                uint32_t ord = (rb & 0x8000u) ? (~rb & 0xffffu) : (rb | 0x8000u);
                if ((rb & 0x7fffu) > 0x7f80u) ord = 0;
                st_rlx2(&S->rec[s], (ord << 16) | (tag & 0x8000u) | (0x47ffu - (s & 1023) * 2 - par), pack_bf16(mb, den));
            }
            TSC(TIMING == 12 && lane == 0, 36 + p);
            bar_sync(12, 128);
            if (p == 1) sts1(sb + OFF_ROWMAP + lane * 4, 0xffffffffu);
            if (p == 0) {
                if (lane == 0) {
                    sts1(sb + OFF_TAG, tag);
                }
                __syncwarp();
                bar_arrive(13, 128);
            }
            TSC(ta == 0, 18);
        }
        {
            uint2 r[3];
            nap(N_GA);
            const uint2* src = &S->rec[mt * 256 + ta];
            const int l2 = ta < 8 && j0 ? -8 : 0;
#pragma unroll 1
            for (int it = 0; it < SPIN_LIMIT; it++) {
                r[0] = ld_rlx2(src + l2); r[1] = ld_rlx2(src); r[2] = ld_rlx2(src + 128);
                if (!__any_sync(0xffffffffu, (mism(r[0].x, r[1].x, tag) | (r[2].x ^ tag)) & 0x8000u)) break;
            }
#pragma unroll
            for (int n = 0; n < 3; n++)
                if (n || ta < 8) sts2(sb + OFF_STAT + (n ? n * 1024 - 960 : 0) + ta * 8, (r[n].y << 16) ^ 0x80000000u, __float_as_uint(rcp(bf_hi(r[n].y))));
        }
        __syncwarp();
        if (lane == 0) mbar_arrive(bars + 8 * B_AUX);
        TSC(ta == 0, 30);
        if (f1 && p < EARLY_FILL && elect_one()) { nap(p * N_F1); ffn_w(p, p); }
        __syncwarp();
        uint2 sel;
#pragma unroll 1
        for (int it = 0; it < SPIN_LIMIT; it++) {
            sel = ld_rlx2(&S->sel[lane & 7]);
            if (!__any_sync(0xffffffffu, (sel.x ^ tag) & 0x8000u)) break;
            __nanosleep(POLL_NS);
        }
        TSC(ta == 0, 26);
        if (b == 0 && ta == 0) st_rlx(&S->epoch, epoch + 1);
        {
            const __nv_bfloat16* xp = x + (~sel.x & 0x7ffu) * 1024 + (ta >> 3) * 8;
            const float mb = bf_lo(sel.y), rinv = rcp(bf_hi(sel.y));
            uint4 v = ldg_nc(xp), v2 = ldg_nc(xp + 128);
            int s = f1 ? 0 : 2;
#pragma unroll 1
            for (int n = f1 ? 0 : 8; n < (p ? 8 : 11); n++) {
                mbar_wait(bars + 8 * (f1 ? B_FEMPTY + s : B_PART), f1 && (n < 3 || (n >= 6 && n < 9)));
                if (p == 0 && s == 2) mbar_wait(bars + 8 * B_CSDONE, 0);
                if (p == 0 && n >= EARLY_FILL && elect_one()) ffn_w(n, s);
                if (n < 8) {
                    sts4(sb + OFF_FA + s * 2048 + ta * 16, norm_pair(v.x, mb, rinv), norm_pair(v.y, mb, rinv), norm_pair(v.z, mb, rinv), norm_pair(v.w, mb, rinv));
                    fence_async_smem();
                    __syncwarp();
                    if (lane == 0) mbar_arrive(bars + 8 * (B_FFULL + s));
                    TSC(TIMING == 12 && ta == 0, 41 + n);
                    v = v2;
                    if (n) v = ldg_nc(xp + ((n + 1) & 7) * 128);
                }
                if (++s == 3) s = 0;
            }
        }
        mbar_wait(bars + 8 * B_PART, 0);
        if (f1 && p >= 2) {
            const uint32_t pa = sb + OFF_FA + (ta - 64) * 16, go = wu < wg ? 1024 : 0;
            const float4 g0 = lds4f(pa + go), g1 = lds4f(pa + 2048 + go), u0 = lds4f(pa + (go ^ 1024)), u1 = lds4f(pa + 2048 + (go ^ 1024));
            float hv[4];
#pragma unroll
            for (int c = 0; c < 4; c++) {
                const float ga = bf16r((&g0.x)[c] + (&g1.x)[c]), up = bf16r((&u0.x)[c] + (&u1.x)[c]);
                hv[c] = bf16r(ga * sigmoidf(ga)) * up;
            }
#pragma unroll
            for (int hh = 0; hh < 2; hh++) {
                const float o = __shfl_xor_sync(0xffffffffu, (g & 1) ? hv[2 * hh] : hv[2 * hh + 1], 4);
                st_rlx(&S->h[(fb * 4 + (p & 1) * 2 + hh) * 32 + (2 * t + (g & 1)) * 4 + (g >> 1)],
                       tagw((g & 1) ? pack_bf16(o, hv[2 * hh + 1]) : pack_bf16(hv[2 * hh], o), g < 2, tag));
            }
            TSC(ta == 64, 22);
        }
        {
            uint4 hq[4];
            const uint32_t* hp4 = S->h + kc * 1792 + ta * 4;
#pragma unroll 1
            for (int it = 0; it < SPIN_LIMIT; it++) {
#pragma unroll
                for (int n = 0; n < 4; n++) hq[n] = ld_rlx4(hp4 + (n < 3 ? n * 512 : p < 2 ? 1536 : 0));
                if (!__any_sync(0xffffffffu, (mism(hq[0].x, hq[1].x, tag) | mism(hq[2].x, hq[3].x, tag)) & 1)) break;
            }
            mbar_wait(bars + 8 * B_G1DONE, 0);
            bar_sync(12, 128);
#pragma unroll
            for (int n = 0; n < 4; n++) sts4(sb + OFF_FA + ta * 16 + (n < 3 ? n * 2048 : p < 2 ? 6144 : 0), hq[n].x, hq[n].y, hq[n].z, hq[n].w);
            fence_async_smem();
            bar_sync(12, 128);
            TSC(ta == 0, 25);
            mbar_wait(bars + 8 * B_F2FULL, 0);
            mbar_wait(bars + 8 * B_ATT, 0);
            float acc[4] = {0.f, 0.f, 0.f, 0.f};
            uint32_t da = sd + dlo(OFF_F2X, 8192), db = sd + dlo(OFF_FA, 128);
#pragma unroll 1
            for (int q = 0; q < 7; q++) {
                wg_fence();
#pragma unroll
                for (int j = 0; j < 4; j++) wgmma_n8<1, 0>(acc, mkdesc(da + j * 128, dhi(1024, 1)), mkdesc(db + j * 16, dhi(128, 0)));
                wg_commit();
                da = sd + dlo(OFF_FW, 8192) + q * 512; db += 64;
            }
            wg_wait<0>();
            if (ta == 0) mbar_arrive(bars + 8 * B_F2DONE);
#pragma unroll
            for (int c = 0; c < 4; c++) st_rlx(&S->ypart[kc][2 * t + (c & 1)][c2 * 64 + p * 16 + (c >> 1) * 8 + g], tagf(acc[c], tag));
            TSC(ta == 0, 23);
            bar_sync(12, 128);
        }
#pragma unroll 1
        for (int j = 2 * p; j < 2 * p + 2; j++) {
            const uint32_t kj = __shfl_sync(0xffffffffu, sel.x, j);
            const int row = 0x7ff - (kj & 0x7ffu), jj = (row >> 1) - j0 - hp * 128;
            float a0 = 0.f, a1 = 0.f, a2 = 0.f, a3 = 0.f, sig = 0.f;
            if ((row & 1) == par && jj >= 0 && jj < 128) {
                sig = bf16r(sigmoidf(__uint_as_float(((int)kj < 0 ? kj ^ 0x80000000u : ~kj) & 0xffff0000u)));
#pragma unroll 1
                for (int hh = 0; hh < 8; hh += 4) {
                    uint4 v[4];
#pragma unroll 1
                    for (int it = 0; it < SPIN_LIMIT; it++) {
#pragma unroll
                        for (int m = 0; m < 4; m++) v[m] = ld_rlx4(&S->ypart[hh + m][j][cb * 128 + lane * 4]);
                        if (!__any_sync(0xffffffffu, (mism(v[0], tag) | mism(v[1], tag) | mism(v[2], tag) | mism(v[3], tag)) & 1)) break;
                    }
#pragma unroll
                    for (int m = 0; m < 4; m++) { a0 += __uint_as_float(v[m].x); a1 += __uint_as_float(v[m].y); a2 += __uint_as_float(v[m].z); a3 += __uint_as_float(v[m].w); }
                }
                asm volatile("st.shared.u8 [%0], %1;" ::"r"(sb + OFF_ROWMAP + jj), "r"(j) : "memory");
            }
            sts2(sb + OFF_FA + (lane >> 1) * 128 + j * 16 + (lane & 1) * 8, pack_bf16(bf16r(a0) * sig, bf16r(a1) * sig), pack_bf16(bf16r(a2) * sig, bf16r(a3) * sig));
        }
        fence_async_smem();
        __syncwarp();
        if (lane == 0) mbar_arrive(bars + 8 * B_UPD);
        TSC(ta == 0, 24);
        TS_END();
    } else {
        if (elect_one()) {
#pragma unroll
            for (int i = 0; i < (B_EMPTY - B_WOFULL) / 8; i++) mbar_init(bars + 8 * (B_WOFULL + 8 * i + warp), 1);
        }
        reg_inc<224>();
        const int w = warp >> 2, wi = warp & 3, tw = (1 - w) * 4 + wi;
        const bool elect = (tid & 127) == 0;
        const uint32_t ln = opaque(lane), g = ln >> 2, t = ln & 3;
        uint32_t tag, ow[8][4], xr[32];
        const uint32_t xs = sb + (wi & 1) * 8192 + (tw >> 1) * 2048, mad = xs + (ln & 15) * 128;
        auto store_o = [&](int f0, int f1) {
            uint8_t* ob = g_o + (size_t)((mt * 2 + 1 - w) * 2 + 1 - (wi >> 1)) * 131072 + nt * 1024 + (wi & 1) * 512 + ln * 4;
#pragma unroll
            for (int f = f0; f < f1; f++)
#pragma unroll
                for (int i = 3; i >= 0; i--)
                    st_rlx(ob + f * 16384 + i * 128, ow[f][i]);
        };
        {
            float acc[2][96];
            const uint32_t sta = opaque(sb + OFF_STAT + tw * 256 + 64 + g * 8);
            {
                float fa[4] = {0.f, 0.f, 0.f, 0.f};
                uint32_t so = STAGE >> 4, bo = bars, ph = 0;
                const uint32_t dx0 = sd + dlo(w ? 40960 : 0, 16), dw0 = sd + dlo(16384, 8192);
                int p = 0;
                if (w) bar_arrive(1, 256);
                uint32_t fm = fb < 112 ? F1_MASK >> (16 * w) : 0u, fph = 0;
                int fs = w;
#pragma unroll 1
                for (; p < 16; p++) {
                    mbar_wait(bo + 8 * B_FULLA, ph);
                    if (w) mbar_wait(bo + 8 * B_FULLB, ph);
                    TSC(elect && p == 0, 1 + 8 * w);
                    bar_sync(1 + w, 256);
                    TSC(TIMING == 1 && tid == 0, 32 + p);
                    wg_fence();
#pragma unroll
                    for (int k = 0; k < 4; k++) {
                        wgmma_n192<0, 1>(acc[0], mkdesc(dx0 + so + k * 2, dhi(1024, 1)), mkdesc(dw0 + so + k * 128, dhi(1024, 1)), k ? 1 : p);
                        wgmma_n192<0, 1>(acc[1], mkdesc(dx0 + so + 512 + k * 2, dhi(1024, 1)), mkdesc(dw0 + so + k * 128, dhi(1024, 1)), k ? 1 : p);
                    }
                    wg_commit();
                    if (fm & 1) {
                        mbar_wait(bars + 8 * (B_FFULL + fs), fph);
                        wg_fence();
#pragma unroll
                        for (int j = 0; j < 8; j++)
                            wgmma_n8<1, 0>(fa, mkdesc(sd + dlo(OFF_FW, 8192) + fs * 1024 + j * 64, dhi(512, 2)), mkdesc(sd + dlo(OFF_FA, 128) + fs * 128 + j * 16, dhi(128, 0)));
                        wg_commit();
                    } else if (p == 15) {
                        wg_fence();
                        wgmma_n192<0, 1>(acc[0], mkdesc(sd + dlo(OFF_MEAN, 0) + w * 128, dhi(128, 0)), mkdesc(sd + dlo(OFF_CS, 0), dhi(48, 0)));
                        wgmma_n192<0, 1>(acc[1], mkdesc(sd + dlo(OFF_MEAN + 1024, 0) + w * 128, dhi(128, 0)), mkdesc(sd + dlo(OFF_CS, 0), dhi(48, 0)));
                        wg_commit();
                    }
                    bar_arrive(2 - w, 256);
                    wg_wait<0>();
                    if (wi == 0 && elect_one()) { mbar_arrive(bo + 8 * B_EMPTY); if (fm & 1) mbar_arrive(bars + 8 * (B_FEMPTY + fs)); }
                    so = so == 2 * (STAGE >> 4) ? 0 : so + (STAGE >> 4);
                    bo += 8;
                    if (bo == bars + 24) { bo = bars; ph ^= 1; }
                    if (fm & 1) { fs += 2; if (fs >= 3) { fs -= 3; fph ^= 1; } }
                    fm >>= 1;
                    if (p == P_PART) {
                        if (fb < 112) sts4(sb + OFF_FA + tid * 16, __float_as_uint(fa[0]), __float_as_uint(fa[1]), __float_as_uint(fa[2]), __float_as_uint(fa[3]));
                        __syncwarp();
                        if (lane == 0) mbar_arrive(bars + 8 * B_PART);
                    }
                    if (p != 14) continue;
                    mbar_wait(bars + 8 * B_AUX, 0);
                    mbar_wait(bars + 8 * (B_EMPTY + 1), 0);
                    const uint32_t hm = __float_as_uint(0.5f * lds1f(sb + OFF_STAT + 64 + tw * 256 + ln * 8)) >> 16;
                    sts4(sb + OFF_MEAN + w * 2048 + wi * 256 + (ln >> 4) * 1024 + (ln & 15) * 16, hm * 0x10001u, hm, 0, 0);
                    fence_async_smem();
                }
                if (elect) mbar_arrive(bars + 8 * B_G1DONE);
            }
            TSC(TIMING != 14 && elect, 2 + 8 * w);

            tag = lds1(sb + OFF_TAG);
            mbar_wait(bars + 8 * (B_EMPTY + 2), 0);
            uint32_t pk[4][24];
            const uint32_t hm = tw == 7 ? ~ln & 1 : 0;
            auto np = [&](int i, int j) {
                const float* a = &acc[i >> 1][4 * j + 2 * (i & 1)];
                pk[i][j] = pack_bf16(a[0], a[1]);
                if (j >= 16) pk[i][j] = movm(pk[i][j]);
                if (i == 3 && j >= 8 && !(j & 1)) pk[i][j] = tagw(pk[i][j], hm, tag);
            };
            const uint32_t ha = sb + OFF_HALO + tw * 2048 + ln * 8;
#pragma unroll
            for (int j = 8; j < 24; j += 2) {
                np(3, j); np(3, j + 1);
                sts2(ha + 2048 + (j - 8) * 128, pk[3][j], pk[3][j + 1]);
                asm volatile("{\n.reg .pred p;\nsetp.eq.u32 p, %3, 7;\n@p st.relaxed.gpu.global.v2.u32 [%0], {%1,%2};\n}" ::"l"((char*)&S->halo[b][ln * 2] + (j - 8) * 128),
                             "r"(pk[3][j]), "r"(pk[3][j + 1]), "r"(tw) : "memory");
            }
            bar_arrive(4 + tw, 64);
            TSC(TIMING == 8 && ln == 0 && wi == 1, 32 + 8 * w);
            mbar_wait(bars + 8 * B_G1DONE, 0);
            const bool u0 = 2 * t > g, u1 = 2 * t + 1 > g;
            const uint32_t mU = (u0 ? 0xffffu : 0u) | (u1 ? 0xffff0000u : 0u);
            uint2 hl[8];
            float rk[4][2], fq[4][2];
            const float mask = tw == 0 && j0 == 0 ? -INFINITY : 0.f;
#pragma unroll
            for (int hd = 0; hd < 2; hd++) {
#pragma unroll
                for (int jj = 0; jj < 12; jj++) {
                    const int j = (jj >> 2) * 8 + hd * 4 + (jj & 3);
                    np(0, j); np(1, j); np(2, j);
                    if (j < 8) np(3, j);
                }
                float s[2][3][4];
#pragma unroll
                for (int h = 1; h >= 0; h--)
#pragma unroll
                    for (int n = 2; n >= 0; n--) {
                        if (h == 0 && n == 0 && hd == 0) {
                            const uint32_t ka = sb + OFF_STAT + tw * 256 + 4 + t * 16, k0 = opaque(ka + (u0 ? 0 : 64)), k1 = opaque(ka + (u1 ? 8 : 72));
#pragma unroll
                            for (int i = 0; i < 4; i++) {
                                const float rq = lds1f(sta + i * 64 + 4) * (0.17677669529663687f * 1.4426950408889634f);
                                rk[i][0] = lds1f(k0 + i * 64); rk[i][1] = lds1f(k1 + i * 64);
                                fq[i][0] = rq * rk[i][0]; fq[i][1] = rq * rk[i][1];
                            }
                            TSC(TIMING == 8 && ln == 0 && wi == 1 && s[1][0][0] + s[0][1][0] != 123.456f, 33 + 8 * w);
                            bar_sync(3 + tw, 64);
#pragma unroll
                            for (int c = 0; c < 8; c++) hl[c] = lds2(ha + c * 256);
                        }
                        const int kg = 2 * h - 1 + n;
                        s[h][n][0] = s[h][n][1] = kg < 0 ? mask : 0.f; s[h][n][2] = s[h][n][3] = 0.f;
#pragma unroll
                        for (int ks = 0; ks < 2; ks++) {
                            const int q = hd * 4 + 2 * ks;
                            const uint32_t* k = kg < 0 ? &hl[hd * 2 + ks].x : &pk[kg < 0 ? 0 : kg][8 + q];
                            mma16816(s[h][n], pk[2 * h][q], pk[2 * h + 1][q], pk[2 * h][q + 1], pk[2 * h + 1][q + 1], k[0], k[1]);
                        }
                    }
                uint32_t pp[4], pc[4];
#pragma unroll
                for (int i = 0; i < 4; i++) {
                    const float* sp = &s[i >> 1][i & 1][2 * (i & 1)];
                    const float* sc = &s[i >> 1][(i & 1) + 1][2 * (i & 1)];
                    float a0 = (u0 ? sp[0] : sc[0]) * fq[i][0], a1 = (u1 ? sp[1] : sc[1]) * fq[i][1];
                    float m = fmaxf(a0, a1);
                    m = fmaxf(m, __shfl_xor_sync(0xffffffffu, m, 1));
                    m = fmaxf(m, __shfl_xor_sync(0xffffffffu, m, 2));
                    a0 = ex2(a0 - m); a1 = ex2(a1 - m);
                    float sum = a0 + a1;
                    sum += __shfl_xor_sync(0xffffffffu, sum, 1);
                    sum += __shfl_xor_sync(0xffffffffu, sum, 2);
                    const float inv = rcp(sum);
                    const uint32_t pw = pack_bf16(a0 * rk[i][0] * inv, a1 * rk[i][1] * inv);
                    pp[i] = pw & mU; pc[i] = pw & ~mU;
                }
                TSC(TIMING == 8 && ln == 0 && wi == 1 && pp[0] + pp[3] != 0x12345, 34 + 2 * hd + 8 * w);
#pragma unroll
                for (int fh = 0; fh < 2; fh++)
#pragma unroll
                    for (int i = 0; i < 4; i++) {
                        const int v = 16 + hd * 4 + 2 * fh;
                        const uint32_t* vp = i ? &pk[i ? i - 1 : 0][v] : &hl[4 + hd * 2 + fh].x;
                        float o[4] = {0.f, 0.f, 0.f, 0.f};
                        if (i & 1) mma16816(o, vp[0], vp[1], pk[i][v], pk[i][v + 1], pp[i], pc[i]);
                        else { mma1688(o, pk[i][v], pk[i][v + 1], pc[i]); mma1688(o, vp[0], vp[1], pp[i]); }
                        const uint32_t tm = (ln & 7) == (nt & 3) * 2 + (i & 1);
                        ow[hd * 4 + 2 * fh][i] = tagw(pack_bf16(o[0], o[1]), tm, tag); ow[hd * 4 + 2 * fh + 1][i] = tagw(pack_bf16(o[2], o[3]), tm, tag);
                    }
                store_o(hd ? ST_A : 0, hd ? ST_B : ST_A);
                TSC(TIMING == 11 && !hd && ln == 0 && wi == 3, 45 + w);
                if (hd) mbar_wait(bars + 8 * B_G1DONE, 0);
                if (hd) mbar_arrive_after(bars + 8 * B_ATT, ln, xr[16] ^ xr[20] ^ xr[24] ^ xr[28]);
                else {
                    mbar_arrive_after(bars + 8 * B_AST, ln, hl[2].x ^ hl[3].x ^ hl[5].x ^ hl[6].x ^ hl[7].x);
                    mbar_wait(bars + 8 * B_XR, 0);
#pragma unroll
                    for (int j = 0; j < 16; j += 2)
                        asm volatile("ldmatrix.sync.aligned.m8n8.x4.shared.b16 {%0,%1,%2,%3}, [%4];" : "=r"(xr[2 * j]), "=r"(xr[2 * j + 1]), "=r"(xr[2 * j + 2]), "=r"(xr[2 * j + 3])
                                     : "r"(mad + (j >> 3) * OFF_X1 + ((((j & 7) + (ln >> 4)) ^ (ln & 7)) << 4)) : "memory");
                }
                TSC(TIMING != 14 && elect && hd == 0, 3 + 8 * w);
                TSC(TIMING == 8 && ln == 0 && wi == 1, 35 + 2 * hd + 8 * w);
            }
        }
        TSC(TIMING != 14 && elect, 4 + 8 * w);
        float acc2[64];
        {
            const uint32_t sta = sb + OFF_STAT + (8 + hp * 128 + tw * 16 + g) * 8;
            const float2 s0 = lds2f(sta), s1 = lds2f(sta + 64);
            const float m0 = s0.x * s0.y, r0 = 1.f + s0.y, m1 = s1.x * s1.y, r1 = 1.f + s1.y;
#pragma unroll
            for (int j = 0; j < 32; j++) {
                acc2[2 * j] = fmaf(bf_lo(xr[j]), j & 1 ? r1 : r0, j & 1 ? m1 : m0); acc2[2 * j + 1] = fmaf(bf_hi(xr[j]), j & 1 ? r1 : r0, j & 1 ? m1 : m0);
                asm volatile("" : "+f"(acc2[2 * j]), "+f"(acc2[2 * j + 1]) :: "memory");
            }
        }
        TSC(TIMING != 14 && elect, 5 + 8 * w);
        {
            if (ST_B < ST_C) { mbar_wait(bars + 8 * B_GO, 0); store_o(ST_B, ST_C); }
            mbar_wait(bars + 8 * B_ATT, 0);
            const uint32_t ring = sb + (w ? OFF_O1 : OFF_O0), da0 = (ring >> 4) + dlo(0, 1024);
            const uint32_t chk = ring + wi * 256 + (ln >> 3) * 1032 + (g & 1) * 132 + t * 32;
            uint32_t db = sd + dlo(OFF_WO + 32768, 16384);
#pragma unroll 1
            for (int s = 0; s < 8; s++) {
                const uint32_t ro = (s & 1) * 16384;
                mbar_wait(bars + 8 * (B_WOFULL + s), 0);
                TSC(TIMING == 11 && tid == 0 && s == 0, 43);
                mbar_wait(bars + 8 * (B_OFULL + s) + 64 * w, 0);
                TSC(TIMING == 11 && tid == 0 && s == 0, 44);
#pragma unroll 1
                for (int it = 0; __any_sync(0xffffffffu, (mism(lds1(chk + ro), lds1(chk + ro + 4096), tag) | mism(lds1(chk + ro + 8192), lds1(chk + ro + 12288), tag)) & 1) && it < SPIN_LIMIT; it++) {
                    NRETRY();
                    const uint32_t fo = wi * 256 + (ln >> 4) * 1024 + (ln & 15) * 16;
                    uint4 v[8];
#pragma unroll
                    for (int c = 0; c < 8; c++) v[c] = ld_rlx4(g_o + (size_t)(((mt * 2 + hp) * 2 + w) * 8 + s) * 16384 + fo + c * 2048);
#pragma unroll
                    for (int c = 0; c < 8; c++) sts4(ring + ro + fo + c * 2048, v[c].x, v[c].y, v[c].z, v[c].w);
                    fence_async_smem();
                    __syncwarp();
                }
                if (s <= 8 - LAST) bar_sync(1 + w, 256);
                TSC(elect && s == 0, 6 + 8 * w);
                TSC(TIMING == 2 && elect, 32 + 16 * w + s);
                wg_fence();
#pragma unroll
                for (int k = 0; k < 8; k++)
                    wgmma_n128<1, 1>(acc2, mkdesc(da0 + (ro >> 4) + k * 128, dhi(128, 0)), mkdesc(db + k * 128, dhi(1024, 1)));
                wg_commit();
                db = db == sd + dlo(OFF_WO, 16384) ? sd + dlo(OFF_WO + (NWO - 1) * 32768, 16384) : db - 2048;
                if (s < 8 - LAST) {
                    bar_arrive(2 - w, 256);
                    if (s == 0) store_o(ST_C, 8);
                    wg_wait<0>();
                    if (elect) mbar_arrive(bars + 8 * (B_DONE + s) + 64 * w);
                }
            }
            mbar_wait(bars + 8 * B_UPD, 0);
            int sl0, sl1;
            asm volatile("ld.shared.s8 %0, [%1];" : "=r"(sl0) : "r"(sb + OFF_ROWMAP + tw * 16 + g) : "memory");
            asm volatile("ld.shared.s8 %0, [%1];" : "=r"(sl1) : "r"(sb + OFF_ROWMAP + tw * 16 + 8 + g) : "memory");
            const uint32_t e0 = (sl0 >> 1) == (int)t ? 0x3f80u << ((sl0 & 1) * 16) : 0u, e1 = (sl1 >> 1) == (int)t ? 0x3f80u << ((sl1 & 1) * 16) : 0u;
            wg_fence();
            wgmma_rs_n128<1>(acc2, e0, e1, 0u, 0u, mkdesc(sd + dlo(OFF_FA, 0), dhi(128, 0)));
            wg_commit();
            bar_arrive(2 - w, 256);
            wg_wait<0>();
#pragma unroll
            for (int i = 0; i < 64; i++) asm volatile("" : "+f"(acc2[i]) :: "memory");
            TSC(elect, 7 + 8 * w);
#pragma unroll
            for (int j = 0; j < 16; j += 2) {
                const int ch = (j & 7) + (ln >> 4);
                asm volatile("stmatrix.sync.aligned.m8n8.x4.shared.b16 [%0], {%1,%2,%3,%4};" ::"r"(mad + (j >> 3) * STAGE + ((ch ^ (ln & 7)) << 4)),
                             "r"(pack_bf16(acc2[4 * j], acc2[4 * j + 1])), "r"(pack_bf16(acc2[4 * j + 2], acc2[4 * j + 3])),
                             "r"(pack_bf16(acc2[4 * j + 4], acc2[4 * j + 5])), "r"(pack_bf16(acc2[4 * j + 6], acc2[4 * j + 7])) : "memory");
                if ((j & 7) == 6) {
                    fence_async_smem();
                    __syncwarp();
                    if (ln == 0) tma_store_2d(&mout, xs + (j >> 3) * STAGE, par * 1024 + cb * 128 + (j >> 3) * 64, j0 + hp * 128 + tw * 16);
                }
            }
            if (ln == 0) asm volatile("cp.async.bulk.commit_group;\ncp.async.bulk.wait_group.read 0;" ::: "memory");
            TSC(elect, 8 + 8 * w);
            TS_END();
        }
    }
}

typedef CUresult (*EncodeFn)(CUtensorMap*, CUtensorMapDataType, cuuint32_t, void*, const cuuint64_t*, const cuuint64_t*, const cuuint32_t*,
                             const cuuint32_t*, CUtensorMapInterleave, CUtensorMapSwizzle, CUtensorMapL2promotion, CUtensorMapFloatOOBfill);

CUtensorMap make_map(EncodeFn fn, const void* base, int rank, const cuuint64_t* dims, const cuuint64_t* strides, const cuuint32_t* box,
                     CUtensorMapSwizzle swz = CU_TENSOR_MAP_SWIZZLE_128B, CUtensorMapL2promotion pro = CU_TENSOR_MAP_L2_PROMOTION_L2_256B) {
    CUtensorMap m;
    cuuint32_t es[5] = {1, 1, 1, 1, 1};
    fn(&m, CU_TENSOR_MAP_DATA_TYPE_BFLOAT16, rank, (void*)base, dims, strides, box, es, CU_TENSOR_MAP_INTERLEAVE_NONE,
       swz, pro, CU_TENSOR_MAP_FLOAT_OOB_FILL_NONE);
    return m;
}

}

extern "C" void kernel_launch(void* const* d_in, const int* in_sizes, int n_in, void* d_out, int out_size) {
    (void)in_sizes; (void)n_in; (void)out_size;
    const __nv_bfloat16* x = (const __nv_bfloat16*)d_in[0];
    const __nv_bfloat16* wqkv = (const __nv_bfloat16*)d_in[1];
    const char* wo = (const char*)d_in[2];
    const __nv_bfloat16* wr = (const __nv_bfloat16*)d_in[4];
    const char* wg = (const char*)d_in[5];
    const char* wu = (const char*)d_in[6];
    const char* wd = (const char*)d_in[7];
    static EncodeFn fn = nullptr;
    static int by_sm = 0;
    static Scratch* scr = nullptr;
    if (!fn) {
        void* p = nullptr; cudaDriverEntryPointQueryResult q;
        cudaGetDriverEntryPoint("cuTensorMapEncodeTiled", &p, cudaEnableDefault, &q);
        fn = (EncodeFn)p;
        cudaFuncSetAttribute(fused_kernel, cudaFuncAttributeMaxDynamicSharedMemorySize, SMEM_LAUNCH);
        cudaGetSymbolAddress((void**)&scr, g_scr);
        int dev = 0, sms = 0;
        cudaGetDevice(&dev);
        cudaDeviceGetAttribute(&sms, cudaDevAttrMultiProcessorCount, dev);
        by_sm = sms == 132;
    }
    Roles roles;
    for (int i = 0; i < 132; i++) {
        const int T = i >> 1, T8 = T < 32 ? T : T + 1 + (T - 32) / 7, fb = (T < 60 ? (~T8 & 7) * 8 + (T8 >> 3) : T < 62 ? T + 4 : T - 2) * 2 + (i & 1);
        roles.v[i] = fb | ((fb & ~31) | (fb & 1) << 4 | (fb & 31) >> 1) << 8;
    }
    const cuuint64_t xd[4] = {2048, 16, 32, 2}, xs[3] = {4096, 131072, 65536};
    const cuuint32_t xb[4] = {64, 16, 4, 2};
    const cuuint64_t wdm[3] = {1024, 1024, 3}, wst[2] = {6144, 2048};
    const cuuint32_t wb[3] = {64, 64, 3};
    const cuuint64_t od[4] = {64, 64, 16, 16}, ost[3] = {2048, 131072, 128};
    const cuuint32_t ob[4] = {64, 8, 16, 2};
    const cuuint64_t yd[2] = {2048, 1024}, yst[1] = {4096};
    const cuuint32_t yb[2] = {64, 16};
    const cuuint64_t sd[3] = {64, 1024, 32}, sst[2] = {4096, 128};
    const cuuint32_t sbx[3] = {64, 16, 4};
    CUtensorMap mxs = make_map(fn, x, 3, sd, sst, sbx);
    const cuuint64_t cd[3] = {3072, 64, 16}, cst[2] = {6144, 393216};
    const cuuint32_t cbx[3] = {64, 8, 2};
    CUtensorMap mcs = make_map(fn, wqkv, 3, cd, cst, cbx, CU_TENSOR_MAP_SWIZZLE_NONE);
    CUtensorMap mx = make_map(fn, x, 4, xd, xs, xb), mw = make_map(fn, wqkv, 3, wdm, wst, wb);
    CUtensorMap mwo = make_map(fn, wo, 4, od, ost, ob), mout = make_map(fn, d_out, 2, yd, yst, yb);
    const cuuint64_t gd[3] = {3584, 1024, 2}, gst[2] = {7168, (cuuint64_t)(wu < wg ? wg - wu : wu - wg)};
    const cuuint32_t gb[3] = {32, 128, 2};
    const cuuint64_t dd[2] = {1024, 3584}, dst[1] = {2048};
    const cuuint32_t db[2] = {64, 64};
    CUtensorMap mgu = make_map(fn, wu < wg ? wu : wg, 3, gd, gst, gb, CU_TENSOR_MAP_SWIZZLE_64B, CU_TENSOR_MAP_L2_PROMOTION_L2_128B);
    CUtensorMap mwd = make_map(fn, wd, 2, dd, dst, db, CU_TENSOR_MAP_SWIZZLE_128B, CU_TENSOR_MAP_L2_PROMOTION_L2_128B);
    fused_kernel<<<132, 512, SMEM_LAUNCH, cudaStreamPerThread>>>(by_sm, x, wqkv, wr, scr, wg, wu, wd, wo, roles, mw, mx, mwo, mxs, mcs, mout, mgu, mwd);
}
```

```cpp
#include <cuda_runtime.h>
#include <cuda.h>
#include <cuda_bf16.h>
#include <stdint.h>

namespace {

constexpr int STAGE = 57344;
constexpr int OFF_FW = 3 * STAGE;
constexpr int OFF_FA = OFF_FW + 49152;
constexpr int OFF_CS = OFF_FA + 6144;
constexpr int OFF_STAT = OFF_CS + 1232;
constexpr int OFF_ROWMAP = OFF_STAT + 2112;
constexpr int OFF_TAG = OFF_ROWMAP + 128;
constexpr int OFF_BAR = OFF_TAG + 8;
constexpr int OFF_F2X = 16384, OFF_HALO = 24576, OFF_O1 = 24576, OFF_O0 = 73728, OFF_WO = 106496, NWO = 3, OFF_MEAN = 2 * STAGE, OFF_X1 = 2 * STAGE + 8192;
static_assert(OFF_WO + NWO * 32768 <= OFF_FA && OFF_O0 + 32768 == OFF_WO && OFF_O1 + 32768 == STAGE, "alias");
constexpr int B_FULLA = 0, B_FULLB = 3, B_ROW = 6, B_FFULL = 11, B_FEMPTY = 14, B_F2DONE = 17, B_GO = 18, B_SW = 19, B_CS = 20, B_WOFULL = 26, B_OFULL = B_WOFULL + 8,
              B_DONE = B_OFULL + 16;
constexpr int B_EMPTY = B_DONE + 16, B_XR = B_EMPTY + 3, B_G1DONE = B_XR + 1;
constexpr int B_UPD = B_G1DONE + 1, B_F2FULL = B_UPD + 1;
constexpr int B_AUX = B_F2FULL + 1, B_PART = B_AUX + 1, B_ATT = B_PART + 1, B_CSDONE = B_ATT + 1, B_AST = B_CSDONE + 1, NBAR = B_AST + 1;
constexpr int SMEM_BYTES = OFF_BAR + NBAR * 8;
static_assert(SMEM_BYTES <= 232448 && OFF_BAR % 8 == 0, "smem");
#define P_PART 13
#define F1_MASK (0x6a005a00u >> (14 - P_PART))
#define PF_CNT 0x2aaaaacu
#define EARLY_FILL 2
#define N_S1 1
#define N_S2 3
#define ST_A 2
#define ST_B 4
#define DBG_F2 1
#define DBG_F1 1
#define DBG_XR 1
#define T_H 150
#define T_O1 250
#define WO1_GATE B_GO
#define ST_C 5
#define T_O 1900
#define T_S1 128
#define T_GO 256
#define T_S2 950
#define DBG_CS 0
#define DBG_ST 0
#define N_GA 4
#define N_X 1
#define D_X 2
#define D_R 3
#define N_ROW 5
#define N_W 5
#define K_W1 5
#define K_W2 10
#define N_CS 3
#define N_F1 4
#define LAST 2
#define HOLD 1
#define HOLD_DEP 0
#define HOLD_ALL 0
#define PRE_F 1
#define N_HA 0
#define POLL_NS 100
#define STATS_UNROLL 4
constexpr int kStatsUnroll = STATS_UNROLL;
constexpr int SPIN_LIMIT = 1 << 18;

struct Scratch {
    uint8_t o[2048 * 1024 * 2];
    uint2 rec[2048];
    float cs[8][3072];
    uint32_t halo[128][512];
    uint32_t h[14336];
    float ypart[8][8][1024];
    uint2 sel[16];
    uint32_t hint[128][8];
    uint32_t epoch;
};
__device__ __align__(1024) Scratch g_scr;

#define TS(i) do {} while (0)
#define TS_END() do {} while (0)
constexpr int SMEM_LAUNCH = SMEM_BYTES;
#define TSC(c, i) do {} while (0)
#define NRETRY() do {} while (0)
__device__ __forceinline__ uint32_t smem_u32(const void* p) { return (uint32_t)__cvta_generic_to_shared(p); }
__device__ __forceinline__ void mbar_init(uint32_t bar, uint32_t cnt) { asm volatile("mbarrier.init.shared::cta.b64 [%0], %1;" ::"r"(bar), "r"(cnt) : "memory"); }
__device__ __forceinline__ void mbar_expect_tx(uint32_t bar, uint32_t bytes) { asm volatile("mbarrier.arrive.expect_tx.shared::cta.b64 _, [%0], %1;" ::"r"(bar), "r"(bytes) : "memory"); }
__device__ __forceinline__ void mbar_arrive(uint32_t bar) { asm volatile("mbarrier.arrive.shared::cta.b64 _, [%0];" ::"r"(bar) : "memory"); }
__device__ __forceinline__ void mbar_arrive_after(uint32_t bar, uint32_t lane, uint32_t dep) {
    asm volatile("{\n.reg .pred p;\n.reg .b32 t;\nsetp.eq.u32 p, %1, 0;\nmad.lo.u32 t, %1, %2, %0;\n@p mbarrier.arrive.shared::cta.b64 _, [t];\n}" ::"r"(bar), "r"(lane), "r"(dep) : "memory");
}
__device__ __forceinline__ void mbar_wait(uint32_t bar, uint32_t parity) {
    asm volatile("{\n.reg .pred P1;\nLAB_WAIT:\nmbarrier.try_wait.parity.shared::cta.b64 P1, [%0], %1;\n@!P1 bra LAB_WAIT;\n}" ::"r"(bar), "r"(parity) : "memory");
}
__device__ __forceinline__ bool mbar_test(uint32_t bar, uint32_t parity) {
    uint32_t ok;
    asm volatile("{\n.reg .pred p;\nmbarrier.test_wait.parity.shared::cta.b64 p, [%1], %2;\nselp.u32 %0, 1, 0, p;\n}" : "=r"(ok) : "r"(bar), "r"(parity) : "memory");
    return ok;
}
__device__ __forceinline__ void tma_2d(uint32_t dst, const CUtensorMap* m, uint32_t bar, int c0, int c1) {
    asm volatile("cp.async.bulk.tensor.2d.shared::cluster.global.mbarrier::complete_tx::bytes [%0], [%1, {%3, %4}], [%2];" ::"r"(dst), "l"(m), "r"(bar), "r"(c0), "r"(c1) : "memory");
}
__device__ __forceinline__ void tma_3d(uint32_t dst, const CUtensorMap* m, uint32_t bar, int c0, int c1, int c2) {
    asm volatile("cp.async.bulk.tensor.3d.shared::cluster.global.mbarrier::complete_tx::bytes [%0], [%1, {%3, %4, %5}], [%2];" ::"r"(dst), "l"(m), "r"(bar), "r"(c0), "r"(c1), "r"(c2) : "memory");
}
__device__ __forceinline__ void tma_2d_once(uint32_t dst, const CUtensorMap* m, uint32_t bar, int c0, int c1) {
    asm volatile("cp.async.bulk.tensor.2d.shared::cluster.global.mbarrier::complete_tx::bytes.L2::cache_hint [%0], [%1, {%3, %4}], [%2], %5;" ::"r"(dst), "l"(m), "r"(bar), "r"(c0), "r"(c1), "l"(0x12F0000000000000ull) : "memory");
}
__device__ __forceinline__ void tma_3d_once(uint32_t dst, const CUtensorMap* m, uint32_t bar, int c0, int c1, int c2) {
    asm volatile("cp.async.bulk.tensor.3d.shared::cluster.global.mbarrier::complete_tx::bytes.L2::cache_hint [%0], [%1, {%3, %4, %5}], [%2], %6;" ::"r"(dst), "l"(m), "r"(bar), "r"(c0), "r"(c1), "r"(c2), "l"(0x12F0000000000000ull) : "memory");
}
__device__ __forceinline__ void tma_4d(uint32_t dst, const CUtensorMap* m, uint32_t bar, int c0, int c1, int c2, int c3) {
    asm volatile("cp.async.bulk.tensor.4d.shared::cluster.global.mbarrier::complete_tx::bytes [%0], [%1, {%3, %4, %5, %6}], [%2];" ::"r"(dst), "l"(m), "r"(bar), "r"(c0), "r"(c1), "r"(c2), "r"(c3) : "memory");
}
__device__ __forceinline__ void tma_store_2d(const CUtensorMap* m, uint32_t src, int c0, int c1) {
    asm volatile("cp.async.bulk.tensor.2d.global.shared::cta.bulk_group [%0, {%2, %3}], [%1];" ::"l"(m), "r"(src), "r"(c0), "r"(c1) : "memory");
}
__device__ __forceinline__ void bulk_g2s(uint32_t dst, const void* src, uint32_t bytes, uint32_t bar) {
    asm volatile("cp.async.bulk.shared::cluster.global.mbarrier::complete_tx::bytes [%0], [%1], %2, [%3];" ::"r"(dst), "l"(src), "r"(bytes), "r"(bar) : "memory");
}
__device__ __forceinline__ void bulk_prefetch(const void* p, uint32_t bytes) { asm volatile("cp.async.bulk.prefetch.L2.global [%0], %1;" ::"l"(p), "r"(bytes) : "memory"); }
__device__ __forceinline__ void fence_async_smem() { asm volatile("fence.proxy.async.shared::cta;" ::: "memory"); }
__device__ __forceinline__ void wg_fence() { asm volatile("wgmma.fence.sync.aligned;" ::: "memory"); }
__device__ __forceinline__ void wg_commit() { asm volatile("wgmma.commit_group.sync.aligned;" ::: "memory"); }
template <int N> __device__ __forceinline__ void wg_wait() { asm volatile("wgmma.wait_group.sync.aligned %0;" ::"n"(N) : "memory"); }
__device__ __forceinline__ uint64_t mkdesc(uint32_t lo, uint32_t hi) { return ((uint64_t)hi << 32) | lo; }
__host__ __device__ constexpr uint32_t dhi(uint32_t sbo, uint32_t mode) { return (sbo >> 4) | (mode << 30); }
__host__ __device__ constexpr uint32_t dlo(uint32_t off, uint32_t lbo) { return (off >> 4) + ((lbo >> 4) << 16); }
__device__ __forceinline__ bool elect_one() {
    uint32_t e;
    asm volatile("{\n.reg .pred p;\nelect.sync _|p, 0xffffffff;\nselp.u32 %0, 1, 0, p;\n}" : "=r"(e));
    return e;
}
template <int R> __device__ __forceinline__ void reg_inc() { asm volatile("setmaxnreg.inc.sync.aligned.u32 %0;" ::"n"(R)); }
template <int R> __device__ __forceinline__ void reg_dec() { asm volatile("setmaxnreg.dec.sync.aligned.u32 %0;" ::"n"(R)); }
__device__ __forceinline__ void bar_sync(int id, int n) { asm volatile("bar.sync %0, %1;" ::"r"(id), "r"(n) : "memory"); }
__device__ __forceinline__ void bar_arrive(int id, int n) { asm volatile("bar.arrive %0, %1;" ::"r"(id), "r"(n) : "memory"); }
__device__ __forceinline__ uint32_t pack_bf16(float lo, float hi) { uint32_t r; asm("cvt.rn.bf16x2.f32 %0, %1, %2;" : "=r"(r) : "f"(hi), "f"(lo)); return r; }
__device__ __forceinline__ float bf_lo(uint32_t u) { return __uint_as_float(u << 16); }
__device__ __forceinline__ float bf_hi(uint32_t u) { return __uint_as_float(u & 0xffff0000u); }
__device__ __forceinline__ float bf16r(float v) { return bf_lo(pack_bf16(v, 0.f)); }
__device__ __forceinline__ uint32_t tagw(uint32_t w, uint32_t m, uint32_t tag) { uint32_t r; asm("lop3.b32 %0, %1, %2, %3, 0xb8;" : "=r"(r) : "r"(w), "r"(m), "r"(tag)); return r; }
__device__ __forceinline__ uint32_t tagf(float f, uint32_t tag) { return tagw(__float_as_uint(f), 1u, tag); }
__device__ __forceinline__ uint32_t movm(uint32_t a) { uint32_t d; asm volatile("movmatrix.sync.aligned.m8n8.trans.b16 %0, %1;" : "=r"(d) : "r"(a)); return d; }
__device__ __forceinline__ void mma16816(float (&c)[4], uint32_t a0, uint32_t a1, uint32_t a2, uint32_t a3, uint32_t b0, uint32_t b1) {
    asm volatile("mma.sync.aligned.m16n8k16.row.col.f32.bf16.bf16.f32 {%0,%1,%2,%3}, {%4,%5,%6,%7}, {%8,%9}, {%0,%1,%2,%3};"
                 : "+f"(c[0]), "+f"(c[1]), "+f"(c[2]), "+f"(c[3]) : "r"(a0), "r"(a1), "r"(a2), "r"(a3), "r"(b0), "r"(b1));
}
__device__ __forceinline__ void mma1688(float (&c)[4], uint32_t a0, uint32_t a1, uint32_t b0) {
    asm volatile("mma.sync.aligned.m16n8k8.row.col.f32.bf16.bf16.f32 {%0,%1,%2,%3}, {%4,%5}, {%6}, {%0,%1,%2,%3};"
                 : "+f"(c[0]), "+f"(c[1]), "+f"(c[2]), "+f"(c[3]) : "r"(a0), "r"(a1), "r"(b0));
}
__device__ __forceinline__ uint32_t ld_rlx(const void* p) { uint32_t v; asm volatile("ld.relaxed.gpu.global.u32 %0, [%1];" : "=r"(v) : "l"(p) : "memory"); return v; }
__device__ __forceinline__ uint2 ld_rlx2(const void* p) { uint2 v; asm volatile("ld.relaxed.gpu.global.v2.u32 {%0,%1}, [%2];" : "=r"(v.x), "=r"(v.y) : "l"(p) : "memory"); return v; }
__device__ __forceinline__ uint4 ld_rlx4(const void* p) { uint4 v; asm volatile("ld.relaxed.gpu.global.v4.u32 {%0,%1,%2,%3}, [%4];" : "=r"(v.x), "=r"(v.y), "=r"(v.z), "=r"(v.w) : "l"(p) : "memory"); return v; }
__device__ __forceinline__ uint32_t ld_acq(const void* p) { uint32_t v; asm volatile("ld.acquire.gpu.global.u32 %0, [%1];" : "=r"(v) : "l"(p) : "memory"); return v; }
__device__ __forceinline__ void st_rlx(void* p, uint32_t v) { asm volatile("st.relaxed.gpu.global.u32 [%0], %1;" ::"l"(p), "r"(v) : "memory"); }
__device__ __forceinline__ void st_rlx2(void* p, uint32_t a, uint32_t b) { asm volatile("st.relaxed.gpu.global.v2.u32 [%0], {%1,%2};" ::"l"(p), "r"(a), "r"(b) : "memory"); }
__device__ __forceinline__ void st_rlx4(void* p, uint32_t a, uint32_t b, uint32_t c, uint32_t d) { asm volatile("st.relaxed.gpu.global.v4.u32 [%0], {%1,%2,%3,%4};" ::"l"(p), "r"(a), "r"(b), "r"(c), "r"(d) : "memory"); }
__device__ __forceinline__ uint4 ldg_nc(const void* p) { uint4 v; asm volatile("ld.global.nc.v4.u32 {%0,%1,%2,%3}, [%4];" : "=r"(v.x), "=r"(v.y), "=r"(v.z), "=r"(v.w) : "l"(p)); return v; }
__device__ __forceinline__ uint32_t mism(uint32_t a, uint32_t b, uint32_t tag) { uint32_t r; asm("lop3.b32 %0, %1, %2, %3, 0x7e;" : "=r"(r) : "r"(a), "r"(b), "r"(tag)); return r; }
__device__ __forceinline__ uint32_t mism(const uint4& v, uint32_t tag) { return mism(v.x, v.y, tag) | mism(v.z, v.w, tag); }
__device__ __forceinline__ void prefetch_l2(const void* p) { asm volatile("prefetch.global.L2 [%0];" ::"l"(p)); }
__device__ __forceinline__ void touch256(uint32_t dst, const void* p) { asm volatile("cp.async.ca.shared.global.L2::256B [%0], [%1], 4;" ::"r"(dst), "l"(p) : "memory"); }
__device__ __forceinline__ void nap(int n) {
#pragma unroll 1
    for (int i = 0; i < n; i++) __nanosleep(100);
}
__device__ __forceinline__ uint32_t now() { uint32_t t; asm volatile("mov.u32 %0, %%globaltimer_lo;" : "=r"(t)); return t; }
__device__ __forceinline__ void until(uint32_t t) {
    while (t - now() - 1 < 16384u) __nanosleep(50);
}
__device__ __forceinline__ uint32_t opaque(uint32_t v) { return __shfl_xor_sync(0xffffffffu, v, 0); }
__device__ __forceinline__ void sts4(uint32_t a, uint32_t x, uint32_t y, uint32_t z, uint32_t w) { asm volatile("st.shared.v4.u32 [%0], {%1,%2,%3,%4};" ::"r"(a), "r"(x), "r"(y), "r"(z), "r"(w) : "memory"); }
__device__ __forceinline__ void sts2(uint32_t a, uint32_t x, uint32_t y) { asm volatile("st.shared.v2.u32 [%0], {%1,%2};" ::"r"(a), "r"(x), "r"(y) : "memory"); }
__device__ __forceinline__ uint4 lds4(uint32_t a) { uint4 v; asm volatile("ld.shared.v4.u32 {%0,%1,%2,%3}, [%4];" : "=r"(v.x), "=r"(v.y), "=r"(v.z), "=r"(v.w) : "r"(a) : "memory"); return v; }
__device__ __forceinline__ float4 lds4f(uint32_t a) { float4 v; asm volatile("ld.shared.v4.f32 {%0,%1,%2,%3}, [%4];" : "=f"(v.x), "=f"(v.y), "=f"(v.z), "=f"(v.w) : "r"(a) : "memory"); return v; }
__device__ __forceinline__ uint2 lds2(uint32_t a) { uint2 v; asm volatile("ld.shared.v2.u32 {%0,%1}, [%2];" : "=r"(v.x), "=r"(v.y) : "r"(a) : "memory"); return v; }
__device__ __forceinline__ float2 lds2f(uint32_t a) { float2 v; asm volatile("ld.shared.v2.f32 {%0,%1}, [%2];" : "=f"(v.x), "=f"(v.y) : "r"(a) : "memory"); return v; }
__device__ __forceinline__ uint32_t lds1(uint32_t a) { uint32_t v; asm volatile("ld.shared.u32 %0, [%1];" : "=r"(v) : "r"(a) : "memory"); return v; }
__device__ __forceinline__ float lds1f(uint32_t a) { return __uint_as_float(lds1(a)); }
__device__ __forceinline__ void sts1(uint32_t a, uint32_t v) { asm volatile("st.shared.u32 [%0], %1;" ::"r"(a), "r"(v) : "memory"); }
__device__ __forceinline__ uint32_t redux_max(uint32_t v) { uint32_t r; asm volatile("redux.sync.max.u32 %0, %1, 0xffffffff;" : "=r"(r) : "r"(v)); return r; }
__device__ __forceinline__ float ex2(float x) { float r; asm("ex2.approx.ftz.f32 %0, %1;" : "=f"(r) : "f"(x)); return r; }
__device__ __forceinline__ float rcp(float x) { float r; asm("rcp.approx.ftz.f32 %0, %1;" : "=f"(r) : "f"(x)); return r; }
__device__ __forceinline__ float sigmoidf(float v) { return rcp(1.f + ex2(v * -1.4426950408889634f)); }

template <int TA, int TB>
__device__ __forceinline__ void wgmma_n192(float (&d)[96], uint64_t da, uint64_t db, int acc = 1) {
    asm volatile("{\n.reg .pred p;\nsetp.ne.b32 p, %100, 0;\n"
        "wgmma.mma_async.sync.aligned.m64n192k16.f32.bf16.bf16 "
        "{%0, %1, %2, %3, %4, %5, %6, %7, %8, %9, %10, %11, %12, %13, %14, %15, "
        "%16, %17, %18, %19, %20, %21, %22, %23, %24, %25, %26, %27, %28, %29, %30, %31, "
        "%32, %33, %34, %35, %36, %37, %38, %39, %40, %41, %42, %43, %44, %45, %46, %47, "
        "%48, %49, %50, %51, %52, %53, %54, %55, %56, %57, %58, %59, %60, %61, %62, %63, "
        "%64, %65, %66, %67, %68, %69, %70, %71, %72, %73, %74, %75, %76, %77, %78, %79, "
        "%80, %81, %82, %83, %84, %85, %86, %87, %88, %89, %90, %91, %92, %93, %94, %95}, "
        "%96, %97, p, 1, 1, %98, %99;\n}\n"
        : "+f"(d[0]), "+f"(d[1]), "+f"(d[2]), "+f"(d[3]), "+f"(d[4]), "+f"(d[5]), "+f"(d[6]), "+f"(d[7]),
          "+f"(d[8]), "+f"(d[9]), "+f"(d[10]), "+f"(d[11]), "+f"(d[12]), "+f"(d[13]), "+f"(d[14]), "+f"(d[15]),
          "+f"(d[16]), "+f"(d[17]), "+f"(d[18]), "+f"(d[19]), "+f"(d[20]), "+f"(d[21]), "+f"(d[22]), "+f"(d[23]),
          "+f"(d[24]), "+f"(d[25]), "+f"(d[26]), "+f"(d[27]), "+f"(d[28]), "+f"(d[29]), "+f"(d[30]), "+f"(d[31]),
          "+f"(d[32]), "+f"(d[33]), "+f"(d[34]), "+f"(d[35]), "+f"(d[36]), "+f"(d[37]), "+f"(d[38]), "+f"(d[39]),
          "+f"(d[40]), "+f"(d[41]), "+f"(d[42]), "+f"(d[43]), "+f"(d[44]), "+f"(d[45]), "+f"(d[46]), "+f"(d[47]),
          "+f"(d[48]), "+f"(d[49]), "+f"(d[50]), "+f"(d[51]), "+f"(d[52]), "+f"(d[53]), "+f"(d[54]), "+f"(d[55]),
          "+f"(d[56]), "+f"(d[57]), "+f"(d[58]), "+f"(d[59]), "+f"(d[60]), "+f"(d[61]), "+f"(d[62]), "+f"(d[63]),
          "+f"(d[64]), "+f"(d[65]), "+f"(d[66]), "+f"(d[67]), "+f"(d[68]), "+f"(d[69]), "+f"(d[70]), "+f"(d[71]),
          "+f"(d[72]), "+f"(d[73]), "+f"(d[74]), "+f"(d[75]), "+f"(d[76]), "+f"(d[77]), "+f"(d[78]), "+f"(d[79]),
          "+f"(d[80]), "+f"(d[81]), "+f"(d[82]), "+f"(d[83]), "+f"(d[84]), "+f"(d[85]), "+f"(d[86]), "+f"(d[87]),
          "+f"(d[88]), "+f"(d[89]), "+f"(d[90]), "+f"(d[91]), "+f"(d[92]), "+f"(d[93]), "+f"(d[94]), "+f"(d[95])
        : "l"(da), "l"(db), "n"(TA), "n"(TB), "r"(acc));
}
template <int TA, int TB>
__device__ __forceinline__ void wgmma_n128(float (&d)[64], uint64_t da, uint64_t db, int acc = 1) {
    asm volatile("{\n.reg .pred p;\nsetp.ne.b32 p, %68, 0;\n"
        "wgmma.mma_async.sync.aligned.m64n128k16.f32.bf16.bf16 "
        "{%0, %1, %2, %3, %4, %5, %6, %7, %8, %9, %10, %11, %12, %13, %14, %15, "
        "%16, %17, %18, %19, %20, %21, %22, %23, %24, %25, %26, %27, %28, %29, %30, %31, "
        "%32, %33, %34, %35, %36, %37, %38, %39, %40, %41, %42, %43, %44, %45, %46, %47, "
        "%48, %49, %50, %51, %52, %53, %54, %55, %56, %57, %58, %59, %60, %61, %62, %63}, "
        "%64, %65, p, 1, 1, %66, %67;\n}\n"
        : "+f"(d[0]), "+f"(d[1]), "+f"(d[2]), "+f"(d[3]), "+f"(d[4]), "+f"(d[5]), "+f"(d[6]), "+f"(d[7]),
          "+f"(d[8]), "+f"(d[9]), "+f"(d[10]), "+f"(d[11]), "+f"(d[12]), "+f"(d[13]), "+f"(d[14]), "+f"(d[15]),
          "+f"(d[16]), "+f"(d[17]), "+f"(d[18]), "+f"(d[19]), "+f"(d[20]), "+f"(d[21]), "+f"(d[22]), "+f"(d[23]),
          "+f"(d[24]), "+f"(d[25]), "+f"(d[26]), "+f"(d[27]), "+f"(d[28]), "+f"(d[29]), "+f"(d[30]), "+f"(d[31]),
          "+f"(d[32]), "+f"(d[33]), "+f"(d[34]), "+f"(d[35]), "+f"(d[36]), "+f"(d[37]), "+f"(d[38]), "+f"(d[39]),
          "+f"(d[40]), "+f"(d[41]), "+f"(d[42]), "+f"(d[43]), "+f"(d[44]), "+f"(d[45]), "+f"(d[46]), "+f"(d[47]),
          "+f"(d[48]), "+f"(d[49]), "+f"(d[50]), "+f"(d[51]), "+f"(d[52]), "+f"(d[53]), "+f"(d[54]), "+f"(d[55]),
          "+f"(d[56]), "+f"(d[57]), "+f"(d[58]), "+f"(d[59]), "+f"(d[60]), "+f"(d[61]), "+f"(d[62]), "+f"(d[63])
        : "l"(da), "l"(db), "n"(TA), "n"(TB), "r"(acc));
}
template <int TB>
__device__ __forceinline__ void wgmma_rs_n128(float (&d)[64], uint32_t a0, uint32_t a1, uint32_t a2, uint32_t a3, uint64_t db) {
    asm volatile("{\n.reg .pred p;\nsetp.ne.b32 p, 1, 0;\n"
        "wgmma.mma_async.sync.aligned.m64n128k16.f32.bf16.bf16 "
        "{%0, %1, %2, %3, %4, %5, %6, %7, %8, %9, %10, %11, %12, %13, %14, %15, "
        "%16, %17, %18, %19, %20, %21, %22, %23, %24, %25, %26, %27, %28, %29, %30, %31, "
        "%32, %33, %34, %35, %36, %37, %38, %39, %40, %41, %42, %43, %44, %45, %46, %47, "
        "%48, %49, %50, %51, %52, %53, %54, %55, %56, %57, %58, %59, %60, %61, %62, %63}, "
        "{%64, %65, %66, %67}, %68, p, 1, 1, %69;\n}\n"
        : "+f"(d[0]), "+f"(d[1]), "+f"(d[2]), "+f"(d[3]), "+f"(d[4]), "+f"(d[5]), "+f"(d[6]), "+f"(d[7]),
          "+f"(d[8]), "+f"(d[9]), "+f"(d[10]), "+f"(d[11]), "+f"(d[12]), "+f"(d[13]), "+f"(d[14]), "+f"(d[15]),
          "+f"(d[16]), "+f"(d[17]), "+f"(d[18]), "+f"(d[19]), "+f"(d[20]), "+f"(d[21]), "+f"(d[22]), "+f"(d[23]),
          "+f"(d[24]), "+f"(d[25]), "+f"(d[26]), "+f"(d[27]), "+f"(d[28]), "+f"(d[29]), "+f"(d[30]), "+f"(d[31]),
          "+f"(d[32]), "+f"(d[33]), "+f"(d[34]), "+f"(d[35]), "+f"(d[36]), "+f"(d[37]), "+f"(d[38]), "+f"(d[39]),
          "+f"(d[40]), "+f"(d[41]), "+f"(d[42]), "+f"(d[43]), "+f"(d[44]), "+f"(d[45]), "+f"(d[46]), "+f"(d[47]),
          "+f"(d[48]), "+f"(d[49]), "+f"(d[50]), "+f"(d[51]), "+f"(d[52]), "+f"(d[53]), "+f"(d[54]), "+f"(d[55]),
          "+f"(d[56]), "+f"(d[57]), "+f"(d[58]), "+f"(d[59]), "+f"(d[60]), "+f"(d[61]), "+f"(d[62]), "+f"(d[63])
        : "r"(a0), "r"(a1), "r"(a2), "r"(a3), "l"(db), "n"(TB));
}
template <int TA, int TB>
__device__ __forceinline__ void wgmma_n8(float (&d)[4], uint64_t da, uint64_t db, int acc = 1) {
    asm volatile("{\n.reg .pred p;\nsetp.ne.b32 p, %8, 0;\n"
        "wgmma.mma_async.sync.aligned.m64n8k16.f32.bf16.bf16 "
        "{%0, %1, %2, %3}, "
        "%4, %5, p, 1, 1, %6, %7;\n}\n"
        : "+f"(d[0]), "+f"(d[1]), "+f"(d[2]), "+f"(d[3])
        : "l"(da), "l"(db), "n"(TA), "n"(TB), "r"(acc));
}

__device__ __forceinline__ uint32_t norm_pair(uint32_t u, float m, float rinv) {
    uint32_t d = pack_bf16(bf_lo(u) - m, bf_hi(u) - m);
    return pack_bf16(bf_lo(d) * rinv, bf_hi(d) * rinv);
}

struct Roles { uint16_t v[132]; };

__global__ void __launch_bounds__(512, 1)
fused_kernel(int by_sm, const __nv_bfloat16* __restrict__ x, const __nv_bfloat16* __restrict__ wqkv, const __nv_bfloat16* __restrict__ wr,
             Scratch* const S, const char* __restrict__ wg, const char* __restrict__ wu, const char* __restrict__ wd, const char* __restrict__ wo,
             const __grid_constant__ Roles roles,
             const __grid_constant__ CUtensorMap mw, const __grid_constant__ CUtensorMap mx, const __grid_constant__ CUtensorMap mwo,
             const __grid_constant__ CUtensorMap mxs, const __grid_constant__ CUtensorMap mcs, const __grid_constant__ CUtensorMap mout, const __grid_constant__ CUtensorMap mgu, const __grid_constant__ CUtensorMap mwd) {
    extern __shared__ __align__(1024) uint8_t smem[];
    constexpr uint32_t sb = 1024, bars = sb + OFF_BAR, sd = sb >> 4;
    const int tid = threadIdx.x, lane = tid & 31;
    asm volatile("{\n.reg .pred p, q;\nsetp.lt.u32 p, %2, 16;\nsetp.lt.u32 q, %2, 24;\n@p prefetch.global.L2 [%0];\n@p prefetch.global.L2 [%0 + 128];\n@q prefetch.global.L2 [%1];\n}" ::
                 "l"((const char*)x + (blockIdx.x * 16 + tid - 32) % 2048 * 2048), "l"((const char*)wqkv + (blockIdx.x * 24 + tid - 32) * 128), "r"(tid - 32));
    const int warp = __shfl_sync(0xffffffffu, tid >> 5, 0);
    uint32_t smid;
    asm volatile("mov.u32 %0, %%smid;" : "=r"(smid));
    const int role = roles.v[by_sm ? smid : blockIdx.x], fb = role & 255, b = role >> 8, kc = fb >> 4, c2 = fb & 15;
    const int mt = b >> 4, nt = b & 15, hp = b & 1, cb = nt >> 1;
    const int par = mt >> 2, j0 = (mt & 3) * 256;
    uint8_t* const g_o = S->o;

    auto load_stage = [&](int p, uint32_t so, int bi) {
        const uint32_t fullA = bars + 8 * (B_FULLA + bi), fullB = bars + 8 * (B_FULLB + bi);
        mbar_expect_tx(fullA, 40960);
        tma_3d(sb + so + 16384, &mw, fullA, nt * 64, p * 64, 0);
        tma_4d(sb + so, &mx, fullA, par * 1024 + p * 64, 0, (j0 >> 5) + 4, 0);
        mbar_expect_tx(fullB, 16384);
        tma_4d(sb + so + 40960, &mx, fullB, par * 1024 + p * 64, 0, j0 >> 5, 0);
    };
    if (warp == 0 && fb < 128 && elect_one()) {
        mbar_init(bars + 8 * B_FULLA, 1); mbar_init(bars + 8 * B_FULLB, 1);
        load_stage(0, STAGE, 0);
    }
    if (fb >= 128) {
        if (fb > 128) { nap(16); TS_END(); return; }
        const uint32_t tag = (ld_rlx(&S->epoch) & 1) - 1;
        if (tid < 8) st_rlx2(&S->sel[tid], ~tag, ~tag);
        uint4 ra, rb;
#pragma unroll 1
        for (int it = 0; it < SPIN_LIMIT; it++) {
            ra = ld_rlx4(&S->rec[tid * 2]); rb = ld_rlx4(&S->rec[1024 + tid * 2]);
            if (!__any_sync(0xffffffffu, (mism(ra.x, ra.z, tag) | mism(rb.x, rb.z, tag)) & 0x8000u)) break;
        }
        __syncwarp();
        TSC(tid == 0, 31);
        sts4(sb + 1024 + tid * 16, ra.y, rb.y, ra.w, rb.w);
        uint4 k = make_uint4(ra.x, ra.z, rb.x, rb.z);
        uint32_t cand;
#pragma unroll 1
        for (int pass = 0; pass < 2; pass++) {
            const uint32_t a0 = max(k.x, k.y), a1 = min(k.x, k.y), a2 = max(k.z, k.w), a3 = min(k.z, k.w), c1 = min(a0, a2), c2 = max(a1, a3);
            k = make_uint4(max(a0, a2), max(c1, c2), min(c1, c2), min(a1, a3));
#pragma unroll
            for (int r = 0; r < 8; r++) {
                const uint32_t m = redux_max(k.x);
                if (lane == r) cand = m;
                if (k.x == m) k = make_uint4(k.y, k.z, k.w, 0);
            }
            if (pass) break;
            if (lane < 8) sts1(sb + (warp * 8 + lane) * 4, cand);
            __syncthreads();
            if (warp) { TS_END(); return; }
            k = lds4(sb + lane * 16);
            TSC(TIMING == 12 && tid == 0 && k.x != 0x12345, 40);
        }
        if (lane < 8) st_rlx2(&S->sel[lane], cand, lds1(sb + 1024 + (~cand & 0x7ffu) * 4));
        TSC(tid == 0, 20);
        TS_END();
        return;
    }
    uint32_t epoch;
    if (warp >> 2 == 2) epoch = ld_rlx(&S->epoch);
    if (warp == 1 && elect_one()) {
#pragma unroll
        for (int i = 0; i < B_WOFULL; i++)
            if (i != B_FULLA && i != B_FULLB) mbar_init(bars + 8 * i, i >= B_FFULL && i < B_FEMPTY ? 5 : 1);
    }
    if (warp == 4 && elect_one()) {
#pragma unroll
        for (int i = B_EMPTY; i < NBAR; i++) mbar_init(bars + 8 * i, i < B_UPD ? 2 : i < B_AUX ? 4 : i == B_AUX ? 7 : i == B_CSDONE ? 3 : 8);
    }
    __syncthreads();

    if (warp >= 12) {
        reg_dec<24>();
        if (warp > 12) {
            const int p = warp - 13;
            if (p == 1) {
                float sw = 0.f;
                mbar_wait(bars + 8 * (B_ROW + 4), 0);
#pragma unroll 1
                for (int i = 0; i < 16; i++) { const uint32_t q = lds1(sb + OFF_FA + i * 128 + lane * 4); sw += bf_lo(q) + bf_hi(q); }
#pragma unroll 1
                for (int o = 1; o < 32; o <<= 1) sw += __shfl_xor_sync(0xffffffffu, sw, o);
                if (lane == 0) { sts1(sb + OFF_TAG + 4, __float_as_uint(sw)); mbar_arrive(bars + 8 * B_SW); }
            } else {
#pragma unroll 1
                for (int q = 0; q < 4; q++) {
                    nap(p ? (q ? D_R : N_ROW) : (q ? D_X : N_X));
                    if (p == 0) {
                        const __nv_bfloat16* xp = x + (size_t)((j0 + nt * 16 + (lane >> 1)) * 2 + par) * 1024 + q * 256 + (lane & 1) * 64;
                        prefetch_l2(xp); prefetch_l2(xp + 128);
                    } else if (elect_one()) {
                        mbar_expect_tx(bars + 8 * (B_ROW + q), 8192);
                        tma_3d(sb + OFF_FW + q * 8192, &mxs, bars + 8 * (B_ROW + q), 0, j0 + nt * 16, par * 16 + q * 4);
                    }
                }
                if (p == 0) nap(N_CS);
            }
            const uint32_t stg = sb + OFF_FW + 32768 + p * 4096 + lane * 16;
            float c[8];
#pragma unroll
            for (int i = 0; i < 8; i++) c[i] = 0.f;
#pragma unroll 1
            for (int n = 0; n < 10; n++) {
                const uint32_t bo = (n & 1) * 2048, bar = bars + 8 * (B_CS + 2 * p + (n & 1));
                if (n >= 2) {
                    mbar_wait(bar, ~(n >> 1) & 1);
#pragma unroll 2
                    for (int i = 0; i < 4; i++) {
                        const uint4 v = lds4(stg + bo + i * 512);
                        c[0] += bf_lo(v.x); c[1] += bf_hi(v.x); c[2] += bf_lo(v.y); c[3] += bf_hi(v.y);
                        c[4] += bf_lo(v.z); c[5] += bf_hi(v.z); c[6] += bf_lo(v.w); c[7] += bf_hi(v.w);
                    }
                    asm volatile("" :: "f"(c[7]));
                    __syncwarp();
                }
                if (n < 8 && elect_one()) {
                    mbar_expect_tx(bar, 2048);
                    tma_3d(sb + OFF_FW + 32768 + p * 4096 + bo, &mcs, bar, p * 1024 + nt * 64, mt * 8, 2 * n);
                }
            }
            sts4(stg + lane * 16, __float_as_uint(c[0]), __float_as_uint(c[1]), __float_as_uint(c[2]), __float_as_uint(c[3]));
            sts4(stg + lane * 16 + 16, __float_as_uint(c[4]), __float_as_uint(c[5]), __float_as_uint(c[6]), __float_as_uint(c[7]));
            bar_sync(13, 128);
            const uint32_t tag = lds1(sb + OFF_TAG);
            float* gcs = &S->cs[0][p * 1024 + nt * 64];
            {
                const float2 a0 = lds2f(stg - lane * 8), a1 = lds2f(stg - lane * 8 + 256), a2 = lds2f(stg - lane * 8 + 512), a3 = lds2f(stg - lane * 8 + 768);
                st_rlx2(gcs + mt * 3072 + lane * 2, tagf((a0.x + a1.x) + (a2.x + a3.x), tag), __float_as_uint((a0.y + a1.y) + (a2.y + a3.y)));
            }
            fence_async_smem();
            __syncwarp();
            if (lane == 0) mbar_arrive(bars + 8 * B_CSDONE);
            TSC(warp == 13 && lane == 0, 19);
            {
                uint4 v[4];
                const float* src = gcs + (lane >> 4) * 4 * 3072 + (lane & 15) * 4;
#pragma unroll 1
                for (int it = 0; it < SPIN_LIMIT; it++) {
#pragma unroll
                    for (int m = 0; m < 4; m++) v[m] = ld_rlx4(src + m * 3072);
                    if (!__any_sync(0xffffffffu, (mism(v[0].x, v[1].x, tag) | mism(v[2].x, v[3].x, tag)) & 1)) break;
                }
                __syncwarp();
#pragma unroll
                for (int c = 0; c < 4; c++) {
                    const float a = (__uint_as_float((&v[0].x)[c]) + __uint_as_float((&v[1].x)[c])) + (__uint_as_float((&v[2].x)[c]) + __uint_as_float((&v[3].x)[c]));
                    (&v[0].x)[c] = __float_as_uint(a + __shfl_xor_sync(0xffffffffu, a, 16));
                }
                const uint32_t ca = sb + OFF_CS + p * 384 + ((lane & 15) >> 1) * 48 + (lane & 1) * 8;
#pragma unroll 1
                for (int r = 0; r < 3; r++) {
                    const uint32_t u0 = pack_bf16(__uint_as_float(v[0].x), __uint_as_float(v[0].y)), u1 = pack_bf16(__uint_as_float(v[0].z), __uint_as_float(v[0].w));
                    sts2(ca + r * 16, u0, u1);
                    v[0].x = __float_as_uint(__uint_as_float(v[0].x) - bf_lo(u0)); v[0].y = __float_as_uint(__uint_as_float(v[0].y) - bf_hi(u0));
                    v[0].z = __float_as_uint(__uint_as_float(v[0].z) - bf_lo(u1)); v[0].w = __float_as_uint(__uint_as_float(v[0].w) - bf_hi(u1));
                }
                if (lane < 20) sts1(sb + OFF_CS + 1152 + lane * 4, 0);
                fence_async_smem();
            }
            if (p == 1) { if (lane < 2) st_rlx4(&S->hint[b][lane * 4], ~tag, ~tag, ~tag, ~tag); }
            else { st_rlx4(&S->halo[b][p * 128 + lane * 4], ~tag, ~tag, ~tag, ~tag); st_rlx4(&S->halo[b][p * 128 + 128 + lane * 4], ~tag, ~tag, ~tag, ~tag); }
            __syncwarp();
            if (lane == 0) mbar_arrive(bars + 8 * B_AUX);
            TSC(warp == 13 && lane == 0, 21);
            mbar_wait(bars + 8 * B_PART, 0);
            mbar_wait(bars + 8 * (B_EMPTY + 2), 0);
            if (p == 0) {
                uint4 v[4];
#pragma unroll
                for (int c = 0; c < 4; c++) v[c] = make_uint4(0, 0, 0, 0);
                const uint32_t* hsrc = &S->halo[b - 16][lane * 4];
                nap(N_HA);
#pragma unroll 1
                for (int it = 0; it < SPIN_LIMIT && j0; it++) {
                    TSC(TIMING == 15 && lane == 0 && it < 8, 40 + it);
#pragma unroll
                    for (int c = 0; c < 4; c++) v[c] = ld_rlx4(hsrc + c * 128);
                    if (!__any_sync(0xffffffffu, (mism(v[0].x, v[1].x, tag) | mism(v[2].x, v[3].x, tag)) & 1)) break;
                }
#pragma unroll
                for (int c = 0; c < 4; c++) sts4(sb + OFF_HALO + c * 512 + lane * 16, v[c].x, v[c].y, v[c].z, v[c].w);
                __syncwarp();
                bar_arrive(3, 64);
                TSC(TIMING >= 11 && lane == 0, 34);
            } else {
                const int w = p - 1;
                const uint8_t* osrc = g_o + (size_t)((mt * 2 + hp) * 2 + w) * 131072;
                const bool far = w > hp && j0 && lane >= 16;
                const uint32_t* hsrc = &S->hint[b & 0x70][0] + ((lane & 15) - (far ? 16 : 0)) * 8;
                if (lane == 0 && !w) st_rlx(&S->hint[b][0], tagw(now(), 1u, tag));
                uint32_t hv;
#pragma unroll 1
                for (int it = 0; it < SPIN_LIMIT; it++) {
                    hv = ld_rlx(hsrc);
                    if (!__any_sync(0xffffffffu, (hv ^ tag) & 1)) break;
                }
                TSC(TIMING == 11 && lane == 0, 32 + w);
                const uint32_t tn = __shfl_sync(0xffffffffu, hv, 0) - 0x40000000u;
                hv = redux_max(hv - tn + (far ? T_H : 0)) + tn + T_O + w * T_O1;
                mbar_wait(bars + 8 * (w ? B_AST : B_G1DONE), 0);
                if (elect_one()) {
#pragma unroll 1
                    for (int st = 0; st < 8; st++) {
                        const uint32_t full = bars + 8 * (B_OFULL + 8 * w + st);
                        if (st == 2 && !w) { until(hv + T_GO); mbar_arrive(bars + 8 * B_GO); }
                        if (st >= 2) mbar_wait(full + 8 * (B_DONE - B_OFULL - 2), 0);
                        if (st < 3) until(hv + (st == 2 ? T_S2 : st * T_S1));
                        TSC(st == 0, 28 + w);
                        mbar_expect_tx(full, 16384);
                        bulk_g2s(sb + (w ? OFF_O1 : OFF_O0) + (st & 1) * 16384, osrc + st * 16384, 16384, full);
                    }
                }
            }
            TS_END();
            return;
        }
        if (elect_one()) {
            auto load_wo = [&](int s, int ws) {
                mbar_expect_tx(bars + 8 * (B_WOFULL + s), 32768);
                tma_4d(sb + OFF_WO + ws * 32768, &mwo, bars + 8 * (B_WOFULL + s), 0, s * 8, 0, cb * 2);
            };
            uint32_t so = 2 * STAGE, ph = 1, cnt = PF_CNT << 4;
            int bi = 1, q = 0;
            mbar_expect_tx(bars + 8 * (B_ROW + 4), 2048);
            bulk_g2s(sb + OFF_FA, wr, 2048, bars + 8 * (B_ROW + 4));
            if (smem_u32(smem) != sb) __trap();
            const char* pf = (b < 64 ? wg : wu) + (b & 63) * 7168;
#pragma unroll 1
            for (int p = 1; p < 16; p++) {
                if (p < 3) nap(p == 1 ? N_S1 : N_S2);
                mbar_wait(bars + 8 * (B_EMPTY + bi), ph);
                load_stage(p, so, bi);
                if (p >= 2 && p < 5) {
                    const int k0 = p == 2 ? 3 : p == 3 ? K_W1 : K_W2, n = ((p == 2 ? K_W1 : p == 3 ? K_W2 : 16) - k0) * 3072;
                    if (p == 2) nap(N_W);
                    bulk_prefetch((const char*)wqkv + k0 * 393216 + b * n, n);
                }
#pragma unroll 1
                for (int e = q + (cnt & 3); q < e; q++) {
                    if (q == 16) pf = wd + mt * 7 * 131072 + nt * 8192;
                    if (q == 23) pf = wo + b * 8192;
                    bulk_prefetch(pf, q < 16 ? 7168 : 8192);
                    pf += q < 16 ? 64 * 7168 : q < 23 ? 131072 : 1048576;
                }
                cnt >>= 2;
                so = so == 2 * STAGE ? 0 : so + STAGE;
                if (++bi == 3) { bi = 0; ph ^= 1; }
            }
            TS(27);
            int ws = 1;
#pragma unroll 1
            for (int i = 0; i < 8; i++) {
                if (i < 2) {
                    mbar_wait(bars + 8 * (B_EMPTY + 1 + i), 0);
                    mbar_expect_tx(bars + 8 * B_XR, 16384);
                    tma_4d(sb + (i ? 0 : OFF_X1), &mx, bars + 8 * B_XR, DBG_XR * (par * 1024 + cb * 128 + 64 - i * 64), 0, DBG_XR * ((j0 >> 5) + hp * 4), 0);
                }
                if (i == 1) {
                    mbar_expect_tx(bars + 8 * B_F2FULL, 8192);
                    tma_2d_once(sb + OFF_F2X, &mwd, bars + 8 * B_F2FULL, DBG_F2 * c2 * 64, DBG_F2 * kc * 448);
                }
                if (i) {
                    mbar_wait(bars + 8 * (i == 1 ? B_ATT : i == 2 ? B_F2DONE : B_DONE - NWO + i), 0);
                    mbar_wait(bars + 8 * (i == 1 ? WO1_GATE : i == 2 ? B_OFULL + 8 : B_DONE + 8 - NWO + i), 0);
                }
                load_wo(i, ws);
                ws = ws ? ws - 1 : NWO - 1;
            }
        }
        TS_END();
    } else if (warp >= 8) {
        reg_dec<40>();
        const int p = warp - 8;
        const bool f1 = fb < 112;
        auto ffn_w = [&](int n, int s) {
            const uint32_t dst = sb + OFF_FW + s * 16384;
            if (n < 8) {
                mbar_expect_tx(bars + 8 * (B_FFULL + s), 16384);
                tma_3d_once(dst, &mgu, bars + 8 * (B_FFULL + s), DBG_F1 * fb * 32, n * 128, 0);
            } else {
                mbar_expect_tx(bars + 8 * B_F2FULL, 16384);
                tma_2d_once(dst, &mwd, bars + 8 * B_F2FULL, DBG_F2 * c2 * 64, DBG_F2 * kc * 448 + 64 + s * 128);
                tma_2d_once(dst + 8192, &mwd, bars + 8 * B_F2FULL, DBG_F2 * c2 * 64, DBG_F2 * kc * 448 + 128 + s * 128);
            }
        };
        const uint32_t tag = (epoch & 1) - 1;
        {
            const int ta = tid - 256;
            if (ta < 48) st_rlx4(&S->cs[mt][(ta >> 4) * 1024 + nt * 64 + (ta & 15) * 4], ~tag, ~tag, ~tag, ~tag);
        }
        float s1 = 0.f, s2 = 0.f, sr = 0.f, sw, sh = 0.f;
        {
            const uint32_t xa = sb + OFF_FW + p * 512 + lane * 16, wa = sb + OFF_FA + (((p * 4 + (lane >> 3)) ^ lane) & 7) * 16;
            TSC(TIMING == 12 && lane == 0, 50 + p);
            mbar_wait(bars + 8 * (B_ROW + 4), 0);
            {
                float c1 = 0.f, c2 = 0.f, cr = 0.f;
#pragma unroll 1
                for (int q = 0; q < 4; q++) {
                mbar_wait(bars + 8 * (B_ROW + q), 0);
                TSC(TIMING == 12 && tid == 256 + 96, 32 + q);
                TSC(tid == 256 && q == 3, 17);
#pragma unroll
                for (int i = 0; i < 4; i++) {
                    const uint4 u = lds4(xa + q * 8192 + i * 2048), w4 = lds4(wa + q * 512 + i * 128);
                    if (DBG_ST == 1) { s2 += fabsf(bf_lo(u.x ^ (u.y & u.z & u.w & 1))); sr += bf_lo(w4.x ^ w4.y ^ w4.z ^ w4.w ^ u.x); continue; }
                    const float a0 = bf_lo(u.x), a1 = bf_hi(u.x), a2 = bf_lo(u.y), a3 = bf_hi(u.y), a4 = bf_lo(u.z), a5 = bf_hi(u.z), a6 = bf_lo(u.w), a7 = bf_hi(u.w);
                    s1 += a0 + a1; c1 += a4 + a5; s1 += a2 + a3; c1 += a6 + a7;
                    s2 = fmaf(a0, a0, s2); c2 = fmaf(a4, a4, c2); sr = fmaf(a0, bf_lo(w4.x), sr); cr = fmaf(a4, bf_lo(w4.z), cr);
                    s2 = fmaf(a1, a1, s2); c2 = fmaf(a5, a5, c2); sr = fmaf(a1, bf_hi(w4.x), sr); cr = fmaf(a5, bf_hi(w4.z), cr);
                    s2 = fmaf(a2, a2, s2); c2 = fmaf(a6, a6, c2); sr = fmaf(a2, bf_lo(w4.y), sr); cr = fmaf(a6, bf_lo(w4.w), cr);
                    s2 = fmaf(a3, a3, s2); c2 = fmaf(a7, a7, c2); sr = fmaf(a3, bf_hi(w4.y), sr); cr = fmaf(a7, bf_hi(w4.w), cr);
                }
                }
                s1 += c1; s2 += c2; sr += cr;
            }
            mbar_wait(bars + 8 * B_SW, 0);
            sw = lds1f(sb + OFF_TAG + 4);
#pragma unroll 1
            for (int pass = 0;; pass++) {
#pragma unroll
                for (int o = 1; o < 8; o <<= 1) {
                    s1 += __shfl_xor_sync(0xffffffffu, s1, o); s2 += __shfl_xor_sync(0xffffffffu, s2, o); sr += __shfl_xor_sync(0xffffffffu, sr, o);
                }
                s1 *= 1.f / 1024.f;
                s2 = fmaf(-s1, s1, s2 * (1.f / 1024.f));
                if (!__any_sync(0xffffffffu, !pass && s1 * s1 > 256.f * s2)) break;
                sh = bf16r(s1); s1 = 0.f; s2 = 0.f; sr = 0.f;
#pragma unroll 1
                for (uint32_t o = 0; o < 2048; o = opaque(o + ((o & 12) == 12 ? 116 : 4))) {
                    const uint32_t u = lds1(xa + (o >> 7) * 2048 + (o & 12)), q = lds1(wa + o);
                    const float a0 = bf_lo(u) - sh, a1 = bf_hi(u) - sh;
                    s1 += a0 + a1; s2 = fmaf(a0, a0, fmaf(a1, a1, s2)); sr = fmaf(a0, bf_lo(q), fmaf(a1, bf_hi(q), sr));
                }
            }
        }
        const int ta = opaque(tid) - 256, lane = ta & 31, g = lane >> 2, t = lane & 3;
        {
            if ((lane & 7) == 0) {
                const int s = b * 16 + p * 4 + (lane >> 3);
                const float mb = bf16r(sh + s1);
                float den;
                asm("sqrt.approx.f32 %0, %1;" : "=f"(den) : "f"(bf16r(bf16r(s2) + 1e-5f)));
                den = bf16r(den);
                uint32_t rb = pack_bf16(fmaf(sh - mb, sw, sr) * rcp(den), 0.f);
                if (rb == 0x8000u) rb = 0;
                uint32_t ord = (rb & 0x8000u) ? (~rb & 0xffffu) : (rb | 0x8000u);
                if ((rb & 0x7fffu) > 0x7f80u) ord = 0;
                st_rlx2(&S->rec[s], (ord << 16) | (tag & 0x8000u) | (0x47ffu - (s & 1023) * 2 - par), pack_bf16(mb, den));
            }
            TSC(TIMING == 12 && lane == 0, 36 + p);
            bar_sync(12, 128);
            if (p == 1) sts1(sb + OFF_ROWMAP + lane * 4, 0xffffffffu);
            if (p == 0) {
                if (lane == 0) {
                    sts1(sb + OFF_TAG, tag);
                }
                __syncwarp();
                bar_arrive(13, 128);
            }
            TSC(ta == 0, 18);
        }
        {
            uint2 r[3];
            nap(N_GA);
            const uint2* src = &S->rec[mt * 256 + ta];
            const int l2 = ta < 8 && j0 ? -8 : 0;
#pragma unroll 1
            for (int it = 0; it < SPIN_LIMIT; it++) {
                r[0] = ld_rlx2(src + l2); r[1] = ld_rlx2(src); r[2] = ld_rlx2(src + 128);
                if (!__any_sync(0xffffffffu, (mism(r[0].x, r[1].x, tag) | (r[2].x ^ tag)) & 0x8000u)) break;
            }
#pragma unroll
            for (int n = 0; n < 3; n++)
                if (n || ta < 8) sts2(sb + OFF_STAT + (n ? n * 1024 - 960 : 0) + ta * 8, (r[n].y << 16) ^ 0x80000000u, __float_as_uint(rcp(bf_hi(r[n].y))));
        }
        __syncwarp();
        if (lane == 0) mbar_arrive(bars + 8 * B_AUX);
        TSC(ta == 0, 30);
        if (f1 && p < EARLY_FILL && elect_one()) { nap(p * N_F1); ffn_w(p, p); }
        __syncwarp();
        uint2 sel;
#pragma unroll 1
        for (int it = 0; it < SPIN_LIMIT; it++) {
            sel = ld_rlx2(&S->sel[lane & 7]);
            if (!__any_sync(0xffffffffu, (sel.x ^ tag) & 0x8000u)) break;
            __nanosleep(POLL_NS);
        }
        TSC(ta == 0, 26);
        if (b == 0 && ta == 0) st_rlx(&S->epoch, epoch + 1);
        {
            const __nv_bfloat16* xp = x + (~sel.x & 0x7ffu) * 1024 + (ta >> 3) * 8;
            const float mb = bf_lo(sel.y), rinv = rcp(bf_hi(sel.y));
            uint4 v = ldg_nc(xp), v2 = ldg_nc(xp + 128);
            int s = f1 ? 0 : 2;
#pragma unroll 1
            for (int n = f1 ? 0 : 8; n < (p ? 8 : 11); n++) {
                mbar_wait(bars + 8 * (f1 ? B_FEMPTY + s : B_PART), f1 && (n < 3 || (n >= 6 && n < 9)));
                if (p == 0 && s == 2) mbar_wait(bars + 8 * B_CSDONE, 0);
                if (p == 0 && n >= EARLY_FILL && elect_one()) ffn_w(n, s);
                if (n < 8) {
                    sts4(sb + OFF_FA + s * 2048 + ta * 16, norm_pair(v.x, mb, rinv), norm_pair(v.y, mb, rinv), norm_pair(v.z, mb, rinv), norm_pair(v.w, mb, rinv));
                    fence_async_smem();
                    __syncwarp();
                    if (lane == 0) mbar_arrive(bars + 8 * (B_FFULL + s));
                    TSC(TIMING == 12 && ta == 0, 41 + n);
                    v = v2;
                    if (n) v = ldg_nc(xp + ((n + 1) & 7) * 128);
                }
                if (++s == 3) s = 0;
            }
        }
        if (p) {
            if (p == 1 || f1) st_rlx4(p == 1 ? &S->ypart[kc][lane >> 4][c2 * 64 + (lane & 15) * 4] : (float*)&S->h[fb * 128 + (p & 1) * 64 + (lane & 15) * 4], ~tag, ~tag, ~tag, ~tag);
            st_rlx4(&S->ypart[kc][ta >> 4][c2 * 64 + (ta & 15) * 4], ~tag, ~tag, ~tag, ~tag);
        }
        mbar_wait(bars + 8 * B_PART, 0);
        if (f1 && p >= 2) {
            const uint32_t pa = sb + OFF_FA + (ta - 64) * 16, go = wu < wg ? 1024 : 0;
            const float4 g0 = lds4f(pa + go), g1 = lds4f(pa + 2048 + go), u0 = lds4f(pa + (go ^ 1024)), u1 = lds4f(pa + 2048 + (go ^ 1024));
            float hv[4];
#pragma unroll
            for (int c = 0; c < 4; c++) {
                const float ga = bf16r((&g0.x)[c] + (&g1.x)[c]), up = bf16r((&u0.x)[c] + (&u1.x)[c]);
                hv[c] = bf16r(ga * sigmoidf(ga)) * up;
            }
#pragma unroll
            for (int hh = 0; hh < 2; hh++) {
                const float o = __shfl_xor_sync(0xffffffffu, (g & 1) ? hv[2 * hh] : hv[2 * hh + 1], 4);
                st_rlx(&S->h[(fb * 4 + (p & 1) * 2 + hh) * 32 + (2 * t + (g & 1)) * 4 + (g >> 1)],
                       tagw((g & 1) ? pack_bf16(o, hv[2 * hh + 1]) : pack_bf16(hv[2 * hh], o), g < 2, tag));
            }
            TSC(ta == 64, 22);
        }
        {
            uint4 hq[4];
            const uint32_t* hp4 = S->h + kc * 1792 + ta * 4;
#pragma unroll 1
            for (int it = 0; it < SPIN_LIMIT; it++) {
#pragma unroll
                for (int n = 0; n < 4; n++) hq[n] = ld_rlx4(hp4 + (n < 3 ? n * 512 : p < 2 ? 1536 : 0));
                if (!__any_sync(0xffffffffu, (mism(hq[0].x, hq[1].x, tag) | mism(hq[2].x, hq[3].x, tag)) & 1)) break;
            }
            mbar_wait(bars + 8 * B_G1DONE, 0);
            bar_sync(12, 128);
#pragma unroll
            for (int n = 0; n < 4; n++) sts4(sb + OFF_FA + ta * 16 + (n < 3 ? n * 2048 : p < 2 ? 6144 : 0), hq[n].x, hq[n].y, hq[n].z, hq[n].w);
            fence_async_smem();
            bar_sync(12, 128);
            TSC(ta == 0, 25);
            mbar_wait(bars + 8 * B_F2FULL, 0);
            mbar_wait(bars + 8 * B_ATT, 0);
            float acc[4] = {0.f, 0.f, 0.f, 0.f};
            uint32_t da = sd + dlo(OFF_F2X, 8192), db = sd + dlo(OFF_FA, 128);
#pragma unroll 1
            for (int q = 0; q < 7; q++) {
                wg_fence();
#pragma unroll
                for (int j = 0; j < 4; j++) wgmma_n8<1, 0>(acc, mkdesc(da + j * 128, dhi(1024, 1)), mkdesc(db + j * 16, dhi(128, 0)));
                wg_commit();
                da = sd + dlo(OFF_FW, 8192) + q * 512; db += 64;
            }
            wg_wait<0>();
            if (ta == 0) mbar_arrive(bars + 8 * B_F2DONE);
#pragma unroll
            for (int c = 0; c < 4; c++) st_rlx(&S->ypart[kc][2 * t + (c & 1)][c2 * 64 + p * 16 + (c >> 1) * 8 + g], tagf(acc[c], tag));
            TSC(ta == 0, 23);
            bar_sync(12, 128);
        }
#pragma unroll 1
        for (int j = 2 * p; j < 2 * p + 2; j++) {
            const uint32_t kj = __shfl_sync(0xffffffffu, sel.x, j);
            const int row = 0x7ff - (kj & 0x7ffu), jj = (row >> 1) - j0 - hp * 128;
            float a0 = 0.f, a1 = 0.f, a2 = 0.f, a3 = 0.f, sig = 0.f;
            if ((row & 1) == par && jj >= 0 && jj < 128) {
                sig = bf16r(sigmoidf(__uint_as_float(((int)kj < 0 ? kj ^ 0x80000000u : ~kj) & 0xffff0000u)));
#pragma unroll 1
                for (int hh = 0; hh < 8; hh += 4) {
                    uint4 v[4];
#pragma unroll 1
                    for (int it = 0; it < SPIN_LIMIT; it++) {
#pragma unroll
                        for (int m = 0; m < 4; m++) v[m] = ld_rlx4(&S->ypart[hh + m][j][cb * 128 + lane * 4]);
                        if (!__any_sync(0xffffffffu, (mism(v[0], tag) | mism(v[1], tag) | mism(v[2], tag) | mism(v[3], tag)) & 1)) break;
                    }
#pragma unroll
                    for (int m = 0; m < 4; m++) { a0 += __uint_as_float(v[m].x); a1 += __uint_as_float(v[m].y); a2 += __uint_as_float(v[m].z); a3 += __uint_as_float(v[m].w); }
                }
                asm volatile("st.shared.u8 [%0], %1;" ::"r"(sb + OFF_ROWMAP + jj), "r"(j) : "memory");
            }
            sts2(sb + OFF_FA + (lane >> 1) * 128 + j * 16 + (lane & 1) * 8, pack_bf16(bf16r(a0) * sig, bf16r(a1) * sig), pack_bf16(bf16r(a2) * sig, bf16r(a3) * sig));
        }
        fence_async_smem();
        __syncwarp();
        if (lane == 0) mbar_arrive(bars + 8 * B_UPD);
        TSC(ta == 0, 24);
        TS_END();
    } else {
        if (elect_one()) {
#pragma unroll
            for (int i = 0; i < (B_EMPTY - B_WOFULL) / 8; i++) mbar_init(bars + 8 * (B_WOFULL + 8 * i + warp), 1);
        }
        reg_inc<224>();
        const int w = warp >> 2, wi = warp & 3, tw = (1 - w) * 4 + wi;
        const bool elect = (tid & 127) == 0;
        const uint32_t ln = opaque(lane), g = ln >> 2, t = ln & 3;
        uint32_t tag, ow[8][4], xr[32];
        const uint32_t xs = sb + (wi & 1) * 8192 + (tw >> 1) * 2048, mad = xs + (ln & 15) * 128;
        auto store_o = [&](int f0, int f1) {
            uint8_t* ob = g_o + (size_t)((mt * 2 + 1 - w) * 2 + 1 - (wi >> 1)) * 131072 + nt * 1024 + (wi & 1) * 512 + ln * 4;
#pragma unroll
            for (int f = f0; f < f1; f++)
#pragma unroll
                for (int i = 3; i >= 0; i--)
                    st_rlx(ob + f * 16384 + i * 128, ow[f][i]);
        };
        {
            float acc[2][96];
            const uint32_t sta = opaque(sb + OFF_STAT + tw * 256 + 64 + g * 8);
            {
                float fa[4] = {0.f, 0.f, 0.f, 0.f};
                uint32_t so = STAGE >> 4, bo = bars, ph = 0;
                const uint32_t dx0 = sd + dlo(w ? 40960 : 0, 16), dw0 = sd + dlo(16384, 8192);
                int p = 0;
                if (w) bar_arrive(1, 256);
                uint32_t fm = fb < 112 ? F1_MASK >> (16 * w) : 0u, fph = 0;
                int fs = w;
#pragma unroll 1
                for (; p < 16; p++) {
                    mbar_wait(bo + 8 * B_FULLA, ph);
                    if (w) mbar_wait(bo + 8 * B_FULLB, ph);
                    TSC(elect && p == 0, 1 + 8 * w);
                    bar_sync(1 + w, 256);
                    TSC(TIMING == 1 && tid == 0, 32 + p);
                    if (p == 15) {
                        wg_fence();
                        wgmma_n192<0, 1>(acc[1], mkdesc(sd + dlo(OFF_MEAN + 1024, 0) + w * 128, dhi(128, 0)), mkdesc(sd + dlo(OFF_CS, 0), dhi(48, 0)));
                        wgmma_n192<0, 1>(acc[0], mkdesc(sd + dlo(OFF_MEAN, 0) + w * 128, dhi(128, 0)), mkdesc(sd + dlo(OFF_CS, 0), dhi(48, 0)));
                        wg_commit();
                    }
                    wg_fence();
#pragma unroll
                    for (int h = 1; h >= 0; h--) {
#pragma unroll
                        for (int k = 0; k < 4; k++) wgmma_n192<0, 1>(acc[h], mkdesc(dx0 + so + h * 512 + k * 2, dhi(1024, 1)), mkdesc(dw0 + so + k * 128, dhi(1024, 1)), k ? 1 : p);
                        wg_commit();
                    }
                    if (fm & 1) {
                        mbar_wait(bars + 8 * (B_FFULL + fs), fph);
                        wg_fence();
#pragma unroll
                        for (int j = 0; j < 8; j++)
                            wgmma_n8<1, 0>(fa, mkdesc(sd + dlo(OFF_FW, 8192) + fs * 1024 + j * 64, dhi(512, 2)), mkdesc(sd + dlo(OFF_FA, 128) + fs * 128 + j * 16, dhi(128, 0)));
                        wg_commit();
                    }
                    bar_arrive(2 - w, 256);
                    if (p == 15) break;
                    wg_wait<0>();
                    if (wi == 0 && elect_one()) { mbar_arrive(bo + 8 * B_EMPTY); if (fm & 1) mbar_arrive(bars + 8 * (B_FEMPTY + fs)); }
                    so = so == 2 * (STAGE >> 4) ? 0 : so + (STAGE >> 4);
                    bo += 8;
                    if (bo == bars + 24) { bo = bars; ph ^= 1; }
                    if (fm & 1) { fs += 2; if (fs >= 3) { fs -= 3; fph ^= 1; } }
                    fm >>= 1;
                    if (p == P_PART) {
                        if (fb < 112) sts4(sb + OFF_FA + tid * 16, __float_as_uint(fa[0]), __float_as_uint(fa[1]), __float_as_uint(fa[2]), __float_as_uint(fa[3]));
                        __syncwarp();
                        if (lane == 0) mbar_arrive(bars + 8 * B_PART);
                    }
                    if (p != 14) continue;
                    mbar_wait(bars + 8 * B_AUX, 0);
                    mbar_wait(bars + 8 * (B_EMPTY + 1), 0);
                    const uint32_t hm = __float_as_uint(0.5f * lds1f(sb + OFF_STAT + 64 + tw * 256 + ln * 8)) >> 16;
                    sts4(sb + OFF_MEAN + w * 2048 + wi * 256 + (ln >> 4) * 1024 + (ln & 15) * 16, hm * 0x10001u, hm, 0, 0);
                    fence_async_smem();
                }
            }
            TSC(TIMING != 14 && elect, 2 + 8 * w);

            tag = lds1(sb + OFF_TAG);
            mbar_wait(bars + 8 * (B_EMPTY + 2), 0);
            wg_wait<1>();
#pragma unroll
            for (int i = 0; i < 96; i++) asm volatile("" : "+f"(acc[1][i]) :: "memory");
            uint32_t pk[4][24];
            const uint32_t hm = tw == 7 ? ~ln & 1 : 0;
            auto np = [&](int i, int j) {
                const float* a = &acc[i >> 1][4 * j + 2 * (i & 1)];
                pk[i][j] = pack_bf16(a[0], a[1]);
                if (j >= 16) pk[i][j] = movm(pk[i][j]);
                if (i == 3 && j >= 8 && !(j & 1)) pk[i][j] = tagw(pk[i][j], hm, tag);
            };
            const uint32_t ha = sb + OFF_HALO + tw * 2048 + ln * 8;
#pragma unroll
            for (int j = 8; j < 24; j += 2) {
                np(3, j); np(3, j + 1);
                sts2(ha + 2048 + (j - 8) * 128, pk[3][j], pk[3][j + 1]);
                asm volatile("{\n.reg .pred p;\nsetp.eq.u32 p, %3, 7;\n@p st.relaxed.gpu.global.v2.u32 [%0], {%1,%2};\n}" ::"l"((char*)&S->halo[b][ln * 2] + (j - 8) * 128),
                             "r"(pk[3][j]), "r"(pk[3][j + 1]), "r"(tw) : "memory");
            }
            bar_arrive(4 + tw, 64);
            TSC(TIMING == 15 && ln == 0 && tw == 7, 39);
            TSC(TIMING == 8 && ln == 0 && wi == 1, 32 + 8 * w);
            auto load_x = [&]() {
                mbar_wait(bars + 8 * B_XR, 0);
#pragma unroll
                for (int j = 0; j < 16; j += 2)
                    asm volatile("ldmatrix.sync.aligned.m8n8.x4.shared.b16 {%0,%1,%2,%3}, [%4];" : "=r"(xr[2 * j]), "=r"(xr[2 * j + 1]), "=r"(xr[2 * j + 2]), "=r"(xr[2 * j + 3])
                                 : "r"(mad + (j >> 3) * OFF_X1 + ((((j & 7) + (ln >> 4)) ^ (ln & 7)) << 4)) : "memory");
            };
            const bool u0 = 2 * t > g, u1 = 2 * t + 1 > g;
            const uint32_t mU = (u0 ? 0xffffu : 0u) | (u1 ? 0xffff0000u : 0u);
            uint2 hl[8];
            float rk[4][2], fq[4][2];
            auto factors = [&]() {
                const uint32_t ka = sb + OFF_STAT + tw * 256 + 4 + t * 16, k0 = opaque(ka + (u0 ? 0 : 64)), k1 = opaque(ka + (u1 ? 8 : 72));
#pragma unroll
                for (int i = 0; i < 4; i++) {
                    const float rq = lds1f(sta + i * 64 + 4) * (0.17677669529663687f * 1.4426950408889634f);
                    rk[i][0] = lds1f(k0 + i * 64); rk[i][1] = lds1f(k1 + i * 64);
                    fq[i][0] = rq * rk[i][0]; fq[i][1] = rq * rk[i][1];
                }
            };
#pragma unroll
            for (int jj = 0; jj < 12; jj++) { const int j = (jj >> 2) * 8 + (jj & 3); np(2, j); if (j < 8) np(3, j); }
            if (PRE_F) factors();
            wg_wait<0>();
#pragma unroll
            for (int i = 0; i < 96; i++) asm volatile("" : "+f"(acc[0][i]) :: "memory");
            if (elect) mbar_arrive(bars + 8 * B_G1DONE);
            if (HOLD == 0) mbar_wait(bars + 8 * B_G1DONE, 0);
            const float mask = tw == 0 && j0 == 0 ? -INFINITY : 0.f;
#pragma unroll
            for (int hd = 0; hd < 2; hd++) {
#pragma unroll
                for (int jj = 0; jj < 12; jj++) {
                    const int j = (jj >> 2) * 8 + hd * 4 + (jj & 3);
                    np(0, j); np(1, j);
                    if (j & 4)
                    { np(2, j); if (j < 8) np(3, j); }
                }
                if (HOLD && hd == 0) {
                    if (!PRE_F) factors();
                    if (HOLD == 2) load_x();
                    uint32_t dep = __float_as_uint(fq[0][0]) ^ __float_as_uint(fq[3][1]);
#pragma unroll
                    for (int j = 16; j < (HOLD_ALL ? 24 : 20); j++) dep ^= pk[0][j] ^ pk[1][j] ^ pk[2][j];
                    if (HOLD == 2) dep ^= xr[0] ^ xr[4] ^ xr[8] ^ xr[12] ^ xr[16] ^ xr[20] ^ xr[24] ^ xr[28];
                    mbar_wait(bars + 8 * B_G1DONE + (HOLD_DEP ? dep & (ln >> 5) : 0), 0);
                }
                float s[2][3][4];
#pragma unroll
                for (int h = 1; h >= 0; h--)
#pragma unroll
                    for (int n = 2; n >= 0; n--) {
                        if (h == 0 && n == 0 && hd == 0) {
                            if (HOLD == 0 && !PRE_F) factors();
                            TSC(TIMING == 8 && ln == 0 && wi == 1 && s[1][0][0] + s[0][1][0] != 123.456f, 33 + 8 * w);
                            bar_sync(3 + tw, 64);
#pragma unroll
                            for (int c = 0; c < 8; c++) hl[c] = lds2(ha + c * 256);
                        }
                        const int kg = 2 * h - 1 + n;
                        s[h][n][0] = s[h][n][1] = kg < 0 ? mask : 0.f; s[h][n][2] = s[h][n][3] = 0.f;
#pragma unroll
                        for (int ks = 0; ks < 2; ks++) {
                            const int q = hd * 4 + 2 * ks;
                            const uint32_t* k = kg < 0 ? &hl[hd * 2 + ks].x : &pk[kg < 0 ? 0 : kg][8 + q];
                            mma16816(s[h][n], pk[2 * h][q], pk[2 * h + 1][q], pk[2 * h][q + 1], pk[2 * h + 1][q + 1], k[0], k[1]);
                        }
                    }
                uint32_t pp[4], pc[4];
#pragma unroll
                for (int i = 0; i < 4; i++) {
                    const float* sp = &s[i >> 1][i & 1][2 * (i & 1)];
                    const float* sc = &s[i >> 1][(i & 1) + 1][2 * (i & 1)];
                    float a0 = (u0 ? sp[0] : sc[0]) * fq[i][0], a1 = (u1 ? sp[1] : sc[1]) * fq[i][1];
                    float m = fmaxf(a0, a1);
                    m = fmaxf(m, __shfl_xor_sync(0xffffffffu, m, 1));
                    m = fmaxf(m, __shfl_xor_sync(0xffffffffu, m, 2));
                    a0 = ex2(a0 - m); a1 = ex2(a1 - m);
                    float sum = a0 + a1;
                    sum += __shfl_xor_sync(0xffffffffu, sum, 1);
                    sum += __shfl_xor_sync(0xffffffffu, sum, 2);
                    const float inv = rcp(sum);
                    const uint32_t pw = pack_bf16(a0 * rk[i][0] * inv, a1 * rk[i][1] * inv);
                    pp[i] = pw & mU; pc[i] = pw & ~mU;
                }
                TSC(TIMING == 8 && ln == 0 && wi == 1 && pp[0] + pp[3] != 0x12345, 34 + 2 * hd + 8 * w);
#pragma unroll
                for (int fh = 0; fh < 2; fh++)
#pragma unroll
                    for (int i = 0; i < 4; i++) {
                        const int v = 16 + hd * 4 + 2 * fh;
                        const uint32_t* vp = i ? &pk[i ? i - 1 : 0][v] : &hl[4 + hd * 2 + fh].x;
                        float o[4] = {0.f, 0.f, 0.f, 0.f};
                        if (i & 1) mma16816(o, vp[0], vp[1], pk[i][v], pk[i][v + 1], pp[i], pc[i]);
                        else { mma1688(o, pk[i][v], pk[i][v + 1], pc[i]); mma1688(o, vp[0], vp[1], pp[i]); }
                        const uint32_t tm = (ln & 7) == (nt & 3) * 2 + (i & 1);
                        ow[hd * 4 + 2 * fh][i] = tagw(pack_bf16(o[0], o[1]), tm, tag); ow[hd * 4 + 2 * fh + 1][i] = tagw(pack_bf16(o[2], o[3]), tm, tag);
                    }
                store_o(hd ? ST_A : 0, hd ? ST_B : ST_A);
                TSC(TIMING == 11 && !hd && ln == 0 && wi == 3, 45 + w);
                if (hd) mbar_wait(bars + 8 * B_G1DONE, 0);
                if (hd) mbar_arrive_after(bars + 8 * B_ATT, ln, xr[16] ^ xr[20] ^ xr[24] ^ xr[28]);
                else {
                    mbar_arrive_after(bars + 8 * B_AST, ln, hl[2].x ^ hl[3].x ^ hl[5].x ^ hl[6].x ^ hl[7].x);
                    if (HOLD < 2) load_x(); else mbar_wait(bars + 8 * B_G1DONE, 0);
                }
                TSC(TIMING != 14 && elect && hd == 0, 3 + 8 * w);
                TSC(TIMING == 8 && ln == 0 && wi == 1, 35 + 2 * hd + 8 * w);
            }
        }
        TSC(TIMING != 14 && elect, 4 + 8 * w);
        float acc2[64];
        {
            const uint32_t sta = sb + OFF_STAT + (8 + hp * 128 + tw * 16 + g) * 8;
            const float2 s0 = lds2f(sta), s1 = lds2f(sta + 64);
            const float m0 = s0.x * s0.y, r0 = 1.f + s0.y, m1 = s1.x * s1.y, r1 = 1.f + s1.y;
#pragma unroll
            for (int j = 0; j < 32; j++) {
                acc2[2 * j] = fmaf(bf_lo(xr[j]), j & 1 ? r1 : r0, j & 1 ? m1 : m0); acc2[2 * j + 1] = fmaf(bf_hi(xr[j]), j & 1 ? r1 : r0, j & 1 ? m1 : m0);
                asm volatile("" : "+f"(acc2[2 * j]), "+f"(acc2[2 * j + 1]) :: "memory");
            }
        }
        TSC(TIMING != 14 && elect, 5 + 8 * w);
        {
            if (ST_B < ST_C) { mbar_wait(bars + 8 * B_GO, 0); store_o(ST_B, ST_C); }
            mbar_wait(bars + 8 * B_ATT, 0);
            const uint32_t ring = sb + (w ? OFF_O1 : OFF_O0), da0 = (ring >> 4) + dlo(0, 1024);
            const uint32_t l2 = opaque(ln), chk = ring + wi * 256 + (l2 >> 3) * 1032 + ((l2 >> 2) & 1) * 132 + (l2 & 3) * 32;
            uint32_t db = sd + dlo(OFF_WO + 32768, 16384);
#pragma unroll 1
            for (int s = 0; s < 8; s++) {
                const uint32_t ro = (s & 1) * 16384;
                mbar_wait(bars + 8 * (B_WOFULL + s), 0);
                TSC(TIMING == 11 && tid == 0 && s == 0, 43);
                mbar_wait(bars + 8 * (B_OFULL + s) + 64 * w, 0);
                TSC(TIMING == 11 && tid == 0 && s == 0, 44);
#pragma unroll 1
                for (int it = 0; __any_sync(0xffffffffu, (mism(lds1(chk + ro), lds1(chk + ro + 4096), tag) | mism(lds1(chk + ro + 8192), lds1(chk + ro + 12288), tag)) & 1) && it < SPIN_LIMIT; it++) {
                    NRETRY();
                    const uint32_t fo = wi * 256 + (l2 >> 4) * 1024 + (l2 & 15) * 16;
                    uint4 v[8];
#pragma unroll
                    for (int c = 0; c < 8; c++) v[c] = ld_rlx4(g_o + (size_t)(((mt * 2 + hp) * 2 + w) * 8 + s) * 16384 + fo + c * 2048);
#pragma unroll
                    for (int c = 0; c < 8; c++) sts4(ring + ro + fo + c * 2048, v[c].x, v[c].y, v[c].z, v[c].w);
                    fence_async_smem();
                    __syncwarp();
                }
                if (s <= 8 - LAST) bar_sync(1 + w, 256);
                TSC(elect && s == 0, 6 + 8 * w);
                TSC(TIMING == 2 && elect, 32 + 16 * w + s);
                wg_fence();
#pragma unroll
                for (int k = 0; k < 8; k++)
                    wgmma_n128<1, 1>(acc2, mkdesc(da0 + (ro >> 4) + k * 128, dhi(128, 0)), mkdesc(db + k * 128, dhi(1024, 1)));
                wg_commit();
                db = db == sd + dlo(OFF_WO, 16384) ? sd + dlo(OFF_WO + (NWO - 1) * 32768, 16384) : db - 2048;
                if (s < 8 - LAST) {
                    bar_arrive(2 - w, 256);
                    if (s == 0) store_o(ST_C, 8);
                    wg_wait<0>();
                    if (elect) mbar_arrive(bars + 8 * (B_DONE + s) + 64 * w);
                }
            }
            mbar_wait(bars + 8 * B_UPD, 0);
            int sl0, sl1;
            asm volatile("ld.shared.s8 %0, [%1];" : "=r"(sl0) : "r"(sb + OFF_ROWMAP + tw * 16 + g) : "memory");
            asm volatile("ld.shared.s8 %0, [%1];" : "=r"(sl1) : "r"(sb + OFF_ROWMAP + tw * 16 + 8 + g) : "memory");
            const uint32_t e0 = (sl0 >> 1) == (int)t ? 0x3f80u << ((sl0 & 1) * 16) : 0u, e1 = (sl1 >> 1) == (int)t ? 0x3f80u << ((sl1 & 1) * 16) : 0u;
            wg_fence();
            wgmma_rs_n128<1>(acc2, e0, e1, 0u, 0u, mkdesc(sd + dlo(OFF_FA, 0), dhi(128, 0)));
            wg_commit();
            bar_arrive(2 - w, 256);
            wg_wait<0>();
#pragma unroll
            for (int i = 0; i < 64; i++) asm volatile("" : "+f"(acc2[i]) :: "memory");
            TSC(elect, 7 + 8 * w);
#pragma unroll
            for (int j = 0; j < 16; j += 2) {
                const int ch = (j & 7) + (ln >> 4);
                asm volatile("stmatrix.sync.aligned.m8n8.x4.shared.b16 [%0], {%1,%2,%3,%4};" ::"r"(mad + (j >> 3) * STAGE + ((ch ^ (ln & 7)) << 4)),
                             "r"(pack_bf16(acc2[4 * j], acc2[4 * j + 1])), "r"(pack_bf16(acc2[4 * j + 2], acc2[4 * j + 3])),
                             "r"(pack_bf16(acc2[4 * j + 4], acc2[4 * j + 5])), "r"(pack_bf16(acc2[4 * j + 6], acc2[4 * j + 7])) : "memory");
                if ((j & 7) == 6) {
                    fence_async_smem();
                    __syncwarp();
                    if (ln == 0) tma_store_2d(&mout, xs + (j >> 3) * STAGE, par * 1024 + cb * 128 + (j >> 3) * 64, j0 + hp * 128 + tw * 16);
                }
            }
            if (ln == 0) asm volatile("cp.async.bulk.commit_group;\ncp.async.bulk.wait_group.read 0;" ::: "memory");
            TSC(elect, 8 + 8 * w);
            TS_END();
        }
    }
}

typedef CUresult (*EncodeFn)(CUtensorMap*, CUtensorMapDataType, cuuint32_t, void*, const cuuint64_t*, const cuuint64_t*, const cuuint32_t*,
                             const cuuint32_t*, CUtensorMapInterleave, CUtensorMapSwizzle, CUtensorMapL2promotion, CUtensorMapFloatOOBfill);

CUtensorMap make_map(EncodeFn fn, const void* base, int rank, const cuuint64_t* dims, const cuuint64_t* strides, const cuuint32_t* box,
                     CUtensorMapSwizzle swz = CU_TENSOR_MAP_SWIZZLE_128B, CUtensorMapL2promotion pro = CU_TENSOR_MAP_L2_PROMOTION_L2_256B) {
    CUtensorMap m;
    cuuint32_t es[5] = {1, 1, 1, 1, 1};
    fn(&m, CU_TENSOR_MAP_DATA_TYPE_BFLOAT16, rank, (void*)base, dims, strides, box, es, CU_TENSOR_MAP_INTERLEAVE_NONE,
       swz, pro, CU_TENSOR_MAP_FLOAT_OOB_FILL_NONE);
    return m;
}

}

extern "C" void kernel_launch(void* const* d_in, const int* in_sizes, int n_in, void* d_out, int out_size) {
    (void)in_sizes; (void)n_in; (void)out_size;
    const __nv_bfloat16* x = (const __nv_bfloat16*)d_in[0];
    const __nv_bfloat16* wqkv = (const __nv_bfloat16*)d_in[1];
    const char* wo = (const char*)d_in[2];
    const __nv_bfloat16* wr = (const __nv_bfloat16*)d_in[4];
    const char* wg = (const char*)d_in[5];
    const char* wu = (const char*)d_in[6];
    const char* wd = (const char*)d_in[7];
    static EncodeFn fn = nullptr;
    static int by_sm = 0;
    static Scratch* scr = nullptr;
    if (!fn) {
        void* p = nullptr; cudaDriverEntryPointQueryResult q;
        cudaGetDriverEntryPoint("cuTensorMapEncodeTiled", &p, cudaEnableDefault, &q);
        fn = (EncodeFn)p;
        cudaFuncSetAttribute(fused_kernel, cudaFuncAttributeMaxDynamicSharedMemorySize, SMEM_LAUNCH);
        cudaGetSymbolAddress((void**)&scr, g_scr);
        int dev = 0, sms = 0;
        cudaGetDevice(&dev);
        cudaDeviceGetAttribute(&sms, cudaDevAttrMultiProcessorCount, dev);
        by_sm = sms == 132;
    }
    Roles roles;
    for (int i = 0; i < 132; i++) {
        const int T = i >> 1, T8 = T < 32 ? T : T + 1 + (T - 32) / 7, fb = (T < 60 ? (~T8 & 7) * 8 + (T8 >> 3) : T < 62 ? T + 4 : T - 2) * 2 + (i & 1);
        roles.v[i] = fb | ((fb & ~31) | (fb & 1) << 4 | (fb & 31) >> 1) << 8;
    }
    const cuuint64_t xd[4] = {2048, 16, 32, 2}, xs[3] = {4096, 131072, 65536};
    const cuuint32_t xb[4] = {64, 16, 4, 2};
    const cuuint64_t wdm[3] = {1024, 1024, 3}, wst[2] = {6144, 2048};
    const cuuint32_t wb[3] = {64, 64, 3};
    const cuuint64_t od[4] = {64, 64, 16, 16}, ost[3] = {2048, 131072, 128};
    const cuuint32_t ob[4] = {64, 8, 16, 2};
    const cuuint64_t yd[2] = {2048, 1024}, yst[1] = {4096};
    const cuuint32_t yb[2] = {64, 16};
    const cuuint64_t sd[3] = {64, 1024, 32}, sst[2] = {4096, 128};
    const cuuint32_t sbx[3] = {64, 16, 4};
    CUtensorMap mxs = make_map(fn, x, 3, sd, sst, sbx);
    const cuuint64_t cd[3] = {3072, 64, 16}, cst[2] = {6144, 393216};
    const cuuint32_t cbx[3] = {64, 8, 2};
    CUtensorMap mcs = make_map(fn, wqkv, 3, cd, cst, cbx, CU_TENSOR_MAP_SWIZZLE_NONE);
    CUtensorMap mx = make_map(fn, x, 4, xd, xs, xb), mw = make_map(fn, wqkv, 3, wdm, wst, wb);
    CUtensorMap mwo = make_map(fn, wo, 4, od, ost, ob), mout = make_map(fn, d_out, 2, yd, yst, yb);
    const cuuint64_t gd[3] = {3584, 1024, 2}, gst[2] = {7168, (cuuint64_t)(wu < wg ? wg - wu : wu - wg)};
    const cuuint32_t gb[3] = {32, 128, 2};
    const cuuint64_t dd[2] = {1024, 3584}, dst[1] = {2048};
    const cuuint32_t db[2] = {64, 64};
    CUtensorMap mgu = make_map(fn, wu < wg ? wu : wg, 3, gd, gst, gb, CU_TENSOR_MAP_SWIZZLE_64B, CU_TENSOR_MAP_L2_PROMOTION_L2_128B);
    CUtensorMap mwd = make_map(fn, wd, 2, dd, dst, db, CU_TENSOR_MAP_SWIZZLE_128B, CU_TENSOR_MAP_L2_PROMOTION_L2_128B);
    fused_kernel<<<132, 512, SMEM_LAUNCH, cudaStreamPerThread>>>(by_sm, x, wqkv, wr, scr, wg, wu, wd, wo, roles, mw, mx, mwo, mxs, mcs, mout, mgu, mwd);
}
```

```cpp
#include <cuda_runtime.h>
#include <cuda.h>
#include <cuda_bf16.h>
#include <stdint.h>

namespace {

constexpr int STAGE = 57344;
constexpr int OFF_FW = 3 * STAGE;
constexpr int OFF_FA = OFF_FW + 49152;
constexpr int OFF_CS = OFF_FA + 6144;
constexpr int OFF_STAT = OFF_CS + 1232;
constexpr int OFF_ROWMAP = OFF_STAT + 2112;
constexpr int OFF_TAG = OFF_ROWMAP + 128;
constexpr int OFF_BAR = OFF_TAG + 8;
constexpr int OFF_F2X = 16384, OFF_HALO = 24576, OFF_O1 = 24576, OFF_O0 = 90112, NWO = 3, OFF_MEAN = 2 * STAGE, OFF_X1 = 2 * STAGE + 8192;
constexpr int OFF_WO0 = OFF_X1 + 16384, OFF_WO1 = STAGE, OFF_WO2 = OFF_FW;
static_assert(OFF_WO0 + 32768 == OFF_FW && OFF_WO1 + 32768 == OFF_O0 && OFF_O0 + 32768 == OFF_X1 && OFF_O1 + 32768 == STAGE, "alias");
__host__ __device__ constexpr uint32_t wo_next(uint32_t o, uint32_t base, int sh) { return o == base + (OFF_WO0 >> sh) ? base + (OFF_WO1 >> sh) : o == base + (OFF_WO1 >> sh) ? base + (OFF_WO2 >> sh) : base + (OFF_WO0 >> sh); }
constexpr int B_FULLA = 0, B_FULLB = 3, B_ROW = 6, B_FFULL = 11, B_FEMPTY = 14, B_F2DONE = 17, B_SW = 18, B_CS = 19, B_WOFULL = 25, B_OFULL = B_WOFULL + 8,
              B_DONE = B_OFULL + 16;
constexpr int B_EMPTY = B_DONE + 16, B_XR = B_EMPTY + 3, B_G1DONE = B_XR + 1;
constexpr int B_UPD = B_G1DONE + 1, B_F2FULL = B_UPD + 1;
constexpr int B_AUX = B_F2FULL + 1, B_PART = B_AUX + 1, B_ATT = B_PART + 1, B_CSDONE = B_ATT + 1, B_AST = B_CSDONE + 1, NBAR = B_AST + 1;
constexpr int SMEM_BYTES = OFF_BAR + NBAR * 8;
static_assert(SMEM_BYTES <= 232448 && OFF_BAR % 8 == 0, "smem");
#define P_PART 13
#define F1_MASK (0x6a005a00u >> (14 - P_PART))
#define PF_CNT 0x2aaaaacu
#define N_S1 1
#define N_S2 3
#define ST_A 2
#define ST_B 5
#define T_H 0
#define T_O1 250
#define T_O 1800
#define T_S1 128
#define T_S2 950
#define N_GA 4
#define N_X 1
#define D_X 2
#define D_R 3
#define N_ROW 5
#define N_W 5
#define K_W1 5
#define K_W2 10
#define N_CS 3
#define N_F1 4
#define LAST 2
#define N_HA 4
#define POLL_NS 100
constexpr int SPIN_LIMIT = 1 << 18;

struct Scratch {
    uint8_t o[2048 * 1024 * 2];
    uint2 rec[2048];
    float cs[8][3072];
    uint32_t halo[128][512];
    uint32_t h[14336];
    float ypart[8][8][1024];
    uint2 sel[16];
    uint32_t hint[128][8];
    uint32_t epoch;
};
__device__ __align__(1024) Scratch g_scr;

#define TS(i) do {} while (0)
#define TS_END() do {} while (0)
constexpr int SMEM_LAUNCH = SMEM_BYTES;
#define TSC(c, i) do {} while (0)
#define NRETRY() do {} while (0)
__device__ __forceinline__ uint32_t smem_u32(const void* p) { return (uint32_t)__cvta_generic_to_shared(p); }
__device__ __forceinline__ void mbar_init(uint32_t bar, uint32_t cnt) { asm volatile("mbarrier.init.shared::cta.b64 [%0], %1;" ::"r"(bar), "r"(cnt) : "memory"); }
__device__ __forceinline__ void mbar_expect_tx(uint32_t bar, uint32_t bytes) { asm volatile("mbarrier.arrive.expect_tx.shared::cta.b64 _, [%0], %1;" ::"r"(bar), "r"(bytes) : "memory"); }
__device__ __forceinline__ void mbar_arrive(uint32_t bar) { asm volatile("mbarrier.arrive.shared::cta.b64 _, [%0];" ::"r"(bar) : "memory"); }
__device__ __forceinline__ void mbar_arrive_after(uint32_t bar, uint32_t lane, uint32_t dep) {
    asm volatile("{\n.reg .pred p;\n.reg .b32 t;\nsetp.eq.u32 p, %1, 0;\nmad.lo.u32 t, %1, %2, %0;\n@p mbarrier.arrive.shared::cta.b64 _, [t];\n}" ::"r"(bar), "r"(lane), "r"(dep) : "memory");
}
__device__ __forceinline__ void mbar_wait(uint32_t bar, uint32_t parity) {
    asm volatile("{\n.reg .pred P1;\nLAB_WAIT:\nmbarrier.try_wait.parity.shared::cta.b64 P1, [%0], %1;\n@!P1 bra LAB_WAIT;\n}" ::"r"(bar), "r"(parity) : "memory");
}
__device__ __forceinline__ void tma_3d(uint32_t dst, const CUtensorMap* m, uint32_t bar, int c0, int c1, int c2) {
    asm volatile("cp.async.bulk.tensor.3d.shared::cluster.global.mbarrier::complete_tx::bytes [%0], [%1, {%3, %4, %5}], [%2];" ::"r"(dst), "l"(m), "r"(bar), "r"(c0), "r"(c1), "r"(c2) : "memory");
}
__device__ __forceinline__ void tma_2d_once(uint32_t dst, const CUtensorMap* m, uint32_t bar, int c0, int c1) {
    asm volatile("cp.async.bulk.tensor.2d.shared::cluster.global.mbarrier::complete_tx::bytes.L2::cache_hint [%0], [%1, {%3, %4}], [%2], %5;" ::"r"(dst), "l"(m), "r"(bar), "r"(c0), "r"(c1), "l"(0x12F0000000000000ull) : "memory");
}
__device__ __forceinline__ void tma_3d_once(uint32_t dst, const CUtensorMap* m, uint32_t bar, int c0, int c1, int c2) {
    asm volatile("cp.async.bulk.tensor.3d.shared::cluster.global.mbarrier::complete_tx::bytes.L2::cache_hint [%0], [%1, {%3, %4, %5}], [%2], %6;" ::"r"(dst), "l"(m), "r"(bar), "r"(c0), "r"(c1), "r"(c2), "l"(0x12F0000000000000ull) : "memory");
}
__device__ __forceinline__ void tma_4d(uint32_t dst, const CUtensorMap* m, uint32_t bar, int c0, int c1, int c2, int c3) {
    asm volatile("cp.async.bulk.tensor.4d.shared::cluster.global.mbarrier::complete_tx::bytes [%0], [%1, {%3, %4, %5, %6}], [%2];" ::"r"(dst), "l"(m), "r"(bar), "r"(c0), "r"(c1), "r"(c2), "r"(c3) : "memory");
}
__device__ __forceinline__ void tma_store_2d(const CUtensorMap* m, uint32_t src, int c0, int c1) {
    asm volatile("cp.async.bulk.tensor.2d.global.shared::cta.bulk_group [%0, {%2, %3}], [%1];" ::"l"(m), "r"(src), "r"(c0), "r"(c1) : "memory");
}
__device__ __forceinline__ void bulk_g2s(uint32_t dst, const void* src, uint32_t bytes, uint32_t bar) {
    asm volatile("cp.async.bulk.shared::cluster.global.mbarrier::complete_tx::bytes [%0], [%1], %2, [%3];" ::"r"(dst), "l"(src), "r"(bytes), "r"(bar) : "memory");
}
__device__ __forceinline__ void bulk_prefetch(const void* p, uint32_t bytes) { asm volatile("cp.async.bulk.prefetch.L2.global [%0], %1;" ::"l"(p), "r"(bytes) : "memory"); }
__device__ __forceinline__ void fence_async_smem() { asm volatile("fence.proxy.async.shared::cta;" ::: "memory"); }
__device__ __forceinline__ void wg_fence() { asm volatile("wgmma.fence.sync.aligned;" ::: "memory"); }
__device__ __forceinline__ void wg_commit() { asm volatile("wgmma.commit_group.sync.aligned;" ::: "memory"); }
template <int N> __device__ __forceinline__ void wg_wait() { asm volatile("wgmma.wait_group.sync.aligned %0;" ::"n"(N) : "memory"); }
__device__ __forceinline__ uint64_t mkdesc(uint32_t lo, uint32_t hi) { return ((uint64_t)hi << 32) | lo; }
__host__ __device__ constexpr uint32_t dhi(uint32_t sbo, uint32_t mode) { return (sbo >> 4) | (mode << 30); }
__host__ __device__ constexpr uint32_t dlo(uint32_t off, uint32_t lbo) { return (off >> 4) + ((lbo >> 4) << 16); }
__device__ __forceinline__ bool elect_one() {
    uint32_t e;
    asm volatile("{\n.reg .pred p;\nelect.sync _|p, 0xffffffff;\nselp.u32 %0, 1, 0, p;\n}" : "=r"(e));
    return e;
}
template <int R> __device__ __forceinline__ void reg_inc() { asm volatile("setmaxnreg.inc.sync.aligned.u32 %0;" ::"n"(R)); }
template <int R> __device__ __forceinline__ void reg_dec() { asm volatile("setmaxnreg.dec.sync.aligned.u32 %0;" ::"n"(R)); }
__device__ __forceinline__ void bar_sync(int id, int n) { asm volatile("bar.sync %0, %1;" ::"r"(id), "r"(n) : "memory"); }
__device__ __forceinline__ void bar_arrive(int id, int n) { asm volatile("bar.arrive %0, %1;" ::"r"(id), "r"(n) : "memory"); }
__device__ __forceinline__ uint32_t pack_bf16(float lo, float hi) { uint32_t r; asm("cvt.rn.bf16x2.f32 %0, %1, %2;" : "=r"(r) : "f"(hi), "f"(lo)); return r; }
__device__ __forceinline__ float bf_lo(uint32_t u) { return __uint_as_float(u << 16); }
__device__ __forceinline__ float bf_hi(uint32_t u) { return __uint_as_float(u & 0xffff0000u); }
__device__ __forceinline__ float bf16r(float v) { return bf_lo(pack_bf16(v, 0.f)); }
__device__ __forceinline__ uint32_t tagw(uint32_t w, uint32_t m, uint32_t tag) { uint32_t r; asm("lop3.b32 %0, %1, %2, %3, 0xb8;" : "=r"(r) : "r"(w), "r"(m), "r"(tag)); return r; }
__device__ __forceinline__ uint32_t tagf(float f, uint32_t tag) { return tagw(__float_as_uint(f), 1u, tag); }
__device__ __forceinline__ uint32_t movm(uint32_t a) { uint32_t d; asm volatile("movmatrix.sync.aligned.m8n8.trans.b16 %0, %1;" : "=r"(d) : "r"(a)); return d; }
__device__ __forceinline__ void mma16816(float (&c)[4], uint32_t a0, uint32_t a1, uint32_t a2, uint32_t a3, uint32_t b0, uint32_t b1) {
    asm volatile("mma.sync.aligned.m16n8k16.row.col.f32.bf16.bf16.f32 {%0,%1,%2,%3}, {%4,%5,%6,%7}, {%8,%9}, {%0,%1,%2,%3};"
                 : "+f"(c[0]), "+f"(c[1]), "+f"(c[2]), "+f"(c[3]) : "r"(a0), "r"(a1), "r"(a2), "r"(a3), "r"(b0), "r"(b1));
}
__device__ __forceinline__ void mma1688(float (&c)[4], uint32_t a0, uint32_t a1, uint32_t b0) {
    asm volatile("mma.sync.aligned.m16n8k8.row.col.f32.bf16.bf16.f32 {%0,%1,%2,%3}, {%4,%5}, {%6}, {%0,%1,%2,%3};"
                 : "+f"(c[0]), "+f"(c[1]), "+f"(c[2]), "+f"(c[3]) : "r"(a0), "r"(a1), "r"(b0));
}
__device__ __forceinline__ uint32_t ld_rlx(const void* p) { uint32_t v; asm volatile("ld.relaxed.gpu.global.u32 %0, [%1];" : "=r"(v) : "l"(p) : "memory"); return v; }
__device__ __forceinline__ uint2 ld_rlx2(const void* p) { uint2 v; asm volatile("ld.relaxed.gpu.global.v2.u32 {%0,%1}, [%2];" : "=r"(v.x), "=r"(v.y) : "l"(p) : "memory"); return v; }
__device__ __forceinline__ uint4 ld_rlx4(const void* p) { uint4 v; asm volatile("ld.relaxed.gpu.global.v4.u32 {%0,%1,%2,%3}, [%4];" : "=r"(v.x), "=r"(v.y), "=r"(v.z), "=r"(v.w) : "l"(p) : "memory"); return v; }
__device__ __forceinline__ void st_rlx(void* p, uint32_t v) { asm volatile("st.relaxed.gpu.global.u32 [%0], %1;" ::"l"(p), "r"(v) : "memory"); }
__device__ __forceinline__ void st_rlx2(void* p, uint32_t a, uint32_t b) { asm volatile("st.relaxed.gpu.global.v2.u32 [%0], {%1,%2};" ::"l"(p), "r"(a), "r"(b) : "memory"); }
__device__ __forceinline__ void st_rlx4(void* p, uint32_t a, uint32_t b, uint32_t c, uint32_t d) { asm volatile("st.relaxed.gpu.global.v4.u32 [%0], {%1,%2,%3,%4};" ::"l"(p), "r"(a), "r"(b), "r"(c), "r"(d) : "memory"); }
__device__ __forceinline__ uint4 ldg_nc(const void* p) { uint4 v; asm volatile("ld.global.nc.v4.u32 {%0,%1,%2,%3}, [%4];" : "=r"(v.x), "=r"(v.y), "=r"(v.z), "=r"(v.w) : "l"(p)); return v; }
__device__ __forceinline__ uint32_t mism(uint32_t a, uint32_t b, uint32_t tag) { uint32_t r; asm("lop3.b32 %0, %1, %2, %3, 0x7e;" : "=r"(r) : "r"(a), "r"(b), "r"(tag)); return r; }
__device__ __forceinline__ uint32_t mism(const uint4& v, uint32_t tag) { return mism(v.x, v.y, tag) | mism(v.z, v.w, tag); }
__device__ __forceinline__ void prefetch_l2(const void* p) { asm volatile("prefetch.global.L2 [%0];" ::"l"(p)); }
__device__ __forceinline__ void nap(int n) {
#pragma unroll 1
    for (int i = 0; i < n; i++) __nanosleep(100);
}
__device__ __forceinline__ uint32_t now() { uint32_t t; asm volatile("mov.u32 %0, %%globaltimer_lo;" : "=r"(t)); return t; }
__device__ __forceinline__ void until(uint32_t t) {
    while (t - now() - 1 < 16384u) __nanosleep(50);
}
__device__ __forceinline__ uint32_t opaque(uint32_t v) { return __shfl_xor_sync(0xffffffffu, v, 0); }
__device__ __forceinline__ void sts4(uint32_t a, uint32_t x, uint32_t y, uint32_t z, uint32_t w) { asm volatile("st.shared.v4.u32 [%0], {%1,%2,%3,%4};" ::"r"(a), "r"(x), "r"(y), "r"(z), "r"(w) : "memory"); }
__device__ __forceinline__ void sts2(uint32_t a, uint32_t x, uint32_t y) { asm volatile("st.shared.v2.u32 [%0], {%1,%2};" ::"r"(a), "r"(x), "r"(y) : "memory"); }
__device__ __forceinline__ uint4 lds4(uint32_t a) { uint4 v; asm volatile("ld.shared.v4.u32 {%0,%1,%2,%3}, [%4];" : "=r"(v.x), "=r"(v.y), "=r"(v.z), "=r"(v.w) : "r"(a) : "memory"); return v; }
__device__ __forceinline__ float4 lds4f(uint32_t a) { float4 v; asm volatile("ld.shared.v4.f32 {%0,%1,%2,%3}, [%4];" : "=f"(v.x), "=f"(v.y), "=f"(v.z), "=f"(v.w) : "r"(a) : "memory"); return v; }
__device__ __forceinline__ uint2 lds2(uint32_t a) { uint2 v; asm volatile("ld.shared.v2.u32 {%0,%1}, [%2];" : "=r"(v.x), "=r"(v.y) : "r"(a) : "memory"); return v; }
__device__ __forceinline__ float2 lds2f(uint32_t a) { float2 v; asm volatile("ld.shared.v2.f32 {%0,%1}, [%2];" : "=f"(v.x), "=f"(v.y) : "r"(a) : "memory"); return v; }
__device__ __forceinline__ uint32_t lds1(uint32_t a) { uint32_t v; asm volatile("ld.shared.u32 %0, [%1];" : "=r"(v) : "r"(a) : "memory"); return v; }
__device__ __forceinline__ float lds1f(uint32_t a) { return __uint_as_float(lds1(a)); }
__device__ __forceinline__ void sts1(uint32_t a, uint32_t v) { asm volatile("st.shared.u32 [%0], %1;" ::"r"(a), "r"(v) : "memory"); }
__device__ __forceinline__ uint32_t redux_max(uint32_t v) { uint32_t r; asm volatile("redux.sync.max.u32 %0, %1, 0xffffffff;" : "=r"(r) : "r"(v)); return r; }
__device__ __forceinline__ float ex2(float x) { float r; asm("ex2.approx.ftz.f32 %0, %1;" : "=f"(r) : "f"(x)); return r; }
__device__ __forceinline__ float rcp(float x) { float r; asm("rcp.approx.ftz.f32 %0, %1;" : "=f"(r) : "f"(x)); return r; }
__device__ __forceinline__ float sigmoidf(float v) { return rcp(1.f + ex2(v * -1.4426950408889634f)); }

template <int TA, int TB>
__device__ __forceinline__ void wgmma_n192(float (&d)[96], uint64_t da, uint64_t db, int acc = 1) {
    asm volatile("{\n.reg .pred p;\nsetp.ne.b32 p, %100, 0;\n"
        "wgmma.mma_async.sync.aligned.m64n192k16.f32.bf16.bf16 "
        "{%0, %1, %2, %3, %4, %5, %6, %7, %8, %9, %10, %11, %12, %13, %14, %15, "
        "%16, %17, %18, %19, %20, %21, %22, %23, %24, %25, %26, %27, %28, %29, %30, %31, "
        "%32, %33, %34, %35, %36, %37, %38, %39, %40, %41, %42, %43, %44, %45, %46, %47, "
        "%48, %49, %50, %51, %52, %53, %54, %55, %56, %57, %58, %59, %60, %61, %62, %63, "
        "%64, %65, %66, %67, %68, %69, %70, %71, %72, %73, %74, %75, %76, %77, %78, %79, "
        "%80, %81, %82, %83, %84, %85, %86, %87, %88, %89, %90, %91, %92, %93, %94, %95}, "
        "%96, %97, p, 1, 1, %98, %99;\n}\n"
        : "+f"(d[0]), "+f"(d[1]), "+f"(d[2]), "+f"(d[3]), "+f"(d[4]), "+f"(d[5]), "+f"(d[6]), "+f"(d[7]),
          "+f"(d[8]), "+f"(d[9]), "+f"(d[10]), "+f"(d[11]), "+f"(d[12]), "+f"(d[13]), "+f"(d[14]), "+f"(d[15]),
          "+f"(d[16]), "+f"(d[17]), "+f"(d[18]), "+f"(d[19]), "+f"(d[20]), "+f"(d[21]), "+f"(d[22]), "+f"(d[23]),
          "+f"(d[24]), "+f"(d[25]), "+f"(d[26]), "+f"(d[27]), "+f"(d[28]), "+f"(d[29]), "+f"(d[30]), "+f"(d[31]),
          "+f"(d[32]), "+f"(d[33]), "+f"(d[34]), "+f"(d[35]), "+f"(d[36]), "+f"(d[37]), "+f"(d[38]), "+f"(d[39]),
          "+f"(d[40]), "+f"(d[41]), "+f"(d[42]), "+f"(d[43]), "+f"(d[44]), "+f"(d[45]), "+f"(d[46]), "+f"(d[47]),
          "+f"(d[48]), "+f"(d[49]), "+f"(d[50]), "+f"(d[51]), "+f"(d[52]), "+f"(d[53]), "+f"(d[54]), "+f"(d[55]),
          "+f"(d[56]), "+f"(d[57]), "+f"(d[58]), "+f"(d[59]), "+f"(d[60]), "+f"(d[61]), "+f"(d[62]), "+f"(d[63]),
          "+f"(d[64]), "+f"(d[65]), "+f"(d[66]), "+f"(d[67]), "+f"(d[68]), "+f"(d[69]), "+f"(d[70]), "+f"(d[71]),
          "+f"(d[72]), "+f"(d[73]), "+f"(d[74]), "+f"(d[75]), "+f"(d[76]), "+f"(d[77]), "+f"(d[78]), "+f"(d[79]),
          "+f"(d[80]), "+f"(d[81]), "+f"(d[82]), "+f"(d[83]), "+f"(d[84]), "+f"(d[85]), "+f"(d[86]), "+f"(d[87]),
          "+f"(d[88]), "+f"(d[89]), "+f"(d[90]), "+f"(d[91]), "+f"(d[92]), "+f"(d[93]), "+f"(d[94]), "+f"(d[95])
        : "l"(da), "l"(db), "n"(TA), "n"(TB), "r"(acc));
}
template <int TA, int TB>
__device__ __forceinline__ void wgmma_n128(float (&d)[64], uint64_t da, uint64_t db, int acc = 1) {
    asm volatile("{\n.reg .pred p;\nsetp.ne.b32 p, %68, 0;\n"
        "wgmma.mma_async.sync.aligned.m64n128k16.f32.bf16.bf16 "
        "{%0, %1, %2, %3, %4, %5, %6, %7, %8, %9, %10, %11, %12, %13, %14, %15, "
        "%16, %17, %18, %19, %20, %21, %22, %23, %24, %25, %26, %27, %28, %29, %30, %31, "
        "%32, %33, %34, %35, %36, %37, %38, %39, %40, %41, %42, %43, %44, %45, %46, %47, "
        "%48, %49, %50, %51, %52, %53, %54, %55, %56, %57, %58, %59, %60, %61, %62, %63}, "
        "%64, %65, p, 1, 1, %66, %67;\n}\n"
        : "+f"(d[0]), "+f"(d[1]), "+f"(d[2]), "+f"(d[3]), "+f"(d[4]), "+f"(d[5]), "+f"(d[6]), "+f"(d[7]),
          "+f"(d[8]), "+f"(d[9]), "+f"(d[10]), "+f"(d[11]), "+f"(d[12]), "+f"(d[13]), "+f"(d[14]), "+f"(d[15]),
          "+f"(d[16]), "+f"(d[17]), "+f"(d[18]), "+f"(d[19]), "+f"(d[20]), "+f"(d[21]), "+f"(d[22]), "+f"(d[23]),
          "+f"(d[24]), "+f"(d[25]), "+f"(d[26]), "+f"(d[27]), "+f"(d[28]), "+f"(d[29]), "+f"(d[30]), "+f"(d[31]),
          "+f"(d[32]), "+f"(d[33]), "+f"(d[34]), "+f"(d[35]), "+f"(d[36]), "+f"(d[37]), "+f"(d[38]), "+f"(d[39]),
          "+f"(d[40]), "+f"(d[41]), "+f"(d[42]), "+f"(d[43]), "+f"(d[44]), "+f"(d[45]), "+f"(d[46]), "+f"(d[47]),
          "+f"(d[48]), "+f"(d[49]), "+f"(d[50]), "+f"(d[51]), "+f"(d[52]), "+f"(d[53]), "+f"(d[54]), "+f"(d[55]),
          "+f"(d[56]), "+f"(d[57]), "+f"(d[58]), "+f"(d[59]), "+f"(d[60]), "+f"(d[61]), "+f"(d[62]), "+f"(d[63])
        : "l"(da), "l"(db), "n"(TA), "n"(TB), "r"(acc));
}
template <int TB>
__device__ __forceinline__ void wgmma_rs_n128(float (&d)[64], uint32_t a0, uint32_t a1, uint32_t a2, uint32_t a3, uint64_t db) {
    asm volatile("{\n.reg .pred p;\nsetp.ne.b32 p, 1, 0;\n"
        "wgmma.mma_async.sync.aligned.m64n128k16.f32.bf16.bf16 "
        "{%0, %1, %2, %3, %4, %5, %6, %7, %8, %9, %10, %11, %12, %13, %14, %15, "
        "%16, %17, %18, %19, %20, %21, %22, %23, %24, %25, %26, %27, %28, %29, %30, %31, "
        "%32, %33, %34, %35, %36, %37, %38, %39, %40, %41, %42, %43, %44, %45, %46, %47, "
        "%48, %49, %50, %51, %52, %53, %54, %55, %56, %57, %58, %59, %60, %61, %62, %63}, "
        "{%64, %65, %66, %67}, %68, p, 1, 1, %69;\n}\n"
        : "+f"(d[0]), "+f"(d[1]), "+f"(d[2]), "+f"(d[3]), "+f"(d[4]), "+f"(d[5]), "+f"(d[6]), "+f"(d[7]),
          "+f"(d[8]), "+f"(d[9]), "+f"(d[10]), "+f"(d[11]), "+f"(d[12]), "+f"(d[13]), "+f"(d[14]), "+f"(d[15]),
          "+f"(d[16]), "+f"(d[17]), "+f"(d[18]), "+f"(d[19]), "+f"(d[20]), "+f"(d[21]), "+f"(d[22]), "+f"(d[23]),
          "+f"(d[24]), "+f"(d[25]), "+f"(d[26]), "+f"(d[27]), "+f"(d[28]), "+f"(d[29]), "+f"(d[30]), "+f"(d[31]),
          "+f"(d[32]), "+f"(d[33]), "+f"(d[34]), "+f"(d[35]), "+f"(d[36]), "+f"(d[37]), "+f"(d[38]), "+f"(d[39]),
          "+f"(d[40]), "+f"(d[41]), "+f"(d[42]), "+f"(d[43]), "+f"(d[44]), "+f"(d[45]), "+f"(d[46]), "+f"(d[47]),
          "+f"(d[48]), "+f"(d[49]), "+f"(d[50]), "+f"(d[51]), "+f"(d[52]), "+f"(d[53]), "+f"(d[54]), "+f"(d[55]),
          "+f"(d[56]), "+f"(d[57]), "+f"(d[58]), "+f"(d[59]), "+f"(d[60]), "+f"(d[61]), "+f"(d[62]), "+f"(d[63])
        : "r"(a0), "r"(a1), "r"(a2), "r"(a3), "l"(db), "n"(TB));
}
template <int TA, int TB>
__device__ __forceinline__ void wgmma_n8(float (&d)[4], uint64_t da, uint64_t db, int acc = 1) {
    asm volatile("{\n.reg .pred p;\nsetp.ne.b32 p, %8, 0;\n"
        "wgmma.mma_async.sync.aligned.m64n8k16.f32.bf16.bf16 "
        "{%0, %1, %2, %3}, "
        "%4, %5, p, 1, 1, %6, %7;\n}\n"
        : "+f"(d[0]), "+f"(d[1]), "+f"(d[2]), "+f"(d[3])
        : "l"(da), "l"(db), "n"(TA), "n"(TB), "r"(acc));
}

__device__ __forceinline__ uint32_t norm_pair(uint32_t u, float m, float rinv) {
    uint32_t d = pack_bf16(bf_lo(u) - m, bf_hi(u) - m);
    return pack_bf16(bf_lo(d) * rinv, bf_hi(d) * rinv);
}

struct Roles { uint16_t v[132]; };

__global__ void __launch_bounds__(512, 1)
fused_kernel(int by_sm, const __nv_bfloat16* __restrict__ x, const __nv_bfloat16* __restrict__ wqkv, const __nv_bfloat16* __restrict__ wr,
             Scratch* const S, const char* __restrict__ wg, const char* __restrict__ wu, const char* __restrict__ wd, const char* __restrict__ wo,
             const __grid_constant__ Roles roles,
             const __grid_constant__ CUtensorMap mw, const __grid_constant__ CUtensorMap mx, const __grid_constant__ CUtensorMap mwo,
             const __grid_constant__ CUtensorMap mxs, const __grid_constant__ CUtensorMap mcs, const __grid_constant__ CUtensorMap mout, const __grid_constant__ CUtensorMap mgu, const __grid_constant__ CUtensorMap mwd) {
    extern __shared__ __align__(1024) uint8_t smem[];
    constexpr uint32_t sb = 1024, bars = sb + OFF_BAR, sd = sb >> 4;
    const int tid = threadIdx.x, lane = tid & 31;
    asm volatile("{\n.reg .pred p, q;\nsetp.lt.u32 p, %2, 16;\nsetp.lt.u32 q, %2, 24;\n@p prefetch.global.L2 [%0];\n@p prefetch.global.L2 [%0 + 128];\n@q prefetch.global.L2 [%1];\n}" ::
                 "l"((const char*)x + (blockIdx.x * 16 + tid - 32) % 2048 * 2048), "l"((const char*)wqkv + (blockIdx.x * 24 + tid - 32) * 128), "r"(tid - 32));
    const int warp = __shfl_sync(0xffffffffu, tid >> 5, 0);
    uint32_t smid;
    asm volatile("mov.u32 %0, %%smid;" : "=r"(smid));
    const int role = roles.v[by_sm ? smid : blockIdx.x], fb = role & 255, b = role >> 8, kc = fb >> 4, c2 = fb & 15;
    const int mt = b >> 4, nt = b & 15, hp = b & 1, cb = nt >> 1;
    const int par = mt >> 2, j0 = (mt & 3) * 256;
    uint8_t* const g_o = S->o;

    auto load_stage = [&](int p, uint32_t so, int bi) {
        const uint32_t fullA = bars + 8 * (B_FULLA + bi), fullB = bars + 8 * (B_FULLB + bi);
        mbar_expect_tx(fullA, 40960);
        tma_3d(sb + so + 16384, &mw, fullA, nt * 64, p * 64, 0);
        tma_4d(sb + so, &mx, fullA, par * 1024 + p * 64, 0, (j0 >> 5) + 4, 0);
        mbar_expect_tx(fullB, 16384);
        tma_4d(sb + so + 40960, &mx, fullB, par * 1024 + p * 64, 0, j0 >> 5, 0);
    };
    if (warp == 0 && fb < 128 && elect_one()) {
        mbar_init(bars + 8 * B_FULLA, 1); mbar_init(bars + 8 * B_FULLB, 1);
        load_stage(0, STAGE, 0);
    }
    if (fb >= 128) {
        if (fb > 128) { nap(16); TS_END(); return; }
        const uint32_t tag = (ld_rlx(&S->epoch) & 1) - 1;
        if (tid < 8) st_rlx2(&S->sel[tid], ~tag, ~tag);
        uint4 ra, rb;
#pragma unroll 1
        for (int it = 0; it < SPIN_LIMIT; it++) {
            ra = ld_rlx4(&S->rec[tid * 2]); rb = ld_rlx4(&S->rec[1024 + tid * 2]);
            if (!__any_sync(0xffffffffu, (mism(ra.x, ra.z, tag) | mism(rb.x, rb.z, tag)) & 0x8000u)) break;
        }
        __syncwarp();
        TSC(tid == 0, 31);
        sts4(sb + 1024 + tid * 16, ra.y, rb.y, ra.w, rb.w);
        uint4 k = make_uint4(ra.x, ra.z, rb.x, rb.z);
        uint32_t cand;
#pragma unroll 1
        for (int pass = 0; pass < 2; pass++) {
            const uint32_t a0 = max(k.x, k.y), a1 = min(k.x, k.y), a2 = max(k.z, k.w), a3 = min(k.z, k.w), c1 = min(a0, a2), c2 = max(a1, a3);
            k = make_uint4(max(a0, a2), max(c1, c2), min(c1, c2), min(a1, a3));
#pragma unroll
            for (int r = 0; r < 8; r++) {
                const uint32_t m = redux_max(k.x);
                if (lane == r) cand = m;
                if (k.x == m) k = make_uint4(k.y, k.z, k.w, 0);
            }
            if (pass) break;
            if (lane < 8) sts1(sb + (warp * 8 + lane) * 4, cand);
            __syncthreads();
            if (warp) { TS_END(); return; }
            k = lds4(sb + lane * 16);
            TSC(TIMING == 12 && tid == 0 && k.x != 0x12345, 40);
        }
        if (lane < 8) st_rlx2(&S->sel[lane], cand, lds1(sb + 1024 + (~cand & 0x7ffu) * 4));
        TSC(tid == 0, 20);
        TS_END();
        return;
    }
    uint32_t epoch;
    if (warp >> 2 == 2) epoch = ld_rlx(&S->epoch);
    if (warp == 1 && elect_one()) {
#pragma unroll
        for (int i = 0; i < B_WOFULL; i++)
            if (i != B_FULLA && i != B_FULLB) mbar_init(bars + 8 * i, i >= B_FFULL && i < B_FEMPTY ? 5 : 1);
    }
    if (warp == 4 && elect_one()) {
#pragma unroll
        for (int i = B_EMPTY; i < NBAR; i++) mbar_init(bars + 8 * i, i < B_UPD ? 2 : i < B_AUX ? 4 : i == B_AUX ? 7 : i == B_CSDONE ? 3 : 8);
    }
    __syncthreads();

    if (warp >= 12) {
        reg_dec<24>();
        if (warp > 12) {
            const int p = warp - 13;
            if (p == 1) {
                float sw = 0.f;
                mbar_wait(bars + 8 * (B_ROW + 4), 0);
#pragma unroll 1
                for (int i = 0; i < 16; i++) { const uint32_t q = lds1(sb + OFF_FA + i * 128 + lane * 4); sw += bf_lo(q) + bf_hi(q); }
#pragma unroll 1
                for (int o = 1; o < 32; o <<= 1) sw += __shfl_xor_sync(0xffffffffu, sw, o);
                if (lane == 0) { sts1(sb + OFF_TAG + 4, __float_as_uint(sw)); mbar_arrive(bars + 8 * B_SW); }
            } else {
#pragma unroll 1
                for (int q = 0; q < 4; q++) {
                    nap(p ? (q ? D_R : N_ROW) : (q ? D_X : N_X));
                    if (p == 0) {
                        const __nv_bfloat16* xp = x + (size_t)((j0 + nt * 16 + (lane >> 1)) * 2 + par) * 1024 + q * 256 + (lane & 1) * 64;
                        prefetch_l2(xp); prefetch_l2(xp + 128);
                    } else if (elect_one()) {
                        mbar_expect_tx(bars + 8 * (B_ROW + q), 8192);
                        tma_3d(sb + OFF_FW + q * 8192, &mxs, bars + 8 * (B_ROW + q), 0, j0 + nt * 16, par * 16 + q * 4);
                    }
                }
                if (p == 0) nap(N_CS);
            }
            const uint32_t stg = sb + OFF_FW + 32768 + p * 4096 + lane * 16;
            float c[8];
#pragma unroll
            for (int i = 0; i < 8; i++) c[i] = 0.f;
#pragma unroll 1
            for (int n = 0; n < 10; n++) {
                const uint32_t bo = (n & 1) * 2048, bar = bars + 8 * (B_CS + 2 * p + (n & 1));
                if (n >= 2) {
                    mbar_wait(bar, ~(n >> 1) & 1);
#pragma unroll 2
                    for (int i = 0; i < 4; i++) {
                        const uint4 v = lds4(stg + bo + i * 512);
                        c[0] += bf_lo(v.x); c[1] += bf_hi(v.x); c[2] += bf_lo(v.y); c[3] += bf_hi(v.y);
                        c[4] += bf_lo(v.z); c[5] += bf_hi(v.z); c[6] += bf_lo(v.w); c[7] += bf_hi(v.w);
                    }
                    asm volatile("" :: "f"(c[7]));
                    __syncwarp();
                }
                if (n < 8 && elect_one()) {
                    mbar_expect_tx(bar, 2048);
                    tma_3d(sb + OFF_FW + 32768 + p * 4096 + bo, &mcs, bar, p * 1024 + nt * 64, mt * 8, 2 * n);
                }
            }
            sts4(stg + lane * 16, __float_as_uint(c[0]), __float_as_uint(c[1]), __float_as_uint(c[2]), __float_as_uint(c[3]));
            sts4(stg + lane * 16 + 16, __float_as_uint(c[4]), __float_as_uint(c[5]), __float_as_uint(c[6]), __float_as_uint(c[7]));
            bar_sync(13, 128);
            const uint32_t tag = lds1(sb + OFF_TAG);
            float* gcs = &S->cs[0][p * 1024 + nt * 64];
            {
                const float2 a0 = lds2f(stg - lane * 8), a1 = lds2f(stg - lane * 8 + 256), a2 = lds2f(stg - lane * 8 + 512), a3 = lds2f(stg - lane * 8 + 768);
                st_rlx2(gcs + mt * 3072 + lane * 2, tagf((a0.x + a1.x) + (a2.x + a3.x), tag), __float_as_uint((a0.y + a1.y) + (a2.y + a3.y)));
            }
            fence_async_smem();
            __syncwarp();
            if (lane == 0) mbar_arrive(bars + 8 * B_CSDONE);
            TSC(warp == 13 && lane == 0, 19);
            {
                uint4 v[4];
                const float* src = gcs + (lane >> 4) * 4 * 3072 + (lane & 15) * 4;
#pragma unroll 1
                for (int it = 0; it < SPIN_LIMIT; it++) {
#pragma unroll
                    for (int m = 0; m < 4; m++) v[m] = ld_rlx4(src + m * 3072);
                    if (!__any_sync(0xffffffffu, (mism(v[0].x, v[1].x, tag) | mism(v[2].x, v[3].x, tag)) & 1)) break;
                }
                __syncwarp();
#pragma unroll
                for (int c = 0; c < 4; c++) {
                    const float a = (__uint_as_float((&v[0].x)[c]) + __uint_as_float((&v[1].x)[c])) + (__uint_as_float((&v[2].x)[c]) + __uint_as_float((&v[3].x)[c]));
                    (&v[0].x)[c] = __float_as_uint(a + __shfl_xor_sync(0xffffffffu, a, 16));
                }
                const uint32_t ca = sb + OFF_CS + p * 384 + ((lane & 15) >> 1) * 48 + (lane & 1) * 8;
#pragma unroll 1
                for (int r = 0; r < 3; r++) {
                    const uint32_t u0 = pack_bf16(__uint_as_float(v[0].x), __uint_as_float(v[0].y)), u1 = pack_bf16(__uint_as_float(v[0].z), __uint_as_float(v[0].w));
                    sts2(ca + r * 16, u0, u1);
                    v[0].x = __float_as_uint(__uint_as_float(v[0].x) - bf_lo(u0)); v[0].y = __float_as_uint(__uint_as_float(v[0].y) - bf_hi(u0));
                    v[0].z = __float_as_uint(__uint_as_float(v[0].z) - bf_lo(u1)); v[0].w = __float_as_uint(__uint_as_float(v[0].w) - bf_hi(u1));
                }
                if (lane < 20) sts1(sb + OFF_CS + 1152 + lane * 4, 0);
                fence_async_smem();
            }
            if (p == 1) { if (lane < 2) st_rlx4(&S->hint[b][lane * 4], ~tag, ~tag, ~tag, ~tag); }
            else { st_rlx4(&S->halo[b][p * 128 + lane * 4], ~tag, ~tag, ~tag, ~tag); st_rlx4(&S->halo[b][p * 128 + 128 + lane * 4], ~tag, ~tag, ~tag, ~tag); }
            __syncwarp();
            if (lane == 0) mbar_arrive(bars + 8 * B_AUX);
            TSC(warp == 13 && lane == 0, 21);
            mbar_wait(bars + 8 * B_PART, 0);
            mbar_wait(bars + 8 * (B_EMPTY + 2), 0);
            if (p == 0) {
                if (j0) {
                    nap(N_HA);
#pragma unroll 1
                    for (int it = 0; it < SPIN_LIMIT; it++) {
                        TSC(TIMING == 15 && lane == 0 && it < 8, 40 + it);
                        if (elect_one()) { mbar_expect_tx(bars + 8 * B_CS, 2048); bulk_g2s(sb + OFF_HALO, S->halo[b - 16], 2048, bars + 8 * B_CS); }
                        mbar_wait(bars + 8 * B_CS, it & 1);
                        const uint32_t a = sb + OFF_HALO + lane * 16;
                        if (!__any_sync(0xffffffffu, (mism(lds1(a), lds1(a + 512), tag) | mism(lds1(a + 1024), lds1(a + 1536), tag)) & 1)) break;
                    }
                } else {
#pragma unroll
                    for (int c = 0; c < 4; c++) sts4(sb + OFF_HALO + c * 512 + lane * 16, 0, 0, 0, 0);
                }
                __syncwarp();
                bar_arrive(3, 64);
                TSC(TIMING >= 11 && lane == 0, 34);
            } else {
                const int w = p - 1;
                const uint8_t* osrc = g_o + (size_t)((mt * 2 + hp) * 2 + w) * 131072;
                const bool far = w > hp && j0 && lane >= 16;
                const uint32_t* hsrc = &S->hint[b & 0x70][0] + ((lane & 15) - (far ? 16 : 0)) * 8;
                if (lane == 0 && !w) st_rlx(&S->hint[b][0], tagw(now(), 1u, tag));
                uint32_t hv;
#pragma unroll 1
                for (int it = 0; it < SPIN_LIMIT; it++) {
                    hv = ld_rlx(hsrc);
                    if (!__any_sync(0xffffffffu, (hv ^ tag) & 1)) break;
                }
                TSC(TIMING == 11 && lane == 0, 32 + w);
                const uint32_t tn = __shfl_sync(0xffffffffu, hv, 0) - 0x40000000u;
                hv = redux_max(hv - tn + (far ? T_H : 0)) + tn + T_O + w * T_O1;
                mbar_wait(bars + 8 * (w ? B_AST : B_G1DONE), 0);
                if (elect_one()) {
#pragma unroll 1
                    for (int st = 0; st < 8; st++) {
                        const uint32_t full = bars + 8 * (B_OFULL + 8 * w + st);
                        if (st >= 2) mbar_wait(full + 8 * (B_DONE - B_OFULL - 2), 0);
                        if (st < 3) until(hv + (st == 2 ? T_S2 : st * T_S1));
                        TSC(st == 0, 28 + w);
                        mbar_expect_tx(full, 16384);
                        bulk_g2s(sb + (w ? OFF_O1 : OFF_O0) + (st & 1) * 16384, osrc + st * 16384, 16384, full);
                    }
                }
            }
            TS_END();
            return;
        }
        if (elect_one()) {
            auto load_wo = [&](int s, uint32_t ws) {
                mbar_expect_tx(bars + 8 * (B_WOFULL + s), 32768);
                tma_4d(ws, &mwo, bars + 8 * (B_WOFULL + s), 0, s * 8, 0, cb * 2);
            };
            uint32_t so = 2 * STAGE, ph = 1, cnt = PF_CNT << 4;
            int bi = 1, q = 0;
            mbar_expect_tx(bars + 8 * (B_ROW + 4), 2048);
            bulk_g2s(sb + OFF_FA, wr, 2048, bars + 8 * (B_ROW + 4));
            if (smem_u32(smem) != sb) __trap();
            const char* pf = (b < 64 ? wg : wu) + (b & 63) * 7168;
#pragma unroll 1
            for (int p = 1; p < 16; p++) {
                if (p < 3) nap(p == 1 ? N_S1 : N_S2);
                mbar_wait(bars + 8 * (B_EMPTY + bi), ph);
                load_stage(p, so, bi);
                if (p >= 2 && p < 5) {
                    const int k0 = p == 2 ? 3 : p == 3 ? K_W1 : K_W2, n = ((p == 2 ? K_W1 : p == 3 ? K_W2 : 16) - k0) * 3072;
                    if (p == 2) nap(N_W);
                    bulk_prefetch((const char*)wqkv + k0 * 393216 + b * n, n);
                }
#pragma unroll 1
                for (int e = q + (cnt & 3); q < e; q++) {
                    if (q == 16) pf = wd + mt * 7 * 131072 + nt * 8192;
                    if (q == 23) pf = wo + b * 8192;
                    bulk_prefetch(pf, q < 16 ? 7168 : 8192);
                    pf += q < 16 ? 64 * 7168 : q < 23 ? 131072 : 1048576;
                }
                cnt >>= 2;
                so = so == 2 * STAGE ? 0 : so + STAGE;
                if (++bi == 3) { bi = 0; ph ^= 1; }
            }
            TS(27);
            uint32_t ws = sb + OFF_WO0;
#pragma unroll 1
            for (int i = 0; i < 8; i++) {
                if (i < 2) {
                    mbar_wait(bars + 8 * (B_EMPTY + 1 + i), 0);
                    mbar_expect_tx(bars + 8 * B_XR, 16384);
                    tma_4d(sb + (i ? 0 : OFF_X1), &mx, bars + 8 * B_XR, par * 1024 + cb * 128 + 64 - i * 64, 0, (j0 >> 5) + hp * 4, 0);
                }
                if (i == 1) {
                    mbar_expect_tx(bars + 8 * B_F2FULL, 8192);
                    tma_2d_once(sb + OFF_F2X, &mwd, bars + 8 * B_F2FULL, c2 * 64, kc * 448);
                }
                if (i) {
                    mbar_wait(bars + 8 * (i == 1 ? B_G1DONE : i == 2 ? B_F2DONE : B_DONE - NWO + i), 0);
                    if (i > 1) mbar_wait(bars + 8 * (i == 2 ? B_OFULL + 8 : B_DONE + 8 - NWO + i), 0);
                }
                load_wo(i, ws);
                ws = wo_next(ws, sb, 0);
            }
        }
        TS_END();
    } else if (warp >= 8) {
        reg_dec<40>();
        const int p = warp - 8;
        const bool f1 = fb < 112;
        auto ffn_w = [&](int n, int s) {
            const uint32_t dst = sb + OFF_FW + s * 16384;
            if (n < 8) {
                mbar_expect_tx(bars + 8 * (B_FFULL + s), 16384);
                tma_3d_once(dst, &mgu, bars + 8 * (B_FFULL + s), fb * 32, n * 128, 0);
            } else {
                mbar_expect_tx(bars + 8 * B_F2FULL, 16384);
                tma_2d_once(dst, &mwd, bars + 8 * B_F2FULL, c2 * 64, kc * 448 + 64 + s * 128);
                tma_2d_once(dst + 8192, &mwd, bars + 8 * B_F2FULL, c2 * 64, kc * 448 + 128 + s * 128);
            }
        };
        const uint32_t tag = (epoch & 1) - 1;
        {
            const int ta = tid - 256;
            if (ta < 48) st_rlx4(&S->cs[mt][(ta >> 4) * 1024 + nt * 64 + (ta & 15) * 4], ~tag, ~tag, ~tag, ~tag);
        }
        float s1 = 0.f, s2 = 0.f, sr = 0.f, sw, sh = 0.f;
        {
            const uint32_t xa = sb + OFF_FW + p * 512 + lane * 16, wa = sb + OFF_FA + (((p * 4 + (lane >> 3)) ^ lane) & 7) * 16;
            TSC(TIMING == 12 && lane == 0, 50 + p);
            mbar_wait(bars + 8 * (B_ROW + 4), 0);
            {
                float c1 = 0.f, c2 = 0.f, cr = 0.f;
#pragma unroll 1
                for (int q = 0; q < 4; q++) {
                mbar_wait(bars + 8 * (B_ROW + q), 0);
                TSC(TIMING == 12 && tid == 256 + 96, 32 + q);
                TSC(tid == 256 && q == 3, 17);
#pragma unroll
                for (int i = 0; i < 4; i++) {
                    const uint4 u = lds4(xa + q * 8192 + i * 2048), w4 = lds4(wa + q * 512 + i * 128);
                    const float a0 = bf_lo(u.x), a1 = bf_hi(u.x), a2 = bf_lo(u.y), a3 = bf_hi(u.y), a4 = bf_lo(u.z), a5 = bf_hi(u.z), a6 = bf_lo(u.w), a7 = bf_hi(u.w);
                    s1 += a0 + a1; c1 += a4 + a5; s1 += a2 + a3; c1 += a6 + a7;
                    s2 = fmaf(a0, a0, s2); c2 = fmaf(a4, a4, c2); sr = fmaf(a0, bf_lo(w4.x), sr); cr = fmaf(a4, bf_lo(w4.z), cr);
                    s2 = fmaf(a1, a1, s2); c2 = fmaf(a5, a5, c2); sr = fmaf(a1, bf_hi(w4.x), sr); cr = fmaf(a5, bf_hi(w4.z), cr);
                    s2 = fmaf(a2, a2, s2); c2 = fmaf(a6, a6, c2); sr = fmaf(a2, bf_lo(w4.y), sr); cr = fmaf(a6, bf_lo(w4.w), cr);
                    s2 = fmaf(a3, a3, s2); c2 = fmaf(a7, a7, c2); sr = fmaf(a3, bf_hi(w4.y), sr); cr = fmaf(a7, bf_hi(w4.w), cr);
                }
                }
                s1 += c1; s2 += c2; sr += cr;
            }
            mbar_wait(bars + 8 * B_SW, 0);
            sw = lds1f(sb + OFF_TAG + 4);
#pragma unroll 1
            for (int pass = 0;; pass++) {
#pragma unroll
                for (int o = 1; o < 8; o <<= 1) {
                    s1 += __shfl_xor_sync(0xffffffffu, s1, o); s2 += __shfl_xor_sync(0xffffffffu, s2, o); sr += __shfl_xor_sync(0xffffffffu, sr, o);
                }
                s1 *= 1.f / 1024.f;
                s2 = fmaf(-s1, s1, s2 * (1.f / 1024.f));
                if (!__any_sync(0xffffffffu, !pass && s1 * s1 > 256.f * s2)) break;
                sh = bf16r(s1); s1 = 0.f; s2 = 0.f; sr = 0.f;
#pragma unroll 1
                for (uint32_t o = 0; o < 2048; o = opaque(o + ((o & 12) == 12 ? 116 : 4))) {
                    const uint32_t u = lds1(xa + (o >> 7) * 2048 + (o & 12)), q = lds1(wa + o);
                    const float a0 = bf_lo(u) - sh, a1 = bf_hi(u) - sh;
                    s1 += a0 + a1; s2 = fmaf(a0, a0, fmaf(a1, a1, s2)); sr = fmaf(a0, bf_lo(q), fmaf(a1, bf_hi(q), sr));
                }
            }
        }
        const int ta = opaque(tid) - 256, lane = ta & 31, g = lane >> 2, t = lane & 3;
        {
            if ((lane & 7) == 0) {
                const int s = b * 16 + p * 4 + (lane >> 3);
                const float mb = bf16r(sh + s1);
                float den;
                asm("sqrt.approx.f32 %0, %1;" : "=f"(den) : "f"(bf16r(bf16r(s2) + 1e-5f)));
                den = bf16r(den);
                uint32_t rb = pack_bf16(fmaf(sh - mb, sw, sr) * rcp(den), 0.f);
                if (rb == 0x8000u) rb = 0;
                uint32_t ord = (rb & 0x8000u) ? (~rb & 0xffffu) : (rb | 0x8000u);
                if ((rb & 0x7fffu) > 0x7f80u) ord = 0;
                st_rlx2(&S->rec[s], (ord << 16) | (tag & 0x8000u) | (0x47ffu - (s & 1023) * 2 - par), pack_bf16(mb, den));
            }
            TSC(TIMING == 12 && lane == 0, 36 + p);
            bar_sync(12, 128);
            if (p == 1) sts1(sb + OFF_ROWMAP + lane * 4, 0xffffffffu);
            if (p == 0) {
                if (lane == 0) {
                    sts1(sb + OFF_TAG, tag);
                }
                __syncwarp();
                bar_arrive(13, 128);
            }
            TSC(ta == 0, 18);
        }
        {
            uint2 r[3];
            nap(N_GA);
            const uint2* src = &S->rec[mt * 256 + ta];
            const int l2 = ta < 8 && j0 ? -8 : 0;
#pragma unroll 1
            for (int it = 0; it < SPIN_LIMIT; it++) {
                r[0] = ld_rlx2(src + l2); r[1] = ld_rlx2(src); r[2] = ld_rlx2(src + 128);
                if (!__any_sync(0xffffffffu, (mism(r[0].x, r[1].x, tag) | (r[2].x ^ tag)) & 0x8000u)) break;
            }
#pragma unroll
            for (int n = 0; n < 3; n++)
                if (n || ta < 8) sts2(sb + OFF_STAT + (n ? n * 1024 - 960 : 0) + ta * 8, (r[n].y << 16) ^ 0x80000000u, __float_as_uint(rcp(bf_hi(r[n].y))));
        }
        __syncwarp();
        if (lane == 0) mbar_arrive(bars + 8 * B_AUX);
        TSC(ta == 0, 30);
        if (f1 && p < 2 && elect_one()) { nap(p * N_F1); ffn_w(p, p); }
        __syncwarp();
        uint2 sel;
#pragma unroll 1
        for (int it = 0; it < SPIN_LIMIT; it++) {
            sel = ld_rlx2(&S->sel[lane & 7]);
            if (!__any_sync(0xffffffffu, (sel.x ^ tag) & 0x8000u)) break;
            __nanosleep(POLL_NS);
        }
        TSC(ta == 0, 26);
        if (b == 0 && ta == 0) st_rlx(&S->epoch, epoch + 1);
        {
            const __nv_bfloat16* xp = x + (~sel.x & 0x7ffu) * 1024 + (ta >> 3) * 8;
            const float mb = bf_lo(sel.y), rinv = rcp(bf_hi(sel.y));
            uint4 v = ldg_nc(xp), v2 = ldg_nc(xp + 128);
            int s = f1 ? 0 : 2;
#pragma unroll 1
            for (int n = f1 ? 0 : 8; n < (p ? 8 : 11); n++) {
                mbar_wait(bars + 8 * (f1 ? B_FEMPTY + s : B_PART), f1 && (n < 3 || (n >= 6 && n < 9)));
                if (p == 0 && s == 2) mbar_wait(bars + 8 * B_CSDONE, 0);
                if (p == 0 && n >= 2 && elect_one()) ffn_w(n, s);
                if (n < 8) {
                    sts4(sb + OFF_FA + s * 2048 + ta * 16, norm_pair(v.x, mb, rinv), norm_pair(v.y, mb, rinv), norm_pair(v.z, mb, rinv), norm_pair(v.w, mb, rinv));
                    fence_async_smem();
                    __syncwarp();
                    if (lane == 0) mbar_arrive(bars + 8 * (B_FFULL + s));
                    TSC(TIMING == 12 && ta == 0, 41 + n);
                    v = v2;
                    if (n) v = ldg_nc(xp + ((n + 1) & 7) * 128);
                }
                if (++s == 3) s = 0;
            }
        }
        if (p) {
            if (p == 1 || f1) st_rlx4(p == 1 ? &S->ypart[kc][lane >> 4][c2 * 64 + (lane & 15) * 4] : (float*)&S->h[fb * 128 + (p & 1) * 64 + (lane & 15) * 4], ~tag, ~tag, ~tag, ~tag);
            st_rlx4(&S->ypart[kc][ta >> 4][c2 * 64 + (ta & 15) * 4], ~tag, ~tag, ~tag, ~tag);
        }
        mbar_wait(bars + 8 * B_PART, 0);
        if (f1 && p >= 2) {
            const uint32_t pa = sb + OFF_FA + (ta - 64) * 16, go = wu < wg ? 1024 : 0;
            const float4 g0 = lds4f(pa + go), g1 = lds4f(pa + 2048 + go), u0 = lds4f(pa + (go ^ 1024)), u1 = lds4f(pa + 2048 + (go ^ 1024));
            float hv[4];
#pragma unroll
            for (int c = 0; c < 4; c++) {
                const float ga = bf16r((&g0.x)[c] + (&g1.x)[c]), up = bf16r((&u0.x)[c] + (&u1.x)[c]);
                hv[c] = bf16r(ga * sigmoidf(ga)) * up;
            }
#pragma unroll
            for (int hh = 0; hh < 2; hh++) {
                const float o = __shfl_xor_sync(0xffffffffu, (g & 1) ? hv[2 * hh] : hv[2 * hh + 1], 4);
                st_rlx(&S->h[(fb * 4 + (p & 1) * 2 + hh) * 32 + (2 * t + (g & 1)) * 4 + (g >> 1)],
                       tagw((g & 1) ? pack_bf16(o, hv[2 * hh + 1]) : pack_bf16(hv[2 * hh], o), g < 2, tag));
            }
            TSC(ta == 64, 22);
        }
        {
            uint4 hq[4];
            const uint32_t* hp4 = S->h + kc * 1792 + ta * 4;
#pragma unroll 1
            for (int it = 0; it < SPIN_LIMIT; it++) {
#pragma unroll
                for (int n = 0; n < 4; n++) hq[n] = ld_rlx4(hp4 + (n < 3 ? n * 512 : p < 2 ? 1536 : 0));
                if (!__any_sync(0xffffffffu, (mism(hq[0].x, hq[1].x, tag) | mism(hq[2].x, hq[3].x, tag)) & 1)) break;
            }
            mbar_wait(bars + 8 * B_G1DONE, 0);
            bar_sync(12, 128);
#pragma unroll
            for (int n = 0; n < 4; n++) sts4(sb + OFF_FA + ta * 16 + (n < 3 ? n * 2048 : p < 2 ? 6144 : 0), hq[n].x, hq[n].y, hq[n].z, hq[n].w);
            fence_async_smem();
            bar_sync(12, 128);
            TSC(ta == 0, 25);
            mbar_wait(bars + 8 * B_F2FULL, 0);
            mbar_wait(bars + 8 * B_ATT, 0);
            float acc[4] = {0.f, 0.f, 0.f, 0.f};
            uint32_t da = sd + dlo(OFF_F2X, 8192), db = sd + dlo(OFF_FA, 128);
#pragma unroll 1
            for (int q = 0; q < 7; q++) {
                wg_fence();
#pragma unroll
                for (int j = 0; j < 4; j++) wgmma_n8<1, 0>(acc, mkdesc(da + j * 128, dhi(1024, 1)), mkdesc(db + j * 16, dhi(128, 0)));
                wg_commit();
                da = sd + dlo(OFF_FW, 8192) + q * 512; db += 64;
            }
            wg_wait<0>();
            if (ta == 0) mbar_arrive(bars + 8 * B_F2DONE);
#pragma unroll
            for (int c = 0; c < 4; c++) st_rlx(&S->ypart[kc][2 * t + (c & 1)][c2 * 64 + p * 16 + (c >> 1) * 8 + g], tagf(acc[c], tag));
            TSC(ta == 0, 23);
            bar_sync(12, 128);
        }
#pragma unroll 1
        for (int j = 2 * p; j < 2 * p + 2; j++) {
            const uint32_t kj = __shfl_sync(0xffffffffu, sel.x, j);
            const int row = 0x7ff - (kj & 0x7ffu), jj = (row >> 1) - j0 - hp * 128;
            float a0 = 0.f, a1 = 0.f, a2 = 0.f, a3 = 0.f, sig = 0.f;
            if ((row & 1) == par && jj >= 0 && jj < 128) {
                sig = bf16r(sigmoidf(__uint_as_float(((int)kj < 0 ? kj ^ 0x80000000u : ~kj) & 0xffff0000u)));
#pragma unroll 1
                for (int hh = 0; hh < 8; hh += 4) {
                    uint4 v[4];
#pragma unroll 1
                    for (int it = 0; it < SPIN_LIMIT; it++) {
#pragma unroll
                        for (int m = 0; m < 4; m++) v[m] = ld_rlx4(&S->ypart[hh + m][j][cb * 128 + lane * 4]);
                        if (!__any_sync(0xffffffffu, (mism(v[0], tag) | mism(v[1], tag) | mism(v[2], tag) | mism(v[3], tag)) & 1)) break;
                    }
#pragma unroll
                    for (int m = 0; m < 4; m++) { a0 += __uint_as_float(v[m].x); a1 += __uint_as_float(v[m].y); a2 += __uint_as_float(v[m].z); a3 += __uint_as_float(v[m].w); }
                }
                asm volatile("st.shared.u8 [%0], %1;" ::"r"(sb + OFF_ROWMAP + jj), "r"(j) : "memory");
            }
            sts2(sb + OFF_FA + (lane >> 1) * 128 + j * 16 + (lane & 1) * 8, pack_bf16(bf16r(a0) * sig, bf16r(a1) * sig), pack_bf16(bf16r(a2) * sig, bf16r(a3) * sig));
        }
        fence_async_smem();
        __syncwarp();
        if (lane == 0) mbar_arrive(bars + 8 * B_UPD);
        TSC(ta == 0, 24);
        TS_END();
    } else {
        if (elect_one()) {
#pragma unroll
            for (int i = 0; i < (B_EMPTY - B_WOFULL) / 8; i++) mbar_init(bars + 8 * (B_WOFULL + 8 * i + warp), 1);
        }
        reg_inc<224>();
        const int w = warp >> 2, wi = warp & 3, tw = (1 - w) * 4 + wi;
        const bool elect = (tid & 127) == 0;
        const uint32_t ln = opaque(lane), g = ln >> 2, t = ln & 3;
        uint32_t tag, ow[8][4];
        auto store_o = [&](int f0, int f1) {
            uint8_t* ob = g_o + (size_t)((mt * 2 + 1 - w) * 2 + 1 - (wi >> 1)) * 131072 + nt * 1024 + (wi & 1) * 512 + ln * 4;
#pragma unroll
            for (int f = f0; f < f1; f++)
#pragma unroll
                for (int i = 3; i >= 0; i--)
                    st_rlx(ob + f * 16384 + i * 128, ow[f][i]);
        };
        {
            float acc[2][96];
            const uint32_t sta = opaque(sb + OFF_STAT + tw * 256 + 64 + g * 8);
            {
                float fa[4] = {0.f, 0.f, 0.f, 0.f};
                uint32_t so = STAGE >> 4, bo = bars, ph = 0;
                const uint32_t dx0 = sd + dlo(w ? 40960 : 0, 16), dw0 = sd + dlo(16384, 8192);
                int p = 0;
                if (w) bar_arrive(1, 256);
                uint32_t fm = fb < 112 ? F1_MASK >> (16 * w) : 0u, fph = 0;
                int fs = w;
#pragma unroll 1
                for (; p < 16; p++) {
                    mbar_wait(bo + 8 * B_FULLA, ph);
                    if (w) mbar_wait(bo + 8 * B_FULLB, ph);
                    TSC(elect && p == 0, 1 + 8 * w);
                    bar_sync(1 + w, 256);
                    TSC(TIMING == 1 && tid == 0, 32 + p);
                    if (p == 15) {
                        wg_fence();
                        wgmma_n192<0, 1>(acc[1], mkdesc(sd + dlo(OFF_MEAN + 1024, 0) + w * 128, dhi(128, 0)), mkdesc(sd + dlo(OFF_CS, 0), dhi(48, 0)));
                        wgmma_n192<0, 1>(acc[0], mkdesc(sd + dlo(OFF_MEAN, 0) + w * 128, dhi(128, 0)), mkdesc(sd + dlo(OFF_CS, 0), dhi(48, 0)));
                        wg_commit();
                    }
                    wg_fence();
#pragma unroll
                    for (int h = 1; h >= 0; h--) {
#pragma unroll
                        for (int k = 0; k < 4; k++) wgmma_n192<0, 1>(acc[h], mkdesc(dx0 + so + h * 512 + k * 2, dhi(1024, 1)), mkdesc(dw0 + so + k * 128, dhi(1024, 1)), k ? 1 : p);
                        wg_commit();
                    }
                    if (fm & 1) {
                        mbar_wait(bars + 8 * (B_FFULL + fs), fph);
                        wg_fence();
#pragma unroll
                        for (int j = 0; j < 8; j++)
                            wgmma_n8<1, 0>(fa, mkdesc(sd + dlo(OFF_FW, 8192) + fs * 1024 + j * 64, dhi(512, 2)), mkdesc(sd + dlo(OFF_FA, 128) + fs * 128 + j * 16, dhi(128, 0)));
                        wg_commit();
                    }
                    bar_arrive(2 - w, 256);
                    if (p == 15) break;
                    wg_wait<0>();
                    if (wi == 0 && elect_one()) { mbar_arrive(bo + 8 * B_EMPTY); if (fm & 1) mbar_arrive(bars + 8 * (B_FEMPTY + fs)); }
                    so = so == 2 * (STAGE >> 4) ? 0 : so + (STAGE >> 4);
                    bo += 8;
                    if (bo == bars + 24) { bo = bars; ph ^= 1; }
                    if (fm & 1) { fs += 2; if (fs >= 3) { fs -= 3; fph ^= 1; } }
                    fm >>= 1;
                    if (p == P_PART) {
                        if (fb < 112) sts4(sb + OFF_FA + tid * 16, __float_as_uint(fa[0]), __float_as_uint(fa[1]), __float_as_uint(fa[2]), __float_as_uint(fa[3]));
                        __syncwarp();
                        if (lane == 0) mbar_arrive(bars + 8 * B_PART);
                    }
                    if (p != 14) continue;
                    mbar_wait(bars + 8 * B_AUX, 0);
                    mbar_wait(bars + 8 * (B_EMPTY + 1), 0);
                    const uint32_t hm = __float_as_uint(0.5f * lds1f(sb + OFF_STAT + 64 + tw * 256 + ln * 8)) >> 16;
                    sts4(sb + OFF_MEAN + w * 2048 + wi * 256 + (ln >> 4) * 1024 + (ln & 15) * 16, hm * 0x10001u, hm, 0, 0);
                    fence_async_smem();
                }
            }
            TSC(TIMING != 14 && elect, 2 + 8 * w);

            tag = lds1(sb + OFF_TAG);
            mbar_wait(bars + 8 * (B_EMPTY + 2), 0);
            wg_wait<1>();
#pragma unroll
            for (int i = 0; i < 96; i++) asm volatile("" : "+f"(acc[1][i]) :: "memory");
            uint32_t pk[4][24];
            const uint32_t hm = tw == 7 ? ~ln & 1 : 0;
            auto np = [&](int i, int j) {
                const float* a = &acc[i >> 1][4 * j + 2 * (i & 1)];
                pk[i][j] = pack_bf16(a[0], a[1]);
                if (j >= 16) pk[i][j] = movm(pk[i][j]);
                if (i == 3 && j >= 8 && !(j & 1)) pk[i][j] = tagw(pk[i][j], hm, tag);
            };
            const uint32_t ha = sb + OFF_HALO + tw * 2048 + ln * 8;
#pragma unroll
            for (int j = 8; j < 24; j += 2) {
                np(3, j); np(3, j + 1);
                sts2(ha + 2048 + (j - 8) * 128, pk[3][j], pk[3][j + 1]);
                asm volatile("{\n.reg .pred p;\nsetp.eq.u32 p, %3, 7;\n@p st.relaxed.gpu.global.v2.u32 [%0], {%1,%2};\n}" ::"l"((char*)&S->halo[b][ln * 2] + (j - 8) * 128),
                             "r"(pk[3][j]), "r"(pk[3][j + 1]), "r"(tw) : "memory");
            }
            bar_arrive(4 + tw, 64);
            TSC(TIMING == 15 && ln == 0 && tw == 7, 39);
            TSC(TIMING == 8 && ln == 0 && wi == 1, 32 + 8 * w);
            const bool u0 = 2 * t > g, u1 = 2 * t + 1 > g;
            const uint32_t mU = (u0 ? 0xffffu : 0u) | (u1 ? 0xffff0000u : 0u);
            uint2 hl[8];
            float rk[4][2], fq[4][2];
            auto factors = [&]() {
                const uint32_t ka = sb + OFF_STAT + tw * 256 + 4 + t * 16, k0 = opaque(ka + (u0 ? 0 : 64)), k1 = opaque(ka + (u1 ? 8 : 72));
#pragma unroll
                for (int i = 0; i < 4; i++) {
                    const float rq = lds1f(sta + i * 64 + 4) * (0.17677669529663687f * 1.4426950408889634f);
                    rk[i][0] = lds1f(k0 + i * 64); rk[i][1] = lds1f(k1 + i * 64);
                    fq[i][0] = rq * rk[i][0]; fq[i][1] = rq * rk[i][1];
                }
            };
#pragma unroll
            for (int jj = 0; jj < 12; jj++) { const int j = (jj >> 2) * 8 + (jj & 3); np(2, j); if (j < 8) np(3, j); }
            factors();
            wg_wait<0>();
#pragma unroll
            for (int i = 0; i < 96; i++) asm volatile("" : "+f"(acc[0][i]) :: "memory");
            if (elect) mbar_arrive(bars + 8 * B_G1DONE);
            const float mask = tw == 0 && j0 == 0 ? -INFINITY : 0.f;
#pragma unroll
            for (int hd = 0; hd < 2; hd++) {
#pragma unroll
                for (int jj = 0; jj < 12; jj++) {
                    const int j = (jj >> 2) * 8 + hd * 4 + (jj & 3);
                    np(0, j); np(1, j);
                    if (j & 4)
                    { np(2, j); if (j < 8) np(3, j); }
                }
                if (hd == 0) mbar_wait(bars + 8 * B_G1DONE, 0);
                float s[2][3][4];
#pragma unroll
                for (int h = 1; h >= 0; h--)
#pragma unroll
                    for (int n = 2; n >= 0; n--) {
                        if (h == 0 && n == 0 && hd == 0) {
                            TSC(TIMING == 8 && ln == 0 && wi == 1 && s[1][0][0] + s[0][1][0] != 123.456f, 33 + 8 * w);
                            bar_sync(3 + tw, 64);
#pragma unroll
                            for (int c = 0; c < 8; c++) hl[c] = lds2(ha + c * 256);
                        }
                        const int kg = 2 * h - 1 + n;
                        s[h][n][0] = s[h][n][1] = kg < 0 ? mask : 0.f; s[h][n][2] = s[h][n][3] = 0.f;
#pragma unroll
                        for (int ks = 0; ks < 2; ks++) {
                            const int q = hd * 4 + 2 * ks;
                            const uint32_t* k = kg < 0 ? &hl[hd * 2 + ks].x : &pk[kg < 0 ? 0 : kg][8 + q];
                            mma16816(s[h][n], pk[2 * h][q], pk[2 * h + 1][q], pk[2 * h][q + 1], pk[2 * h + 1][q + 1], k[0], k[1]);
                        }
                    }
                uint32_t pp[4], pc[4];
#pragma unroll
                for (int i = 0; i < 4; i++) {
                    const float* sp = &s[i >> 1][i & 1][2 * (i & 1)];
                    const float* sc = &s[i >> 1][(i & 1) + 1][2 * (i & 1)];
                    float a0 = (u0 ? sp[0] : sc[0]) * fq[i][0], a1 = (u1 ? sp[1] : sc[1]) * fq[i][1];
                    float m = fmaxf(a0, a1);
                    m = fmaxf(m, __shfl_xor_sync(0xffffffffu, m, 1));
                    m = fmaxf(m, __shfl_xor_sync(0xffffffffu, m, 2));
                    a0 = ex2(a0 - m); a1 = ex2(a1 - m);
                    float sum = a0 + a1;
                    sum += __shfl_xor_sync(0xffffffffu, sum, 1);
                    sum += __shfl_xor_sync(0xffffffffu, sum, 2);
                    const float inv = rcp(sum);
                    const uint32_t pw = pack_bf16(a0 * rk[i][0] * inv, a1 * rk[i][1] * inv);
                    pp[i] = pw & mU; pc[i] = pw & ~mU;
                }
                TSC(TIMING == 8 && ln == 0 && wi == 1 && pp[0] + pp[3] != 0x12345, 34 + 2 * hd + 8 * w);
#pragma unroll
                for (int fh = 0; fh < 2; fh++)
#pragma unroll
                    for (int i = 0; i < 4; i++) {
                        const int v = 16 + hd * 4 + 2 * fh;
                        const uint32_t* vp = i ? &pk[i ? i - 1 : 0][v] : &hl[4 + hd * 2 + fh].x;
                        float o[4] = {0.f, 0.f, 0.f, 0.f};
                        if (i & 1) mma16816(o, vp[0], vp[1], pk[i][v], pk[i][v + 1], pp[i], pc[i]);
                        else { mma1688(o, pk[i][v], pk[i][v + 1], pc[i]); mma1688(o, vp[0], vp[1], pp[i]); }
                        const uint32_t tm = (ln & 7) == (nt & 3) * 2 + (i & 1);
                        ow[hd * 4 + 2 * fh][i] = tagw(pack_bf16(o[0], o[1]), tm, tag); ow[hd * 4 + 2 * fh + 1][i] = tagw(pack_bf16(o[2], o[3]), tm, tag);
                    }
                store_o(hd ? ST_A : 0, hd ? ST_B : ST_A);
                TSC(TIMING == 11 && !hd && ln == 0 && wi == 3, 45 + w);
                if (!hd) mbar_arrive_after(bars + 8 * B_AST, ln, hl[2].x ^ hl[3].x ^ hl[5].x ^ hl[6].x ^ hl[7].x);
                mbar_wait(bars + 8 * B_G1DONE, 0);
                if (hd && ln == 0) mbar_arrive(bars + 8 * B_ATT);
                TSC(TIMING != 14 && elect && hd == 0, 3 + 8 * w);
                TSC(TIMING == 8 && ln == 0 && wi == 1, 35 + 2 * hd + 8 * w);
            }
        }
        TSC(TIMING != 14 && elect, 4 + 8 * w);
        float acc2[64];
        TSC(TIMING != 14 && elect, 5 + 8 * w);
        {
            const uint32_t ring = sb + (w ? OFF_O1 : OFF_O0), da0 = (ring >> 4) + dlo(0, 1024);
            const uint32_t l2 = opaque(ln), chk = ring + wi * 256 + (l2 >> 3) * 1032 + ((l2 >> 2) & 1) * 132 + (l2 & 3) * 32;
            const uint32_t xs = sb + (wi & 1) * 8192 + (tw >> 1) * 2048, mad = xs + (l2 & 15) * 128;
            auto residual = [&](float* base) {
                const uint32_t sta = sb + OFF_STAT + (8 + hp * 128 + tw * 16 + g) * 8;
                const float2 s0 = lds2f(sta), s1 = lds2f(sta + 64);
                const float m0 = s0.x * s0.y, r0 = 1.f + s0.y, m1 = s1.x * s1.y, r1 = 1.f + s1.y;
                mbar_wait(bars + 8 * B_XR, 0);
#pragma unroll
                for (int j = 0; j < 16; j += 2) {
                    uint32_t xr[4];
                    asm volatile("ldmatrix.sync.aligned.m8n8.x4.shared.b16 {%0,%1,%2,%3}, [%4];" : "=r"(xr[0]), "=r"(xr[1]), "=r"(xr[2]), "=r"(xr[3])
                                 : "r"(mad + (j >> 3) * OFF_X1 + ((((j & 7) + (l2 >> 4)) ^ (l2 & 7)) << 4)) : "memory");
#pragma unroll
                    for (int c = 0; c < 4; c++) {
                        base[4 * j + 2 * c] = fmaf(bf_lo(xr[c]), c & 1 ? r1 : r0, c & 1 ? m1 : m0); base[4 * j + 2 * c + 1] = fmaf(bf_hi(xr[c]), c & 1 ? r1 : r0, c & 1 ? m1 : m0);
                        asm volatile("" : "+f"(base[4 * j + 2 * c]), "+f"(base[4 * j + 2 * c + 1]) :: "memory");
                    }
                }
            };
            residual(acc2);
            uint32_t db = sd + dlo(OFF_WO0, 16384);
#pragma unroll 1
            for (int s = 0; s < 8; s++) {
                const uint32_t ro = (s & 1) * 16384;
                mbar_wait(bars + 8 * (B_WOFULL + s), 0);
                TSC(TIMING == 11 && tid == 0 && s == 0, 43);
                mbar_wait(bars + 8 * (B_OFULL + s) + 64 * w, 0);
                TSC(TIMING == 11 && tid == 0 && s == 0, 44);
#pragma unroll 1
                for (int it = 0; __any_sync(0xffffffffu, (mism(lds1(chk + ro), lds1(chk + ro + 4096), tag) | mism(lds1(chk + ro + 8192), lds1(chk + ro + 12288), tag)) & 1) && it < SPIN_LIMIT; it++) {
                    NRETRY();
                    const uint32_t fo = wi * 256 + (l2 >> 4) * 1024 + (l2 & 15) * 16;
                    uint4 v[8];
#pragma unroll
                    for (int c = 0; c < 8; c++) v[c] = ld_rlx4(g_o + (size_t)(((mt * 2 + hp) * 2 + w) * 8 + s) * 16384 + fo + c * 2048);
#pragma unroll
                    for (int c = 0; c < 8; c++) sts4(ring + ro + fo + c * 2048, v[c].x, v[c].y, v[c].z, v[c].w);
                    fence_async_smem();
                    __syncwarp();
                }
                if (s == 0) mbar_wait(bars + 8 * B_ATT, 0);
                if (s <= 8 - LAST) bar_sync(1 + w, 256);
                TSC(elect && s == 0, 6 + 8 * w);
                TSC(TIMING == 2 && elect, 32 + 16 * w + s);
                wg_fence();
#pragma unroll
                for (int k = 0; k < 8; k++)
                    wgmma_n128<1, 1>(acc2, mkdesc(da0 + (ro >> 4) + k * 128, dhi(128, 0)), mkdesc(db + k * 128, dhi(1024, 1)));
                wg_commit();
                db = wo_next(db, sd + dlo(0, 16384), 4);
                if (s < 8 - LAST) {
                    bar_arrive(2 - w, 256);
                    if (s == 0) store_o(ST_B, 8);
                    wg_wait<0>();
                    if (elect) mbar_arrive(bars + 8 * (B_DONE + s) + 64 * w);
                }
            }
            mbar_wait(bars + 8 * B_UPD, 0);
            int sl0, sl1;
            asm volatile("ld.shared.s8 %0, [%1];" : "=r"(sl0) : "r"(sb + OFF_ROWMAP + tw * 16 + g) : "memory");
            asm volatile("ld.shared.s8 %0, [%1];" : "=r"(sl1) : "r"(sb + OFF_ROWMAP + tw * 16 + 8 + g) : "memory");
            const uint32_t e0 = (sl0 >> 1) == (int)t ? 0x3f80u << ((sl0 & 1) * 16) : 0u, e1 = (sl1 >> 1) == (int)t ? 0x3f80u << ((sl1 & 1) * 16) : 0u;
            wg_fence();
            wgmma_rs_n128<1>(acc2, e0, e1, 0u, 0u, mkdesc(sd + dlo(OFF_FA, 0), dhi(128, 0)));
            wg_commit();
            bar_arrive(2 - w, 256);
            wg_wait<0>();
#pragma unroll
            for (int i = 0; i < 64; i++) asm volatile("" : "+f"(acc2[i]) :: "memory");
            TSC(elect, 7 + 8 * w);
#pragma unroll
            for (int j = 0; j < 16; j += 2) {
                const int ch = (j & 7) + (l2 >> 4);
                asm volatile("stmatrix.sync.aligned.m8n8.x4.shared.b16 [%0], {%1,%2,%3,%4};" ::"r"(mad + (j >> 3) * OFF_X1 + ((ch ^ (l2 & 7)) << 4)),
                             "r"(pack_bf16(acc2[4 * j], acc2[4 * j + 1])), "r"(pack_bf16(acc2[4 * j + 2], acc2[4 * j + 3])),
                             "r"(pack_bf16(acc2[4 * j + 4], acc2[4 * j + 5])), "r"(pack_bf16(acc2[4 * j + 6], acc2[4 * j + 7])) : "memory");
                if ((j & 7) == 6) {
                    fence_async_smem();
                    __syncwarp();
                    if (ln == 0) tma_store_2d(&mout, xs + (j >> 3) * OFF_X1, par * 1024 + cb * 128 + (j >> 3) * 64, j0 + hp * 128 + tw * 16);
                }
            }
            if (ln == 0) asm volatile("cp.async.bulk.commit_group;\ncp.async.bulk.wait_group.read 0;" ::: "memory");
            TSC(elect, 8 + 8 * w);
            TS_END();
        }
    }
}

typedef CUresult (*EncodeFn)(CUtensorMap*, CUtensorMapDataType, cuuint32_t, void*, const cuuint64_t*, const cuuint64_t*, const cuuint32_t*,
                             const cuuint32_t*, CUtensorMapInterleave, CUtensorMapSwizzle, CUtensorMapL2promotion, CUtensorMapFloatOOBfill);

CUtensorMap make_map(EncodeFn fn, const void* base, int rank, const cuuint64_t* dims, const cuuint64_t* strides, const cuuint32_t* box,
                     CUtensorMapSwizzle swz = CU_TENSOR_MAP_SWIZZLE_128B, CUtensorMapL2promotion pro = CU_TENSOR_MAP_L2_PROMOTION_L2_256B) {
    CUtensorMap m;
    cuuint32_t es[5] = {1, 1, 1, 1, 1};
    fn(&m, CU_TENSOR_MAP_DATA_TYPE_BFLOAT16, rank, (void*)base, dims, strides, box, es, CU_TENSOR_MAP_INTERLEAVE_NONE,
       swz, pro, CU_TENSOR_MAP_FLOAT_OOB_FILL_NONE);
    return m;
}

}

extern "C" void kernel_launch(void* const* d_in, const int* in_sizes, int n_in, void* d_out, int out_size) {
    (void)in_sizes; (void)n_in; (void)out_size;
    const __nv_bfloat16* x = (const __nv_bfloat16*)d_in[0];
    const __nv_bfloat16* wqkv = (const __nv_bfloat16*)d_in[1];
    const char* wo = (const char*)d_in[2];
    const __nv_bfloat16* wr = (const __nv_bfloat16*)d_in[4];
    const char* wg = (const char*)d_in[5];
    const char* wu = (const char*)d_in[6];
    const char* wd = (const char*)d_in[7];
    static EncodeFn fn = nullptr;
    static int by_sm = 0;
    static Scratch* scr = nullptr;
    if (!fn) {
        void* p = nullptr; cudaDriverEntryPointQueryResult q;
        cudaGetDriverEntryPoint("cuTensorMapEncodeTiled", &p, cudaEnableDefault, &q);
        fn = (EncodeFn)p;
        cudaFuncSetAttribute(fused_kernel, cudaFuncAttributeMaxDynamicSharedMemorySize, SMEM_LAUNCH);
        cudaGetSymbolAddress((void**)&scr, g_scr);
        int dev = 0, sms = 0;
        cudaGetDevice(&dev);
        cudaDeviceGetAttribute(&sms, cudaDevAttrMultiProcessorCount, dev);
        by_sm = sms == 132;
    }
    Roles roles;
    for (int i = 0; i < 132; i++) {
        const int T = i >> 1, T8 = T < 32 ? T : T + 1 + (T - 32) / 7, fb = (T < 60 ? (~T8 & 7) * 8 + (T8 >> 3) : T < 62 ? T + 4 : T - 2) * 2 + (i & 1);
        roles.v[i] = fb | ((fb & ~31) | (fb & 1) << 4 | (fb & 31) >> 1) << 8;
    }
    const cuuint64_t xd[4] = {2048, 16, 32, 2}, xs[3] = {4096, 131072, 65536};
    const cuuint32_t xb[4] = {64, 16, 4, 2};
    const cuuint64_t wdm[3] = {1024, 1024, 3}, wst[2] = {6144, 2048};
    const cuuint32_t wb[3] = {64, 64, 3};
    const cuuint64_t od[4] = {64, 64, 16, 16}, ost[3] = {2048, 131072, 128};
    const cuuint32_t ob[4] = {64, 8, 16, 2};
    const cuuint64_t yd[2] = {2048, 1024}, yst[1] = {4096};
    const cuuint32_t yb[2] = {64, 16};
    const cuuint64_t sd[3] = {64, 1024, 32}, sst[2] = {4096, 128};
    const cuuint32_t sbx[3] = {64, 16, 4};
    CUtensorMap mxs = make_map(fn, x, 3, sd, sst, sbx);
    const cuuint64_t cd[3] = {3072, 64, 16}, cst[2] = {6144, 393216};
    const cuuint32_t cbx[3] = {64, 8, 2};
    CUtensorMap mcs = make_map(fn, wqkv, 3, cd, cst, cbx, CU_TENSOR_MAP_SWIZZLE_NONE);
    CUtensorMap mx = make_map(fn, x, 4, xd, xs, xb), mw = make_map(fn, wqkv, 3, wdm, wst, wb);
    CUtensorMap mwo = make_map(fn, wo, 4, od, ost, ob), mout = make_map(fn, d_out, 2, yd, yst, yb);
    const cuuint64_t gd[3] = {3584, 1024, 2}, gst[2] = {7168, (cuuint64_t)(wu < wg ? wg - wu : wu - wg)};
    const cuuint32_t gb[3] = {32, 128, 2};
    const cuuint64_t dd[2] = {1024, 3584}, dst[1] = {2048};
    const cuuint32_t db[2] = {64, 64};
    CUtensorMap mgu = make_map(fn, wu < wg ? wu : wg, 3, gd, gst, gb, CU_TENSOR_MAP_SWIZZLE_64B, CU_TENSOR_MAP_L2_PROMOTION_L2_128B);
    CUtensorMap mwd = make_map(fn, wd, 2, dd, dst, db, CU_TENSOR_MAP_SWIZZLE_128B, CU_TENSOR_MAP_L2_PROMOTION_L2_128B);
    fused_kernel<<<132, 512, SMEM_LAUNCH, cudaStreamPerThread>>>(by_sm, x, wqkv, wr, scr, wg, wu, wd, wo, roles, mw, mx, mwo, mxs, mcs, mout, mgu, mwd);
}
```

```cpp
#include <cuda_runtime.h>
#include <cuda.h>
#include <cuda_bf16.h>
#include <stdint.h>

namespace {

constexpr int STAGE = 57344;
constexpr int OFF_FW = 3 * STAGE;
constexpr int OFF_FA = OFF_FW + 49152;
constexpr int OFF_CS = OFF_FA + 6144;
constexpr int OFF_STAT = OFF_CS + 1232;
constexpr int OFF_ROWMAP = OFF_STAT + 2112;
constexpr int OFF_TAG = OFF_ROWMAP + 128;
constexpr int OFF_BAR = OFF_TAG + 8;
constexpr int OFF_F2X = 16384, OFF_HALO = 24576, OFF_O1 = 24576, OFF_O0 = 90112, NWO = 3, OFF_MEAN = 2 * STAGE, OFF_X1 = 2 * STAGE + 8192;
constexpr int OFF_WO0 = OFF_X1 + 16384, OFF_WO1 = STAGE, OFF_WO2 = OFF_FW;
static_assert(OFF_WO0 + 32768 == OFF_FW && OFF_WO1 + 32768 == OFF_O0 && OFF_O0 + 32768 == OFF_X1 && OFF_O1 + 32768 == STAGE, "alias");
__host__ __device__ constexpr uint32_t wo_next(uint32_t o, uint32_t base, int sh) { return o == base + (OFF_WO0 >> sh) ? base + (OFF_WO1 >> sh) : o == base + (OFF_WO1 >> sh) ? base + (OFF_WO2 >> sh) : base + (OFF_WO0 >> sh); }
constexpr int B_FULLA = 0, B_FULLB = 3, B_ROW = 6, B_FFULL = 11, B_F2DONE = 14, B_SW = 15, B_CS = 16, B_FDONE = 22, B_WOFULL = B_FDONE + 8, B_OFULL = B_WOFULL + 8,
              B_DONE = B_OFULL + 16;
constexpr int B_EMPTY = B_DONE + 16, B_XR = B_EMPTY + 3, B_G1DONE = B_XR + 1;
constexpr int B_UPD = B_G1DONE + 1, B_F2FULL = B_UPD + 1;
constexpr int B_AUX = B_F2FULL + 1, B_PART = B_AUX + 1, B_ATT = B_PART + 1, B_CSDONE = B_ATT + 1, B_AST = B_CSDONE + 1, NBAR = B_AST + 1;
constexpr int SMEM_BYTES = OFF_BAR + NBAR * 8;
static_assert(SMEM_BYTES <= 232448 && OFF_BAR % 8 == 0, "smem");
#define P_PART 13
#define F1_MASK (0x6a005a00u >> (14 - P_PART))
#define PF_CNT 0x2aaaaacu
#define N_S1 1
#define N_S2 3
#define ST_A 2
#define ST_B 5
#define T_H 0
#define T_O1 250
#define T_O 1800
#define T_S1 128
#define T_S2 950
#define N_GA 4
#define N_X 1
#define D_X 2
#define D_R 3
#define N_ROW 5
#define N_W 5
#define K_W1 5
#define K_W2 10
#define N_CS 3
#define N_F1 4
#define LAST 2
#define N_HA 4
#define N_A2 4
#define POLL_NS 100
constexpr int SPIN_LIMIT = 1 << 18;

struct Scratch {
    uint8_t o[2048 * 1024 * 2];
    uint2 rec[2048];
    float cs[8][3072];
    uint32_t halo[128][512];
    uint32_t h[14336];
    float ypart[8][8][1024];
    uint2 sel[16];
    uint32_t hint[128][8];
    uint32_t epoch;
};
__device__ __align__(1024) Scratch g_scr;

#define TS(i) do {} while (0)
#define TS_END() do {} while (0)
constexpr int SMEM_LAUNCH = SMEM_BYTES;
#define TSC(c, i) do {} while (0)
#define NRETRY() do {} while (0)
__device__ __forceinline__ uint32_t smem_u32(const void* p) { return (uint32_t)__cvta_generic_to_shared(p); }
__device__ __forceinline__ void mbar_init(uint32_t bar, uint32_t cnt) { asm volatile("mbarrier.init.shared::cta.b64 [%0], %1;" ::"r"(bar), "r"(cnt) : "memory"); }
__device__ __forceinline__ void mbar_expect_tx(uint32_t bar, uint32_t bytes) { asm volatile("mbarrier.arrive.expect_tx.shared::cta.b64 _, [%0], %1;" ::"r"(bar), "r"(bytes) : "memory"); }
__device__ __forceinline__ void mbar_arrive(uint32_t bar) { asm volatile("mbarrier.arrive.shared::cta.b64 _, [%0];" ::"r"(bar) : "memory"); }
__device__ __forceinline__ void mbar_arrive_after(uint32_t bar, uint32_t lane, uint32_t dep) {
    asm volatile("{\n.reg .pred p;\n.reg .b32 t;\nsetp.eq.u32 p, %1, 0;\nmad.lo.u32 t, %1, %2, %0;\n@p mbarrier.arrive.shared::cta.b64 _, [t];\n}" ::"r"(bar), "r"(lane), "r"(dep) : "memory");
}
__device__ __forceinline__ void mbar_wait(uint32_t bar, uint32_t parity) {
    asm volatile("{\n.reg .pred P1;\nLAB_WAIT:\nmbarrier.try_wait.parity.shared::cta.b64 P1, [%0], %1;\n@!P1 bra LAB_WAIT;\n}" ::"r"(bar), "r"(parity) : "memory");
}
__device__ __forceinline__ void tma_3d(uint32_t dst, const CUtensorMap* m, uint32_t bar, int c0, int c1, int c2) {
    asm volatile("cp.async.bulk.tensor.3d.shared::cluster.global.mbarrier::complete_tx::bytes [%0], [%1, {%3, %4, %5}], [%2];" ::"r"(dst), "l"(m), "r"(bar), "r"(c0), "r"(c1), "r"(c2) : "memory");
}
__device__ __forceinline__ void tma_2d_once(uint32_t dst, const CUtensorMap* m, uint32_t bar, int c0, int c1) {
    asm volatile("cp.async.bulk.tensor.2d.shared::cluster.global.mbarrier::complete_tx::bytes.L2::cache_hint [%0], [%1, {%3, %4}], [%2], %5;" ::"r"(dst), "l"(m), "r"(bar), "r"(c0), "r"(c1), "l"(0x12F0000000000000ull) : "memory");
}
__device__ __forceinline__ void tma_3d_once(uint32_t dst, const CUtensorMap* m, uint32_t bar, int c0, int c1, int c2) {
    asm volatile("cp.async.bulk.tensor.3d.shared::cluster.global.mbarrier::complete_tx::bytes.L2::cache_hint [%0], [%1, {%3, %4, %5}], [%2], %6;" ::"r"(dst), "l"(m), "r"(bar), "r"(c0), "r"(c1), "r"(c2), "l"(0x12F0000000000000ull) : "memory");
}
__device__ __forceinline__ void tma_4d(uint32_t dst, const CUtensorMap* m, uint32_t bar, int c0, int c1, int c2, int c3) {
    asm volatile("cp.async.bulk.tensor.4d.shared::cluster.global.mbarrier::complete_tx::bytes [%0], [%1, {%3, %4, %5, %6}], [%2];" ::"r"(dst), "l"(m), "r"(bar), "r"(c0), "r"(c1), "r"(c2), "r"(c3) : "memory");
}
__device__ __forceinline__ void tma_store_2d(const CUtensorMap* m, uint32_t src, int c0, int c1) {
    asm volatile("cp.async.bulk.tensor.2d.global.shared::cta.bulk_group [%0, {%2, %3}], [%1];" ::"l"(m), "r"(src), "r"(c0), "r"(c1) : "memory");
}
__device__ __forceinline__ void bulk_g2s(uint32_t dst, const void* src, uint32_t bytes, uint32_t bar) {
    asm volatile("cp.async.bulk.shared::cluster.global.mbarrier::complete_tx::bytes [%0], [%1], %2, [%3];" ::"r"(dst), "l"(src), "r"(bytes), "r"(bar) : "memory");
}
__device__ __forceinline__ void bulk_prefetch(const void* p, uint32_t bytes) { asm volatile("cp.async.bulk.prefetch.L2.global [%0], %1;" ::"l"(p), "r"(bytes) : "memory"); }
__device__ __forceinline__ void fence_async_smem() { asm volatile("fence.proxy.async.shared::cta;" ::: "memory"); }
__device__ __forceinline__ void wg_fence() { asm volatile("wgmma.fence.sync.aligned;" ::: "memory"); }
__device__ __forceinline__ void wg_commit() { asm volatile("wgmma.commit_group.sync.aligned;" ::: "memory"); }
template <int N> __device__ __forceinline__ void wg_wait() { asm volatile("wgmma.wait_group.sync.aligned %0;" ::"n"(N) : "memory"); }
__device__ __forceinline__ uint64_t mkdesc(uint32_t lo, uint32_t hi) { return ((uint64_t)hi << 32) | lo; }
__host__ __device__ constexpr uint32_t dhi(uint32_t sbo, uint32_t mode) { return (sbo >> 4) | (mode << 30); }
__host__ __device__ constexpr uint32_t dlo(uint32_t off, uint32_t lbo) { return (off >> 4) + ((lbo >> 4) << 16); }
__device__ __forceinline__ bool elect_one() {
    uint32_t e;
    asm volatile("{\n.reg .pred p;\nelect.sync _|p, 0xffffffff;\nselp.u32 %0, 1, 0, p;\n}" : "=r"(e));
    return e;
}
template <int R> __device__ __forceinline__ void reg_inc() { asm volatile("setmaxnreg.inc.sync.aligned.u32 %0;" ::"n"(R)); }
template <int R> __device__ __forceinline__ void reg_dec() { asm volatile("setmaxnreg.dec.sync.aligned.u32 %0;" ::"n"(R)); }
__device__ __forceinline__ void bar_sync(int id, int n) { asm volatile("bar.sync %0, %1;" ::"r"(id), "r"(n) : "memory"); }
__device__ __forceinline__ void bar_arrive(int id, int n) { asm volatile("bar.arrive %0, %1;" ::"r"(id), "r"(n) : "memory"); }
__device__ __forceinline__ uint32_t pack_bf16(float lo, float hi) { uint32_t r; asm("cvt.rn.bf16x2.f32 %0, %1, %2;" : "=r"(r) : "f"(hi), "f"(lo)); return r; }
__device__ __forceinline__ float bf_lo(uint32_t u) { return __uint_as_float(u << 16); }
__device__ __forceinline__ float bf_hi(uint32_t u) { return __uint_as_float(u & 0xffff0000u); }
__device__ __forceinline__ float bf16r(float v) { return bf_lo(pack_bf16(v, 0.f)); }
__device__ __forceinline__ uint32_t tagw(uint32_t w, uint32_t m, uint32_t tag) { uint32_t r; asm("lop3.b32 %0, %1, %2, %3, 0xb8;" : "=r"(r) : "r"(w), "r"(m), "r"(tag)); return r; }
__device__ __forceinline__ uint32_t tagf(float f, uint32_t tag) { return tagw(__float_as_uint(f), 1u, tag); }
__device__ __forceinline__ uint32_t movm(uint32_t a) { uint32_t d; asm volatile("movmatrix.sync.aligned.m8n8.trans.b16 %0, %1;" : "=r"(d) : "r"(a)); return d; }
__device__ __forceinline__ void mma16816(float (&c)[4], uint32_t a0, uint32_t a1, uint32_t a2, uint32_t a3, uint32_t b0, uint32_t b1) {
    asm volatile("mma.sync.aligned.m16n8k16.row.col.f32.bf16.bf16.f32 {%0,%1,%2,%3}, {%4,%5,%6,%7}, {%8,%9}, {%0,%1,%2,%3};"
                 : "+f"(c[0]), "+f"(c[1]), "+f"(c[2]), "+f"(c[3]) : "r"(a0), "r"(a1), "r"(a2), "r"(a3), "r"(b0), "r"(b1));
}
__device__ __forceinline__ void mma1688(float (&c)[4], uint32_t a0, uint32_t a1, uint32_t b0) {
    asm volatile("mma.sync.aligned.m16n8k8.row.col.f32.bf16.bf16.f32 {%0,%1,%2,%3}, {%4,%5}, {%6}, {%0,%1,%2,%3};"
                 : "+f"(c[0]), "+f"(c[1]), "+f"(c[2]), "+f"(c[3]) : "r"(a0), "r"(a1), "r"(b0));
}
__device__ __forceinline__ uint32_t ld_rlx(const void* p) { uint32_t v; asm volatile("ld.relaxed.gpu.global.u32 %0, [%1];" : "=r"(v) : "l"(p) : "memory"); return v; }
__device__ __forceinline__ uint2 ld_rlx2(const void* p) { uint2 v; asm volatile("ld.relaxed.gpu.global.v2.u32 {%0,%1}, [%2];" : "=r"(v.x), "=r"(v.y) : "l"(p) : "memory"); return v; }
__device__ __forceinline__ uint4 ld_rlx4(const void* p) { uint4 v; asm volatile("ld.relaxed.gpu.global.v4.u32 {%0,%1,%2,%3}, [%4];" : "=r"(v.x), "=r"(v.y), "=r"(v.z), "=r"(v.w) : "l"(p) : "memory"); return v; }
__device__ __forceinline__ void st_rlx(void* p, uint32_t v) { asm volatile("st.relaxed.gpu.global.u32 [%0], %1;" ::"l"(p), "r"(v) : "memory"); }
__device__ __forceinline__ void st_rlx2(void* p, uint32_t a, uint32_t b) { asm volatile("st.relaxed.gpu.global.v2.u32 [%0], {%1,%2};" ::"l"(p), "r"(a), "r"(b) : "memory"); }
__device__ __forceinline__ void st_rlx4(void* p, uint32_t a, uint32_t b, uint32_t c, uint32_t d) { asm volatile("st.relaxed.gpu.global.v4.u32 [%0], {%1,%2,%3,%4};" ::"l"(p), "r"(a), "r"(b), "r"(c), "r"(d) : "memory"); }
__device__ __forceinline__ uint4 ldg_nc(const void* p) { uint4 v; asm volatile("ld.global.nc.v4.u32 {%0,%1,%2,%3}, [%4];" : "=r"(v.x), "=r"(v.y), "=r"(v.z), "=r"(v.w) : "l"(p)); return v; }
__device__ __forceinline__ uint32_t mism(uint32_t a, uint32_t b, uint32_t tag) { uint32_t r; asm("lop3.b32 %0, %1, %2, %3, 0x7e;" : "=r"(r) : "r"(a), "r"(b), "r"(tag)); return r; }
__device__ __forceinline__ uint32_t mism(const uint4& v, uint32_t tag) { return mism(v.x, v.y, tag) | mism(v.z, v.w, tag); }
__device__ __forceinline__ void prefetch_l2(const void* p) { asm volatile("prefetch.global.L2 [%0];" ::"l"(p)); }
__device__ __forceinline__ void nap(int n) {
#pragma unroll 1
    for (int i = 0; i < n; i++) __nanosleep(100);
}
__device__ __forceinline__ uint32_t now() { uint32_t t; asm volatile("mov.u32 %0, %%globaltimer_lo;" : "=r"(t)); return t; }
__device__ __forceinline__ void until(uint32_t t) {
    while (t - now() - 1 < 16384u) __nanosleep(50);
}
__device__ __forceinline__ uint32_t opaque(uint32_t v) { return __shfl_xor_sync(0xffffffffu, v, 0); }
__device__ __forceinline__ void sts4(uint32_t a, uint32_t x, uint32_t y, uint32_t z, uint32_t w) { asm volatile("st.shared.v4.u32 [%0], {%1,%2,%3,%4};" ::"r"(a), "r"(x), "r"(y), "r"(z), "r"(w) : "memory"); }
__device__ __forceinline__ void sts2(uint32_t a, uint32_t x, uint32_t y) { asm volatile("st.shared.v2.u32 [%0], {%1,%2};" ::"r"(a), "r"(x), "r"(y) : "memory"); }
__device__ __forceinline__ uint4 lds4(uint32_t a) { uint4 v; asm volatile("ld.shared.v4.u32 {%0,%1,%2,%3}, [%4];" : "=r"(v.x), "=r"(v.y), "=r"(v.z), "=r"(v.w) : "r"(a) : "memory"); return v; }
__device__ __forceinline__ float4 lds4f(uint32_t a) { float4 v; asm volatile("ld.shared.v4.f32 {%0,%1,%2,%3}, [%4];" : "=f"(v.x), "=f"(v.y), "=f"(v.z), "=f"(v.w) : "r"(a) : "memory"); return v; }
__device__ __forceinline__ uint2 lds2(uint32_t a) { uint2 v; asm volatile("ld.shared.v2.u32 {%0,%1}, [%2];" : "=r"(v.x), "=r"(v.y) : "r"(a) : "memory"); return v; }
__device__ __forceinline__ float2 lds2f(uint32_t a) { float2 v; asm volatile("ld.shared.v2.f32 {%0,%1}, [%2];" : "=f"(v.x), "=f"(v.y) : "r"(a) : "memory"); return v; }
__device__ __forceinline__ uint32_t lds1(uint32_t a) { uint32_t v; asm volatile("ld.shared.u32 %0, [%1];" : "=r"(v) : "r"(a) : "memory"); return v; }
__device__ __forceinline__ float lds1f(uint32_t a) { return __uint_as_float(lds1(a)); }
__device__ __forceinline__ void sts1(uint32_t a, uint32_t v) { asm volatile("st.shared.u32 [%0], %1;" ::"r"(a), "r"(v) : "memory"); }
__device__ __forceinline__ uint32_t redux_max(uint32_t v) { uint32_t r; asm volatile("redux.sync.max.u32 %0, %1, 0xffffffff;" : "=r"(r) : "r"(v)); return r; }
__device__ __forceinline__ float ex2(float x) { float r; asm("ex2.approx.ftz.f32 %0, %1;" : "=f"(r) : "f"(x)); return r; }
__device__ __forceinline__ float rcp(float x) { float r; asm("rcp.approx.ftz.f32 %0, %1;" : "=f"(r) : "f"(x)); return r; }
__device__ __forceinline__ float sigmoidf(float v) { return rcp(1.f + ex2(v * -1.4426950408889634f)); }

template <int TA, int TB>
__device__ __forceinline__ void wgmma_n192(float (&d)[96], uint64_t da, uint64_t db, int acc = 1) {
    asm volatile("{\n.reg .pred p;\nsetp.ne.b32 p, %100, 0;\n"
        "wgmma.mma_async.sync.aligned.m64n192k16.f32.bf16.bf16 "
        "{%0, %1, %2, %3, %4, %5, %6, %7, %8, %9, %10, %11, %12, %13, %14, %15, "
        "%16, %17, %18, %19, %20, %21, %22, %23, %24, %25, %26, %27, %28, %29, %30, %31, "
        "%32, %33, %34, %35, %36, %37, %38, %39, %40, %41, %42, %43, %44, %45, %46, %47, "
        "%48, %49, %50, %51, %52, %53, %54, %55, %56, %57, %58, %59, %60, %61, %62, %63, "
        "%64, %65, %66, %67, %68, %69, %70, %71, %72, %73, %74, %75, %76, %77, %78, %79, "
        "%80, %81, %82, %83, %84, %85, %86, %87, %88, %89, %90, %91, %92, %93, %94, %95}, "
        "%96, %97, p, 1, 1, %98, %99;\n}\n"
        : "+f"(d[0]), "+f"(d[1]), "+f"(d[2]), "+f"(d[3]), "+f"(d[4]), "+f"(d[5]), "+f"(d[6]), "+f"(d[7]),
          "+f"(d[8]), "+f"(d[9]), "+f"(d[10]), "+f"(d[11]), "+f"(d[12]), "+f"(d[13]), "+f"(d[14]), "+f"(d[15]),
          "+f"(d[16]), "+f"(d[17]), "+f"(d[18]), "+f"(d[19]), "+f"(d[20]), "+f"(d[21]), "+f"(d[22]), "+f"(d[23]),
          "+f"(d[24]), "+f"(d[25]), "+f"(d[26]), "+f"(d[27]), "+f"(d[28]), "+f"(d[29]), "+f"(d[30]), "+f"(d[31]),
          "+f"(d[32]), "+f"(d[33]), "+f"(d[34]), "+f"(d[35]), "+f"(d[36]), "+f"(d[37]), "+f"(d[38]), "+f"(d[39]),
          "+f"(d[40]), "+f"(d[41]), "+f"(d[42]), "+f"(d[43]), "+f"(d[44]), "+f"(d[45]), "+f"(d[46]), "+f"(d[47]),
          "+f"(d[48]), "+f"(d[49]), "+f"(d[50]), "+f"(d[51]), "+f"(d[52]), "+f"(d[53]), "+f"(d[54]), "+f"(d[55]),
          "+f"(d[56]), "+f"(d[57]), "+f"(d[58]), "+f"(d[59]), "+f"(d[60]), "+f"(d[61]), "+f"(d[62]), "+f"(d[63]),
          "+f"(d[64]), "+f"(d[65]), "+f"(d[66]), "+f"(d[67]), "+f"(d[68]), "+f"(d[69]), "+f"(d[70]), "+f"(d[71]),
          "+f"(d[72]), "+f"(d[73]), "+f"(d[74]), "+f"(d[75]), "+f"(d[76]), "+f"(d[77]), "+f"(d[78]), "+f"(d[79]),
          "+f"(d[80]), "+f"(d[81]), "+f"(d[82]), "+f"(d[83]), "+f"(d[84]), "+f"(d[85]), "+f"(d[86]), "+f"(d[87]),
          "+f"(d[88]), "+f"(d[89]), "+f"(d[90]), "+f"(d[91]), "+f"(d[92]), "+f"(d[93]), "+f"(d[94]), "+f"(d[95])
        : "l"(da), "l"(db), "n"(TA), "n"(TB), "r"(acc));
}
template <int TA, int TB>
__device__ __forceinline__ void wgmma_n128(float (&d)[64], uint64_t da, uint64_t db, int acc = 1) {
    asm volatile("{\n.reg .pred p;\nsetp.ne.b32 p, %68, 0;\n"
        "wgmma.mma_async.sync.aligned.m64n128k16.f32.bf16.bf16 "
        "{%0, %1, %2, %3, %4, %5, %6, %7, %8, %9, %10, %11, %12, %13, %14, %15, "
        "%16, %17, %18, %19, %20, %21, %22, %23, %24, %25, %26, %27, %28, %29, %30, %31, "
        "%32, %33, %34, %35, %36, %37, %38, %39, %40, %41, %42, %43, %44, %45, %46, %47, "
        "%48, %49, %50, %51, %52, %53, %54, %55, %56, %57, %58, %59, %60, %61, %62, %63}, "
        "%64, %65, p, 1, 1, %66, %67;\n}\n"
        : "+f"(d[0]), "+f"(d[1]), "+f"(d[2]), "+f"(d[3]), "+f"(d[4]), "+f"(d[5]), "+f"(d[6]), "+f"(d[7]),
          "+f"(d[8]), "+f"(d[9]), "+f"(d[10]), "+f"(d[11]), "+f"(d[12]), "+f"(d[13]), "+f"(d[14]), "+f"(d[15]),
          "+f"(d[16]), "+f"(d[17]), "+f"(d[18]), "+f"(d[19]), "+f"(d[20]), "+f"(d[21]), "+f"(d[22]), "+f"(d[23]),
          "+f"(d[24]), "+f"(d[25]), "+f"(d[26]), "+f"(d[27]), "+f"(d[28]), "+f"(d[29]), "+f"(d[30]), "+f"(d[31]),
          "+f"(d[32]), "+f"(d[33]), "+f"(d[34]), "+f"(d[35]), "+f"(d[36]), "+f"(d[37]), "+f"(d[38]), "+f"(d[39]),
          "+f"(d[40]), "+f"(d[41]), "+f"(d[42]), "+f"(d[43]), "+f"(d[44]), "+f"(d[45]), "+f"(d[46]), "+f"(d[47]),
          "+f"(d[48]), "+f"(d[49]), "+f"(d[50]), "+f"(d[51]), "+f"(d[52]), "+f"(d[53]), "+f"(d[54]), "+f"(d[55]),
          "+f"(d[56]), "+f"(d[57]), "+f"(d[58]), "+f"(d[59]), "+f"(d[60]), "+f"(d[61]), "+f"(d[62]), "+f"(d[63])
        : "l"(da), "l"(db), "n"(TA), "n"(TB), "r"(acc));
}
template <int TB>
__device__ __forceinline__ void wgmma_rs_n128(float (&d)[64], uint32_t a0, uint32_t a1, uint32_t a2, uint32_t a3, uint64_t db) {
    asm volatile("{\n.reg .pred p;\nsetp.ne.b32 p, 1, 0;\n"
        "wgmma.mma_async.sync.aligned.m64n128k16.f32.bf16.bf16 "
        "{%0, %1, %2, %3, %4, %5, %6, %7, %8, %9, %10, %11, %12, %13, %14, %15, "
        "%16, %17, %18, %19, %20, %21, %22, %23, %24, %25, %26, %27, %28, %29, %30, %31, "
        "%32, %33, %34, %35, %36, %37, %38, %39, %40, %41, %42, %43, %44, %45, %46, %47, "
        "%48, %49, %50, %51, %52, %53, %54, %55, %56, %57, %58, %59, %60, %61, %62, %63}, "
        "{%64, %65, %66, %67}, %68, p, 1, 1, %69;\n}\n"
        : "+f"(d[0]), "+f"(d[1]), "+f"(d[2]), "+f"(d[3]), "+f"(d[4]), "+f"(d[5]), "+f"(d[6]), "+f"(d[7]),
          "+f"(d[8]), "+f"(d[9]), "+f"(d[10]), "+f"(d[11]), "+f"(d[12]), "+f"(d[13]), "+f"(d[14]), "+f"(d[15]),
          "+f"(d[16]), "+f"(d[17]), "+f"(d[18]), "+f"(d[19]), "+f"(d[20]), "+f"(d[21]), "+f"(d[22]), "+f"(d[23]),
          "+f"(d[24]), "+f"(d[25]), "+f"(d[26]), "+f"(d[27]), "+f"(d[28]), "+f"(d[29]), "+f"(d[30]), "+f"(d[31]),
          "+f"(d[32]), "+f"(d[33]), "+f"(d[34]), "+f"(d[35]), "+f"(d[36]), "+f"(d[37]), "+f"(d[38]), "+f"(d[39]),
          "+f"(d[40]), "+f"(d[41]), "+f"(d[42]), "+f"(d[43]), "+f"(d[44]), "+f"(d[45]), "+f"(d[46]), "+f"(d[47]),
          "+f"(d[48]), "+f"(d[49]), "+f"(d[50]), "+f"(d[51]), "+f"(d[52]), "+f"(d[53]), "+f"(d[54]), "+f"(d[55]),
          "+f"(d[56]), "+f"(d[57]), "+f"(d[58]), "+f"(d[59]), "+f"(d[60]), "+f"(d[61]), "+f"(d[62]), "+f"(d[63])
        : "r"(a0), "r"(a1), "r"(a2), "r"(a3), "l"(db), "n"(TB));
}
template <int TA, int TB>
__device__ __forceinline__ void wgmma_n8(float (&d)[4], uint64_t da, uint64_t db, int acc = 1) {
    asm volatile("{\n.reg .pred p;\nsetp.ne.b32 p, %8, 0;\n"
        "wgmma.mma_async.sync.aligned.m64n8k16.f32.bf16.bf16 "
        "{%0, %1, %2, %3}, "
        "%4, %5, p, 1, 1, %6, %7;\n}\n"
        : "+f"(d[0]), "+f"(d[1]), "+f"(d[2]), "+f"(d[3])
        : "l"(da), "l"(db), "n"(TA), "n"(TB), "r"(acc));
}

__device__ __forceinline__ uint32_t sub2(uint32_t a, uint32_t b) { uint32_t r; asm("sub.rn.bf16x2 %0, %1, %2;" : "=r"(r) : "r"(a), "r"(b)); return r; }

struct Roles { uint16_t v[132]; };

__global__ void __launch_bounds__(512, 1)
fused_kernel(int by_sm, const __nv_bfloat16* __restrict__ x, const __nv_bfloat16* __restrict__ wqkv, const __nv_bfloat16* __restrict__ wr,
             Scratch* const S, const char* __restrict__ wg, const char* __restrict__ wu, const char* __restrict__ wd, const char* __restrict__ wo,
             const __grid_constant__ Roles roles,
             const __grid_constant__ CUtensorMap mw, const __grid_constant__ CUtensorMap mx, const __grid_constant__ CUtensorMap mwo,
             const __grid_constant__ CUtensorMap mxs, const __grid_constant__ CUtensorMap mcs, const __grid_constant__ CUtensorMap mout, const __grid_constant__ CUtensorMap mgu, const __grid_constant__ CUtensorMap mwd) {
    extern __shared__ __align__(1024) uint8_t smem[];
    constexpr uint32_t sb = 1024, bars = sb + OFF_BAR, sd = sb >> 4;
    const int tid = threadIdx.x, lane = tid & 31;
    asm volatile("{\n.reg .pred p, q;\nsetp.lt.u32 p, %2, 16;\nsetp.lt.u32 q, %2, 24;\n@p prefetch.global.L2 [%0];\n@p prefetch.global.L2 [%0 + 128];\n@q prefetch.global.L2 [%1];\n}" ::
                 "l"((const char*)x + (blockIdx.x * 16 + tid - 32) % 2048 * 2048), "l"((const char*)wqkv + (blockIdx.x * 24 + tid - 32) * 128), "r"(tid - 32));
    const int warp = __shfl_sync(0xffffffffu, tid >> 5, 0);
    uint32_t smid;
    asm volatile("mov.u32 %0, %%smid;" : "=r"(smid));
    const int role = roles.v[by_sm ? smid : blockIdx.x], fb = role & 255, b = role >> 8, kc = fb >> 4, c2 = fb & 15;
    const int mt = b >> 4, nt = b & 15, hp = b & 1, cb = nt >> 1;
    const int par = mt >> 2, j0 = (mt & 3) * 256;
    uint8_t* const g_o = S->o;

    auto load_stage = [&](int p, uint32_t so, int bi) {
        const uint32_t fullA = bars + 8 * (B_FULLA + bi), fullB = bars + 8 * (B_FULLB + bi);
        mbar_expect_tx(fullA, 40960);
        tma_3d(sb + so + 16384, &mw, fullA, nt * 64, p * 64, 0);
        tma_4d(sb + so, &mx, fullA, par * 1024 + p * 64, 0, (j0 >> 5) + 4, 0);
        mbar_expect_tx(fullB, 16384);
        tma_4d(sb + so + 40960, &mx, fullB, par * 1024 + p * 64, 0, j0 >> 5, 0);
    };
    if (warp == 0 && fb < 128 && elect_one()) {
        mbar_init(bars + 8 * B_FULLA, 1); mbar_init(bars + 8 * B_FULLB, 1);
        load_stage(0, STAGE, 0);
    }
    if (fb >= 128) {
        if (fb > 128) { nap(16); TS_END(); return; }
        const uint32_t tag = (ld_rlx(&S->epoch) & 1) - 1;
        if (tid < 8) st_rlx2(&S->sel[tid], ~tag, ~tag);
        uint4 ra, rb;
#pragma unroll 1
        for (int it = 0; it < SPIN_LIMIT; it++) {
            ra = ld_rlx4(&S->rec[tid * 2]); rb = ld_rlx4(&S->rec[1024 + tid * 2]);
            if (!__any_sync(0xffffffffu, (mism(ra.x, ra.z, tag) | mism(rb.x, rb.z, tag)) & 0x8000u)) break;
        }
        __syncwarp();
        TSC(tid == 0, 31);
        sts4(sb + 1024 + tid * 16, ra.y, rb.y, ra.w, rb.w);
        uint4 k = make_uint4(ra.x, ra.z, rb.x, rb.z);
        uint32_t cand;
#pragma unroll 1
        for (int pass = 0; pass < 2; pass++) {
            const uint32_t a0 = max(k.x, k.y), a1 = min(k.x, k.y), a2 = max(k.z, k.w), a3 = min(k.z, k.w), c1 = min(a0, a2), c2 = max(a1, a3);
            k = make_uint4(max(a0, a2), max(c1, c2), min(c1, c2), min(a1, a3));
#pragma unroll
            for (int r = 0; r < 8; r++) {
                const uint32_t m = redux_max(k.x);
                if (lane == r) cand = m;
                if (k.x == m) k = make_uint4(k.y, k.z, k.w, 0);
            }
            if (pass) break;
            if (lane < 8) sts1(sb + (warp * 8 + lane) * 4, cand);
            __syncthreads();
            if (warp) { TS_END(); return; }
            k = lds4(sb + lane * 16);
            TSC(TIMING == 12 && tid == 0 && k.x != 0x12345, 40);
        }
        if (lane < 8) st_rlx2(&S->sel[lane], cand, lds1(sb + 1024 + (~cand & 0x7ffu) * 4));
        TSC(tid == 0, 20);
        TS_END();
        return;
    }
    auto ffn_w = [&](int n, int s) {
        const uint32_t dst = sb + OFF_FW + s * 16384;
        if (n < 8) {
            mbar_expect_tx(bars + 8 * (B_FFULL + s), 16384);
            tma_3d_once(dst, &mgu, bars + 8 * (B_FFULL + s), fb * 32, n * 128, 0);
        } else {
            mbar_expect_tx(bars + 8 * B_F2FULL, 16384);
            tma_2d_once(dst, &mwd, bars + 8 * B_F2FULL, c2 * 64, kc * 448 + 64 + s * 128);
            tma_2d_once(dst + 8192, &mwd, bars + 8 * B_F2FULL, c2 * 64, kc * 448 + 128 + s * 128);
        }
    };
    if (warp == 1 && elect_one()) {
#pragma unroll
        for (int i = 0; i < B_FDONE; i++)
            if (i != B_FULLA && i != B_FULLB) mbar_init(bars + 8 * i, i >= B_FFULL && i < B_F2DONE ? 2 : 1);
    }
    if (warp == 4 && elect_one()) {
#pragma unroll
        for (int i = B_EMPTY; i < NBAR; i++) mbar_init(bars + 8 * i, i < B_UPD ? 2 : i < B_AUX ? 4 : i == B_AUX ? 7 : i == B_CSDONE ? 3 : 8);
    }
    if (warp >= 8 && elect_one()) {
#pragma unroll
        for (int i = 0; i < (B_EMPTY - B_FDONE) / 8; i++) mbar_init(bars + 8 * (B_FDONE + 8 * i - 8 + warp), 1);
    }
    uint32_t epoch;
    if (warp >> 2 == 2) epoch = ld_rlx(&S->epoch);
    __syncthreads();

    if (warp >= 12) {
        reg_dec<24>();
        if (warp > 12) {
            const int p = warp - 13;
            if (p == 1) {
                float sw = 0.f;
                mbar_wait(bars + 8 * (B_ROW + 4), 0);
#pragma unroll 1
                for (int i = 0; i < 16; i++) { const uint32_t q = lds1(sb + OFF_FA + i * 128 + lane * 4); sw += bf_lo(q) + bf_hi(q); }
#pragma unroll 1
                for (int o = 1; o < 32; o <<= 1) sw += __shfl_xor_sync(0xffffffffu, sw, o);
                if (lane == 0) { sts1(sb + OFF_TAG + 4, __float_as_uint(sw)); mbar_arrive(bars + 8 * B_SW); }
            } else {
#pragma unroll 1
                for (int q = 0; q < 4; q++) {
                    nap(p ? (q ? D_R : N_ROW) : (q ? D_X : N_X));
                    if (p == 0) {
                        const __nv_bfloat16* xp = x + (size_t)((j0 + nt * 16 + (lane >> 1)) * 2 + par) * 1024 + q * 256 + (lane & 1) * 64;
                        prefetch_l2(xp); prefetch_l2(xp + 128);
                    } else if (elect_one()) {
                        mbar_expect_tx(bars + 8 * (B_ROW + q), 8192);
                        tma_3d(sb + OFF_FW + q * 8192, &mxs, bars + 8 * (B_ROW + q), 0, j0 + nt * 16, par * 16 + q * 4);
                    }
                }
                if (p == 0) nap(N_CS);
            }
            const uint32_t stg = sb + OFF_FW + 32768 + p * 4096 + lane * 16;
            float c[8];
#pragma unroll
            for (int i = 0; i < 8; i++) c[i] = 0.f;
#pragma unroll 1
            for (int n = 0; n < 10; n++) {
                const uint32_t bo = (n & 1) * 2048, bar = bars + 8 * (B_CS + 2 * p + (n & 1));
                if (n >= 2) {
                    mbar_wait(bar, ~(n >> 1) & 1);
#pragma unroll 2
                    for (int i = 0; i < 4; i++) {
                        const uint4 v = lds4(stg + bo + i * 512);
                        c[0] += bf_lo(v.x); c[1] += bf_hi(v.x); c[2] += bf_lo(v.y); c[3] += bf_hi(v.y);
                        c[4] += bf_lo(v.z); c[5] += bf_hi(v.z); c[6] += bf_lo(v.w); c[7] += bf_hi(v.w);
                    }
                    asm volatile("" :: "f"(c[7]));
                    __syncwarp();
                }
                if (n < 8 && elect_one()) {
                    mbar_expect_tx(bar, 2048);
                    tma_3d(sb + OFF_FW + 32768 + p * 4096 + bo, &mcs, bar, p * 1024 + nt * 64, mt * 8, 2 * n);
                }
            }
            sts4(stg + lane * 16, __float_as_uint(c[0]), __float_as_uint(c[1]), __float_as_uint(c[2]), __float_as_uint(c[3]));
            sts4(stg + lane * 16 + 16, __float_as_uint(c[4]), __float_as_uint(c[5]), __float_as_uint(c[6]), __float_as_uint(c[7]));
            bar_sync(13, 128);
            const uint32_t tag = lds1(sb + OFF_TAG);
            float* gcs = &S->cs[0][p * 1024 + nt * 64];
            {
                const float2 a0 = lds2f(stg - lane * 8), a1 = lds2f(stg - lane * 8 + 256), a2 = lds2f(stg - lane * 8 + 512), a3 = lds2f(stg - lane * 8 + 768);
                st_rlx2(gcs + mt * 3072 + lane * 2, tagf((a0.x + a1.x) + (a2.x + a3.x), tag), __float_as_uint((a0.y + a1.y) + (a2.y + a3.y)));
            }
            fence_async_smem();
            __syncwarp();
            if (lane == 0) mbar_arrive(bars + 8 * B_CSDONE);
            TSC(warp == 13 && lane == 0, 19);
            {
                uint4 v[4];
                const float* src = gcs + (lane >> 4) * 4 * 3072 + (lane & 15) * 4;
#pragma unroll 1
                for (int it = 0; it < SPIN_LIMIT; it++) {
#pragma unroll
                    for (int m = 0; m < 4; m++) v[m] = ld_rlx4(src + m * 3072);
                    if (!__any_sync(0xffffffffu, (mism(v[0].x, v[1].x, tag) | mism(v[2].x, v[3].x, tag)) & 1)) break;
                }
                __syncwarp();
#pragma unroll
                for (int c = 0; c < 4; c++) {
                    const float a = (__uint_as_float((&v[0].x)[c]) + __uint_as_float((&v[1].x)[c])) + (__uint_as_float((&v[2].x)[c]) + __uint_as_float((&v[3].x)[c]));
                    (&v[0].x)[c] = __float_as_uint(a + __shfl_xor_sync(0xffffffffu, a, 16));
                }
                const uint32_t ca = sb + OFF_CS + p * 384 + ((lane & 15) >> 1) * 48 + (lane & 1) * 8;
#pragma unroll 1
                for (int r = 0; r < 3; r++) {
                    const uint32_t u0 = pack_bf16(__uint_as_float(v[0].x), __uint_as_float(v[0].y)), u1 = pack_bf16(__uint_as_float(v[0].z), __uint_as_float(v[0].w));
                    sts2(ca + r * 16, u0, u1);
                    v[0].x = __float_as_uint(__uint_as_float(v[0].x) - bf_lo(u0)); v[0].y = __float_as_uint(__uint_as_float(v[0].y) - bf_hi(u0));
                    v[0].z = __float_as_uint(__uint_as_float(v[0].z) - bf_lo(u1)); v[0].w = __float_as_uint(__uint_as_float(v[0].w) - bf_hi(u1));
                }
                if (lane < 20) sts1(sb + OFF_CS + 1152 + lane * 4, 0);
                fence_async_smem();
            }
            if (p == 1) { if (lane < 2) st_rlx4(&S->hint[b][lane * 4], ~tag, ~tag, ~tag, ~tag); }
            else { st_rlx4(&S->halo[b][p * 128 + lane * 4], ~tag, ~tag, ~tag, ~tag); st_rlx4(&S->halo[b][p * 128 + 128 + lane * 4], ~tag, ~tag, ~tag, ~tag); }
            __syncwarp();
            if (lane == 0) mbar_arrive(bars + 8 * B_AUX);
            TSC(warp == 13 && lane == 0, 21);
            mbar_wait(bars + 8 * B_PART, 0);
            mbar_wait(bars + 8 * (B_EMPTY + 2), 0);
            if (p == 0) {
                if (j0) {
                    nap(N_HA);
#pragma unroll 1
                    for (int it = 0; it < SPIN_LIMIT; it++) {
                        TSC(TIMING == 15 && lane == 0 && it < 8, 40 + it);
                        if (elect_one()) { mbar_expect_tx(bars + 8 * B_CS, 2048); bulk_g2s(sb + OFF_HALO, S->halo[b - 16], 2048, bars + 8 * B_CS); }
                        mbar_wait(bars + 8 * B_CS, it & 1);
                        const uint32_t a = sb + OFF_HALO + lane * 16;
                        if (!__any_sync(0xffffffffu, (mism(lds1(a), lds1(a + 512), tag) | mism(lds1(a + 1024), lds1(a + 1536), tag)) & 1)) break;
                    }
                } else {
#pragma unroll
                    for (int c = 0; c < 4; c++) sts4(sb + OFF_HALO + c * 512 + lane * 16, 0, 0, 0, 0);
                }
                __syncwarp();
                bar_arrive(3, 64);
                TSC(TIMING >= 11 && lane == 0, 34);
            } else {
                const int w = p - 1;
                const uint8_t* osrc = g_o + (size_t)((mt * 2 + hp) * 2 + w) * 131072;
                const bool far = w > hp && j0 && lane >= 16;
                const uint32_t* hsrc = &S->hint[b & 0x70][0] + ((lane & 15) - (far ? 16 : 0)) * 8;
                if (lane == 0 && !w) st_rlx(&S->hint[b][0], tagw(now(), 1u, tag));
                uint32_t hv;
#pragma unroll 1
                for (int it = 0; it < SPIN_LIMIT; it++) {
                    hv = ld_rlx(hsrc);
                    if (!__any_sync(0xffffffffu, (hv ^ tag) & 1)) break;
                }
                TSC(TIMING == 11 && lane == 0, 32 + w);
                const uint32_t tn = __shfl_sync(0xffffffffu, hv, 0) - 0x40000000u;
                hv = redux_max(hv - tn + (far ? T_H : 0)) + tn + T_O + w * T_O1;
                mbar_wait(bars + 8 * (w ? B_AST : B_G1DONE), 0);
                if (elect_one()) {
#pragma unroll 1
                    for (int st = 0; st < 8; st++) {
                        const uint32_t full = bars + 8 * (B_OFULL + 8 * w + st);
                        if (st >= 2) mbar_wait(full + 8 * (B_DONE - B_OFULL - 2), 0);
                        if (st < 3) until(hv + (st == 2 ? T_S2 : st * T_S1));
                        TSC(st == 0, 28 + w);
                        mbar_expect_tx(full, 16384);
                        bulk_g2s(sb + (w ? OFF_O1 : OFF_O0) + (st & 1) * 16384, osrc + st * 16384, 16384, full);
                    }
                }
            }
            TS_END();
            return;
        }
        if (elect_one()) {
            auto load_wo = [&](int s, uint32_t ws) {
                mbar_expect_tx(bars + 8 * (B_WOFULL + s), 32768);
                tma_4d(ws, &mwo, bars + 8 * (B_WOFULL + s), 0, s * 8, 0, cb * 2);
            };
            uint32_t so = 2 * STAGE, ph = 1, cnt = PF_CNT << 4;
            int bi = 1, q = 0;
            mbar_expect_tx(bars + 8 * (B_ROW + 4), 2048);
            bulk_g2s(sb + OFF_FA, wr, 2048, bars + 8 * (B_ROW + 4));
            if (smem_u32(smem) != sb) __trap();
            const char* pf = (b < 64 ? wg : wu) + (b & 63) * 7168;
#pragma unroll 1
            for (int p = 1; p < 16; p++) {
                if (p < 3) nap(p == 1 ? N_S1 : N_S2);
                mbar_wait(bars + 8 * (B_EMPTY + bi), ph);
                load_stage(p, so, bi);
                if (p >= 2 && p < 5) {
                    const int k0 = p == 2 ? 3 : p == 3 ? K_W1 : K_W2, n = ((p == 2 ? K_W1 : p == 3 ? K_W2 : 16) - k0) * 3072;
                    if (p == 2) nap(N_W);
                    bulk_prefetch((const char*)wqkv + k0 * 393216 + b * n, n);
                }
#pragma unroll 1
                for (int e = q + (cnt & 3); q < e; q++) {
                    if (q == 16) pf = wd + mt * 7 * 131072 + nt * 8192;
                    if (q == 23) pf = wo + b * 8192;
                    bulk_prefetch(pf, q < 16 ? 7168 : 8192);
                    pf += q < 16 ? 64 * 7168 : q < 23 ? 131072 : 1048576;
                }
                cnt >>= 2;
                so = so == 2 * STAGE ? 0 : so + STAGE;
                if (++bi == 3) { bi = 0; ph ^= 1; }
            }
            TS(27);
            uint32_t ws = sb + OFF_WO0;
#pragma unroll 1
            for (int i = 0; i < 8; i++) {
                if (i < 2) {
                    mbar_wait(bars + 8 * (B_EMPTY + 1 + i), 0);
                    mbar_expect_tx(bars + 8 * B_XR, 16384);
                    tma_4d(sb + (i ? 0 : OFF_X1), &mx, bars + 8 * B_XR, par * 1024 + cb * 128 + 64 - i * 64, 0, (j0 >> 5) + hp * 4, 0);
                }
                if (i == 1) {
                    mbar_expect_tx(bars + 8 * B_F2FULL, 8192);
                    tma_2d_once(sb + OFF_F2X, &mwd, bars + 8 * B_F2FULL, c2 * 64, kc * 448);
                }
                if (i) {
                    mbar_wait(bars + 8 * (i == 1 ? B_G1DONE : i == 2 ? B_F2DONE : B_DONE - NWO + i), 0);
                    if (i > 1) mbar_wait(bars + 8 * (i == 2 ? B_OFULL + 8 : B_DONE + 8 - NWO + i), 0);
                }
                load_wo(i, ws);
                ws = wo_next(ws, sb, 0);
            }
        }
        TS_END();
    } else if (warp >= 8) {
        reg_dec<40>();
        const int p = warp - 8;
        const bool f1 = fb < 112;
        const uint32_t tag = (epoch & 1) - 1;
        {
            const int ta = tid - 256;
            if (ta < 48) st_rlx4(&S->cs[mt][(ta >> 4) * 1024 + nt * 64 + (ta & 15) * 4], ~tag, ~tag, ~tag, ~tag);
        }
        float s1 = 0.f, s2 = 0.f, sr = 0.f, sw, sh = 0.f;
        {
            const uint32_t xa = sb + OFF_FW + p * 512 + lane * 16, wa = sb + OFF_FA + (((p * 4 + (lane >> 3)) ^ lane) & 7) * 16;
            TSC(TIMING == 12 && lane == 0, 50 + p);
            mbar_wait(bars + 8 * (B_ROW + 4), 0);
            {
                float c1 = 0.f, c2 = 0.f, cr = 0.f;
#pragma unroll 1
                for (int q = 0; q < 4; q++) {
                mbar_wait(bars + 8 * (B_ROW + q), 0);
                TSC(TIMING == 12 && tid == 256 + 96, 32 + q);
                TSC(tid == 256 && q == 3, 17);
#pragma unroll
                for (int i = 0; i < 4; i++) {
                    const uint4 u = lds4(xa + q * 8192 + i * 2048), w4 = lds4(wa + q * 512 + i * 128);
                    const float a0 = bf_lo(u.x), a1 = bf_hi(u.x), a2 = bf_lo(u.y), a3 = bf_hi(u.y), a4 = bf_lo(u.z), a5 = bf_hi(u.z), a6 = bf_lo(u.w), a7 = bf_hi(u.w);
                    s1 += a0 + a1; c1 += a4 + a5; s1 += a2 + a3; c1 += a6 + a7;
                    s2 = fmaf(a0, a0, s2); c2 = fmaf(a4, a4, c2); sr = fmaf(a0, bf_lo(w4.x), sr); cr = fmaf(a4, bf_lo(w4.z), cr);
                    s2 = fmaf(a1, a1, s2); c2 = fmaf(a5, a5, c2); sr = fmaf(a1, bf_hi(w4.x), sr); cr = fmaf(a5, bf_hi(w4.z), cr);
                    s2 = fmaf(a2, a2, s2); c2 = fmaf(a6, a6, c2); sr = fmaf(a2, bf_lo(w4.y), sr); cr = fmaf(a6, bf_lo(w4.w), cr);
                    s2 = fmaf(a3, a3, s2); c2 = fmaf(a7, a7, c2); sr = fmaf(a3, bf_hi(w4.y), sr); cr = fmaf(a7, bf_hi(w4.w), cr);
                }
                }
                s1 += c1; s2 += c2; sr += cr;
            }
            mbar_wait(bars + 8 * B_SW, 0);
            sw = lds1f(sb + OFF_TAG + 4);
#pragma unroll 1
            for (int pass = 0;; pass++) {
#pragma unroll
                for (int o = 1; o < 8; o <<= 1) {
                    s1 += __shfl_xor_sync(0xffffffffu, s1, o); s2 += __shfl_xor_sync(0xffffffffu, s2, o); sr += __shfl_xor_sync(0xffffffffu, sr, o);
                }
                s1 *= 1.f / 1024.f;
                s2 = fmaf(-s1, s1, s2 * (1.f / 1024.f));
                if (!__any_sync(0xffffffffu, !pass && s1 * s1 > 256.f * s2)) break;
                sh = bf16r(s1); s1 = 0.f; s2 = 0.f; sr = 0.f;
#pragma unroll 1
                for (uint32_t o = 0; o < 2048; o = opaque(o + ((o & 12) == 12 ? 116 : 4))) {
                    const uint32_t u = lds1(xa + (o >> 7) * 2048 + (o & 12)), q = lds1(wa + o);
                    const float a0 = bf_lo(u) - sh, a1 = bf_hi(u) - sh;
                    s1 += a0 + a1; s2 = fmaf(a0, a0, fmaf(a1, a1, s2)); sr = fmaf(a0, bf_lo(q), fmaf(a1, bf_hi(q), sr));
                }
            }
        }
        const int ta = opaque(tid) - 256, lane = ta & 31, g = lane >> 2, t = lane & 3;
        {
            if ((lane & 7) == 0) {
                const int s = b * 16 + p * 4 + (lane >> 3);
                const float mb = bf16r(sh + s1);
                float den;
                asm("sqrt.approx.f32 %0, %1;" : "=f"(den) : "f"(bf16r(bf16r(s2) + 1e-5f)));
                den = bf16r(den);
                uint32_t rb = pack_bf16(fmaf(sh - mb, sw, sr) * rcp(den), 0.f);
                if (rb == 0x8000u) rb = 0;
                uint32_t ord = (rb & 0x8000u) ? (~rb & 0xffffu) : (rb | 0x8000u);
                if ((rb & 0x7fffu) > 0x7f80u) ord = 0;
                st_rlx2(&S->rec[s], (ord << 16) | (tag & 0x8000u) | (0x47ffu - (s & 1023) * 2 - par), pack_bf16(mb, den));
            }
            TSC(TIMING == 12 && lane == 0, 36 + p);
            bar_sync(12, 128);
            if (p == 1) sts1(sb + OFF_ROWMAP + lane * 4, 0xffffffffu);
            if (p == 0) {
                if (lane == 0) {
                    sts1(sb + OFF_TAG, tag);
                }
                __syncwarp();
                bar_arrive(13, 128);
            }
            TSC(ta == 0, 18);
        }
        {
            uint2 r[3];
            nap(N_GA);
            const uint2* src = &S->rec[mt * 256 + ta];
            const int l2 = ta < 8 && j0 ? -8 : 0;
#pragma unroll 1
            for (int it = 0; it < SPIN_LIMIT; it++) {
                r[0] = ld_rlx2(src + l2); r[1] = ld_rlx2(src); r[2] = ld_rlx2(src + 128);
                if (!__any_sync(0xffffffffu, (mism(r[0].x, r[1].x, tag) | (r[2].x ^ tag)) & 0x8000u)) break;
            }
#pragma unroll
            for (int n = 0; n < 3; n++)
                if (n || ta < 8) sts2(sb + OFF_STAT + (n ? n * 1024 - 960 : 0) + ta * 8, (r[n].y << 16) ^ 0x80000000u, __float_as_uint(rcp(bf_hi(r[n].y))));
        }
        __syncwarp();
        if (lane == 0) mbar_arrive(bars + 8 * B_AUX);
        TSC(ta == 0, 30);
        if (p == 1) nap(N_F1);
        if (f1 && p < 2 && elect_one()) ffn_w(p, p);
        uint2 sel;
#pragma unroll 1
        for (int it = 0; it < SPIN_LIMIT; it++) {
            sel = ld_rlx2(&S->sel[lane & 7]);
            if (!__any_sync(0xffffffffu, (sel.x ^ tag) & 0x8000u)) break;
            __nanosleep(POLL_NS);
        }
        TSC(ta == 0, 26);
        if (b == 0 && ta == 0) st_rlx(&S->epoch, epoch + 1);
        {
            const __nv_bfloat16* xp = x + (~sel.x & 0x7ffu) * 1024 + (lane >> 3) * 8;
            const uint32_t mb = __byte_perm(sel.y, 0, 0x1010);
            if (p >= 2) nap(N_A2);
#pragma unroll 1
            for (int n = p; n < (f1 ? 8 : 0); n += 4) {
                uint4 v[4];
#pragma unroll
                for (int c = 0; c < 4; c++) v[c] = ldg_nc(xp + n * 128 + c * 32);
                const int s = n % 3;
                if (n >= 2) {
                    mbar_wait(bars + 8 * (n == 2 ? B_CSDONE : B_FDONE + n - 3), 0);
                    if (elect_one()) ffn_w(n & 7, s);
                }
#pragma unroll
                for (int c = 0; c < 4; c++) sts4(sb + OFF_FA + s * 2048 + c * 512 + lane * 16, sub2(v[c].x, mb), sub2(v[c].y, mb), sub2(v[c].z, mb), sub2(v[c].w, mb));
                fence_async_smem();
                __syncwarp();
                if (lane == 0) mbar_arrive(bars + 8 * (B_FFULL + s));
                TSC(TIMING == 12 && lane == 0, 41 + n);
            }
            if (p < 3) {
                mbar_wait(bars + 8 * B_CSDONE, 0);
                mbar_wait(bars + 8 * (f1 ? B_FDONE + 5 + p : B_PART), 0);
                if (elect_one()) ffn_w(8, p ? p - 1 : 2);
            }
        }
        const bool hw = f1 && (p == 0 || p == 3);
        if (hw) st_rlx4(&S->h[fb * 128 + (p & 1) * 64 + (lane & 15) * 4], ~tag, ~tag, ~tag, ~tag);
        st_rlx4(&S->ypart[kc][ta >> 4][c2 * 64 + (ta & 15) * 4], ~tag, ~tag, ~tag, ~tag);
        const float ri[2] = {rcp(bf_hi(__shfl_sync(0xffffffffu, sel.y, 2 * t))), rcp(bf_hi(__shfl_sync(0xffffffffu, sel.y, 2 * t + 1)))};
        mbar_wait(bars + 8 * B_PART, 0);
        if (hw) {
            const uint32_t pa = sb + OFF_FA + (ta & 63) * 16, go = wu < wg ? 1024 : 0;
            const float4 g0 = lds4f(pa + go), g1 = lds4f(pa + 2048 + go), u0 = lds4f(pa + (go ^ 1024)), u1 = lds4f(pa + 2048 + (go ^ 1024));
            float hv[4];
#pragma unroll
            for (int c = 0; c < 4; c++) {
                const float ga = bf16r(((&g0.x)[c] + (&g1.x)[c]) * ri[c & 1]), up = bf16r(((&u0.x)[c] + (&u1.x)[c]) * ri[c & 1]);
                hv[c] = bf16r(ga * sigmoidf(ga)) * up;
            }
#pragma unroll
            for (int hh = 0; hh < 2; hh++) {
                const float o = __shfl_xor_sync(0xffffffffu, (g & 1) ? hv[2 * hh] : hv[2 * hh + 1], 4);
                st_rlx(&S->h[(fb * 4 + (p & 1) * 2 + hh) * 32 + (2 * t + (g & 1)) * 4 + (g >> 1)],
                       tagw((g & 1) ? pack_bf16(o, hv[2 * hh + 1]) : pack_bf16(hv[2 * hh], o), g < 2, tag));
            }
            TSC(ta == 0, 22);
        }
        {
            uint4 hq[4];
            const uint32_t* hp4 = S->h + kc * 1792 + ta * 4;
#pragma unroll 1
            for (int it = 0; it < SPIN_LIMIT; it++) {
#pragma unroll
                for (int n = 0; n < 4; n++) hq[n] = ld_rlx4(hp4 + (n < 3 ? n * 512 : p < 2 ? 1536 : 0));
                if (!__any_sync(0xffffffffu, (mism(hq[0].x, hq[1].x, tag) | mism(hq[2].x, hq[3].x, tag)) & 1)) break;
            }
            mbar_wait(bars + 8 * B_G1DONE, 0);
            bar_sync(12, 128);
#pragma unroll
            for (int n = 0; n < 4; n++) sts4(sb + OFF_FA + ta * 16 + (n < 3 ? n * 2048 : p < 2 ? 6144 : 0), hq[n].x, hq[n].y, hq[n].z, hq[n].w);
            fence_async_smem();
            bar_sync(12, 128);
            TSC(ta == 0, 25);
            mbar_wait(bars + 8 * B_F2FULL, 0);
            mbar_wait(bars + 8 * B_ATT, 0);
            float acc[4] = {0.f, 0.f, 0.f, 0.f};
            uint32_t da = sd + dlo(OFF_F2X, 8192), db = sd + dlo(OFF_FA, 128);
#pragma unroll 1
            for (int q = 0; q < 7; q++) {
                wg_fence();
#pragma unroll
                for (int j = 0; j < 4; j++) wgmma_n8<1, 0>(acc, mkdesc(da + j * 128, dhi(1024, 1)), mkdesc(db + j * 16, dhi(128, 0)));
                wg_commit();
                da = sd + dlo(OFF_FW, 8192) + q * 512; db += 64;
            }
            wg_wait<0>();
            if (ta == 0) mbar_arrive(bars + 8 * B_F2DONE);
#pragma unroll
            for (int c = 0; c < 4; c++) st_rlx(&S->ypart[kc][2 * t + (c & 1)][c2 * 64 + p * 16 + (c >> 1) * 8 + g], tagf(acc[c], tag));
            TSC(ta == 0, 23);
            bar_sync(12, 128);
        }
#pragma unroll 1
        for (int j = 2 * p; j < 2 * p + 2; j++) {
            const uint32_t kj = __shfl_sync(0xffffffffu, sel.x, j);
            const int row = 0x7ff - (kj & 0x7ffu), jj = (row >> 1) - j0 - hp * 128;
            float a0 = 0.f, a1 = 0.f, a2 = 0.f, a3 = 0.f, sig = 0.f;
            if ((row & 1) == par && jj >= 0 && jj < 128) {
                sig = bf16r(sigmoidf(__uint_as_float(((int)kj < 0 ? kj ^ 0x80000000u : ~kj) & 0xffff0000u)));
#pragma unroll 1
                for (int hh = 0; hh < 8; hh += 4) {
                    uint4 v[4];
#pragma unroll 1
                    for (int it = 0; it < SPIN_LIMIT; it++) {
#pragma unroll
                        for (int m = 0; m < 4; m++) v[m] = ld_rlx4(&S->ypart[hh + m][j][cb * 128 + lane * 4]);
                        if (!__any_sync(0xffffffffu, (mism(v[0], tag) | mism(v[1], tag) | mism(v[2], tag) | mism(v[3], tag)) & 1)) break;
                    }
#pragma unroll
                    for (int m = 0; m < 4; m++) { a0 += __uint_as_float(v[m].x); a1 += __uint_as_float(v[m].y); a2 += __uint_as_float(v[m].z); a3 += __uint_as_float(v[m].w); }
                }
                asm volatile("st.shared.u8 [%0], %1;" ::"r"(sb + OFF_ROWMAP + jj), "r"(j) : "memory");
            }
            sts2(sb + OFF_FA + (lane >> 1) * 128 + j * 16 + (lane & 1) * 8, pack_bf16(bf16r(a0) * sig, bf16r(a1) * sig), pack_bf16(bf16r(a2) * sig, bf16r(a3) * sig));
        }
        fence_async_smem();
        __syncwarp();
        if (lane == 0) mbar_arrive(bars + 8 * B_UPD);
        TSC(ta == 0, 24);
        TS_END();
    } else {
        reg_inc<224>();
        const int w = warp >> 2, wi = warp & 3, tw = (1 - w) * 4 + wi;
        const bool elect = (tid & 127) == 0;
        const uint32_t ln = opaque(lane), g = ln >> 2, t = ln & 3;
        uint32_t tag, ow[8][4];
        auto store_o = [&](int f0, int f1) {
            uint8_t* ob = g_o + (size_t)((mt * 2 + 1 - w) * 2 + 1 - (wi >> 1)) * 131072 + nt * 1024 + (wi & 1) * 512 + ln * 4;
#pragma unroll
            for (int f = f0; f < f1; f++)
#pragma unroll
                for (int i = 3; i >= 0; i--)
                    st_rlx(ob + f * 16384 + i * 128, ow[f][i]);
        };
        {
            float acc[2][96];
            const uint32_t sta = opaque(sb + OFF_STAT + tw * 256 + 64 + g * 8);
            {
                float fa[4] = {0.f, 0.f, 0.f, 0.f};
                uint32_t so = STAGE >> 4, bo = bars, ph = 0;
                const uint32_t dx0 = sd + dlo(w ? 40960 : 0, 16), dw0 = sd + dlo(16384, 8192);
                int p = 0;
                if (w) bar_arrive(1, 256);
                uint32_t fm = fb < 112 ? F1_MASK >> (16 * w) : 0u, fph = 0, fd = bars + 8 * (B_FDONE + w);
                int fs = w;
#pragma unroll 1
                for (; p < 16; p++) {
                    mbar_wait(bo + 8 * B_FULLA, ph);
                    if (w) mbar_wait(bo + 8 * B_FULLB, ph);
                    TSC(elect && p == 0, 1 + 8 * w);
                    TSC(TIMING == 9 && elect && p >= 9 && p < 14, 32 + (p - 9) * 6 + w * 3);
                    bar_sync(1 + w, 256);
                    TSC(TIMING == 1 && tid == 0, 32 + p);
                    if (p == 15) {
                        wg_fence();
                        wgmma_n192<0, 1>(acc[1], mkdesc(sd + dlo(OFF_MEAN + 1024, 0) + w * 128, dhi(128, 0)), mkdesc(sd + dlo(OFF_CS, 0), dhi(48, 0)));
                        wgmma_n192<0, 1>(acc[0], mkdesc(sd + dlo(OFF_MEAN, 0) + w * 128, dhi(128, 0)), mkdesc(sd + dlo(OFF_CS, 0), dhi(48, 0)));
                        wg_commit();
                    }
                    wg_fence();
#pragma unroll
                    for (int h = 1; h >= 0; h--) {
#pragma unroll
                        for (int k = 0; k < 4; k++) wgmma_n192<0, 1>(acc[h], mkdesc(dx0 + so + h * 512 + k * 2, dhi(1024, 1)), mkdesc(dw0 + so + k * 128, dhi(1024, 1)), k ? 1 : p);
                        wg_commit();
                    }
                    if (fm & 1) {
                        mbar_wait(bars + 8 * (B_FFULL + fs), fph);
                        TSC(TIMING == 9 && elect && p >= 9, 33 + (p - 9) * 6 + w * 3);
                        wg_fence();
#pragma unroll
                        for (int j = 0; j < 8; j++)
                            wgmma_n8<1, 0>(fa, mkdesc(sd + dlo(OFF_FW, 8192) + fs * 1024 + j * 64, dhi(512, 2)), mkdesc(sd + dlo(OFF_FA, 128) + fs * 128 + j * 16, dhi(128, 0)));
                        wg_commit();
                    }
                    bar_arrive(2 - w, 256);
                    if (p == 15) break;
                    wg_wait<0>();
                    TSC(TIMING == 9 && elect && p >= 9 && p < 14, 34 + (p - 9) * 6 + w * 3);
                    if (wi == 0 && elect_one()) { mbar_arrive(bo + 8 * B_EMPTY); if (fm & 1) mbar_arrive(fd); }
                    so = so == 2 * (STAGE >> 4) ? 0 : so + (STAGE >> 4);
                    bo += 8;
                    if (bo == bars + 24) { bo = bars; ph ^= 1; }
                    if (fm & 1) { fd += 16; fs += 2; if (fs >= 3) { fs -= 3; fph ^= 1; } }
                    fm >>= 1;
                    if (p == P_PART) {
                        if (fb < 112) sts4(sb + OFF_FA + tid * 16, __float_as_uint(fa[0]), __float_as_uint(fa[1]), __float_as_uint(fa[2]), __float_as_uint(fa[3]));
                        __syncwarp();
                        if (lane == 0) mbar_arrive(bars + 8 * B_PART);
                    }
                    if (p != 14) continue;
                    mbar_wait(bars + 8 * B_AUX, 0);
                    mbar_wait(bars + 8 * (B_EMPTY + 1), 0);
                    const uint32_t hm = __float_as_uint(0.5f * lds1f(sb + OFF_STAT + 64 + tw * 256 + ln * 8)) >> 16;
                    sts4(sb + OFF_MEAN + w * 2048 + wi * 256 + (ln >> 4) * 1024 + (ln & 15) * 16, hm * 0x10001u, hm, 0, 0);
                    fence_async_smem();
                }
            }
            TSC(TIMING != 14 && elect, 2 + 8 * w);

            tag = lds1(sb + OFF_TAG);
            mbar_wait(bars + 8 * (B_EMPTY + 2), 0);
            wg_wait<1>();
#pragma unroll
            for (int i = 0; i < 96; i++) asm volatile("" : "+f"(acc[1][i]) :: "memory");
            uint32_t pk[4][24];
            const uint32_t hm = tw == 7 ? ~ln & 1 : 0;
            auto np = [&](int i, int j) {
                const float* a = &acc[i >> 1][4 * j + 2 * (i & 1)];
                pk[i][j] = pack_bf16(a[0], a[1]);
                if (j >= 16) pk[i][j] = movm(pk[i][j]);
                if (i == 3 && j >= 8 && !(j & 1)) pk[i][j] = tagw(pk[i][j], hm, tag);
            };
            const uint32_t ha = sb + OFF_HALO + tw * 2048 + ln * 8;
#pragma unroll
            for (int j = 8; j < 24; j += 2) {
                np(3, j); np(3, j + 1);
                sts2(ha + 2048 + (j - 8) * 128, pk[3][j], pk[3][j + 1]);
                asm volatile("{\n.reg .pred p;\nsetp.eq.u32 p, %3, 7;\n@p st.relaxed.gpu.global.v2.u32 [%0], {%1,%2};\n}" ::"l"((char*)&S->halo[b][ln * 2] + (j - 8) * 128),
                             "r"(pk[3][j]), "r"(pk[3][j + 1]), "r"(tw) : "memory");
            }
            bar_arrive(4 + tw, 64);
            TSC(TIMING == 15 && ln == 0 && tw == 7, 39);
            TSC(TIMING == 8 && ln == 0 && wi == 1, 32 + 8 * w);
            const bool u0 = 2 * t > g, u1 = 2 * t + 1 > g;
            const uint32_t mU = (u0 ? 0xffffu : 0u) | (u1 ? 0xffff0000u : 0u);
            uint2 hl[8];
            float rk[4][2], fq[4][2];
            auto factors = [&]() {
                const uint32_t ka = sb + OFF_STAT + tw * 256 + 4 + t * 16, k0 = opaque(ka + (u0 ? 0 : 64)), k1 = opaque(ka + (u1 ? 8 : 72));
#pragma unroll
                for (int i = 0; i < 4; i++) {
                    const float rq = lds1f(sta + i * 64 + 4) * (0.17677669529663687f * 1.4426950408889634f);
                    rk[i][0] = lds1f(k0 + i * 64); rk[i][1] = lds1f(k1 + i * 64);
                    fq[i][0] = rq * rk[i][0]; fq[i][1] = rq * rk[i][1];
                }
            };
#pragma unroll
            for (int jj = 0; jj < 12; jj++) { const int j = (jj >> 2) * 8 + (jj & 3); np(2, j); if (j < 8) np(3, j); }
            factors();
            wg_wait<0>();
#pragma unroll
            for (int i = 0; i < 96; i++) asm volatile("" : "+f"(acc[0][i]) :: "memory");
            if (elect) mbar_arrive(bars + 8 * B_G1DONE);
            const float mask = tw == 0 && j0 == 0 ? -INFINITY : 0.f;
#pragma unroll
            for (int hd = 0; hd < 2; hd++) {
#pragma unroll
                for (int jj = 0; jj < 12; jj++) {
                    const int j = (jj >> 2) * 8 + hd * 4 + (jj & 3);
                    np(0, j); np(1, j);
                    if (j & 4)
                    { np(2, j); if (j < 8) np(3, j); }
                }
                if (hd == 0) mbar_wait(bars + 8 * B_G1DONE, 0);
                float s[2][3][4];
#pragma unroll
                for (int h = 1; h >= 0; h--)
#pragma unroll
                    for (int n = 2; n >= 0; n--) {
                        if (h == 0 && n == 0 && hd == 0) {
                            TSC(TIMING == 8 && ln == 0 && wi == 1 && s[1][0][0] + s[0][1][0] != 123.456f, 33 + 8 * w);
                            bar_sync(3 + tw, 64);
#pragma unroll
                            for (int c = 0; c < 8; c++) hl[c] = lds2(ha + c * 256);
                        }
                        const int kg = 2 * h - 1 + n;
                        s[h][n][0] = s[h][n][1] = kg < 0 ? mask : 0.f; s[h][n][2] = s[h][n][3] = 0.f;
#pragma unroll
                        for (int ks = 0; ks < 2; ks++) {
                            const int q = hd * 4 + 2 * ks;
                            const uint32_t* k = kg < 0 ? &hl[hd * 2 + ks].x : &pk[kg < 0 ? 0 : kg][8 + q];
                            mma16816(s[h][n], pk[2 * h][q], pk[2 * h + 1][q], pk[2 * h][q + 1], pk[2 * h + 1][q + 1], k[0], k[1]);
                        }
                    }
                uint32_t pp[4], pc[4];
#pragma unroll
                for (int i = 0; i < 4; i++) {
                    const float* sp = &s[i >> 1][i & 1][2 * (i & 1)];
                    const float* sc = &s[i >> 1][(i & 1) + 1][2 * (i & 1)];
                    float a0 = (u0 ? sp[0] : sc[0]) * fq[i][0], a1 = (u1 ? sp[1] : sc[1]) * fq[i][1];
                    float m = fmaxf(a0, a1);
                    m = fmaxf(m, __shfl_xor_sync(0xffffffffu, m, 1));
                    m = fmaxf(m, __shfl_xor_sync(0xffffffffu, m, 2));
                    a0 = ex2(a0 - m); a1 = ex2(a1 - m);
                    float sum = a0 + a1;
                    sum += __shfl_xor_sync(0xffffffffu, sum, 1);
                    sum += __shfl_xor_sync(0xffffffffu, sum, 2);
                    const float inv = rcp(sum);
                    const uint32_t pw = pack_bf16(a0 * rk[i][0] * inv, a1 * rk[i][1] * inv);
                    pp[i] = pw & mU; pc[i] = pw & ~mU;
                }
                TSC(TIMING == 8 && ln == 0 && wi == 1 && pp[0] + pp[3] != 0x12345, 34 + 2 * hd + 8 * w);
#pragma unroll
                for (int fh = 0; fh < 2; fh++)
#pragma unroll
                    for (int i = 0; i < 4; i++) {
                        const int v = 16 + hd * 4 + 2 * fh;
                        const uint32_t* vp = i ? &pk[i ? i - 1 : 0][v] : &hl[4 + hd * 2 + fh].x;
                        float o[4] = {0.f, 0.f, 0.f, 0.f};
                        if (i & 1) mma16816(o, vp[0], vp[1], pk[i][v], pk[i][v + 1], pp[i], pc[i]);
                        else { mma1688(o, pk[i][v], pk[i][v + 1], pc[i]); mma1688(o, vp[0], vp[1], pp[i]); }
                        const uint32_t tm = (ln & 7) == (nt & 3) * 2 + (i & 1);
                        ow[hd * 4 + 2 * fh][i] = tagw(pack_bf16(o[0], o[1]), tm, tag); ow[hd * 4 + 2 * fh + 1][i] = tagw(pack_bf16(o[2], o[3]), tm, tag);
                    }
                store_o(hd ? ST_A : 0, hd ? ST_B : ST_A);
                TSC(TIMING == 11 && !hd && ln == 0 && wi == 3, 45 + w);
                if (!hd) mbar_arrive_after(bars + 8 * B_AST, ln, hl[2].x ^ hl[3].x ^ hl[5].x ^ hl[6].x ^ hl[7].x);
                mbar_wait(bars + 8 * B_G1DONE, 0);
                if (hd && ln == 0) mbar_arrive(bars + 8 * B_ATT);
                TSC(TIMING != 14 && elect && hd == 0, 3 + 8 * w);
                TSC(TIMING == 8 && ln == 0 && wi == 1, 35 + 2 * hd + 8 * w);
            }
        }
        TSC(TIMING != 14 && elect, 4 + 8 * w);
        float acc2[64];
        TSC(TIMING != 14 && elect, 5 + 8 * w);
        {
            const uint32_t ring = sb + (w ? OFF_O1 : OFF_O0), da0 = (ring >> 4) + dlo(0, 1024);
            const uint32_t l2 = opaque(ln), chk = ring + wi * 256 + (l2 >> 3) * 1032 + ((l2 >> 2) & 1) * 132 + (l2 & 3) * 32;
            const uint32_t xs = sb + (wi & 1) * 8192 + (tw >> 1) * 2048, mad = xs + (l2 & 15) * 128;
            auto residual = [&](float* base) {
                const uint32_t sta = sb + OFF_STAT + (8 + hp * 128 + tw * 16 + g) * 8;
                const float2 s0 = lds2f(sta), s1 = lds2f(sta + 64);
                const float m0 = s0.x * s0.y, r0 = 1.f + s0.y, m1 = s1.x * s1.y, r1 = 1.f + s1.y;
                mbar_wait(bars + 8 * B_XR, 0);
#pragma unroll
                for (int j = 0; j < 16; j += 2) {
                    uint32_t xr[4];
                    asm volatile("ldmatrix.sync.aligned.m8n8.x4.shared.b16 {%0,%1,%2,%3}, [%4];" : "=r"(xr[0]), "=r"(xr[1]), "=r"(xr[2]), "=r"(xr[3])
                                 : "r"(mad + (j >> 3) * OFF_X1 + ((((j & 7) + (l2 >> 4)) ^ (l2 & 7)) << 4)) : "memory");
#pragma unroll
                    for (int c = 0; c < 4; c++) {
                        base[4 * j + 2 * c] = fmaf(bf_lo(xr[c]), c & 1 ? r1 : r0, c & 1 ? m1 : m0); base[4 * j + 2 * c + 1] = fmaf(bf_hi(xr[c]), c & 1 ? r1 : r0, c & 1 ? m1 : m0);
                        asm volatile("" : "+f"(base[4 * j + 2 * c]), "+f"(base[4 * j + 2 * c + 1]) :: "memory");
                    }
                }
            };
            residual(acc2);
            uint32_t db = sd + dlo(OFF_WO0, 16384);
#pragma unroll 1
            for (int s = 0; s < 8; s++) {
                const uint32_t ro = (s & 1) * 16384;
                mbar_wait(bars + 8 * (B_WOFULL + s), 0);
                TSC(TIMING == 11 && tid == 0 && s == 0, 43);
                mbar_wait(bars + 8 * (B_OFULL + s) + 64 * w, 0);
                TSC(TIMING == 11 && tid == 0 && s == 0, 44);
#pragma unroll 1
                for (int it = 0; __any_sync(0xffffffffu, (mism(lds1(chk + ro), lds1(chk + ro + 4096), tag) | mism(lds1(chk + ro + 8192), lds1(chk + ro + 12288), tag)) & 1) && it < SPIN_LIMIT; it++) {
                    NRETRY();
                    const uint32_t fo = wi * 256 + (l2 >> 4) * 1024 + (l2 & 15) * 16;
                    uint4 v[8];
#pragma unroll
                    for (int c = 0; c < 8; c++) v[c] = ld_rlx4(g_o + (size_t)(((mt * 2 + hp) * 2 + w) * 8 + s) * 16384 + fo + c * 2048);
#pragma unroll
                    for (int c = 0; c < 8; c++) sts4(ring + ro + fo + c * 2048, v[c].x, v[c].y, v[c].z, v[c].w);
                    fence_async_smem();
                    __syncwarp();
                }
                if (s == 0) mbar_wait(bars + 8 * B_ATT, 0);
                if (s <= 8 - LAST) bar_sync(1 + w, 256);
                TSC(elect && s == 0, 6 + 8 * w);
                TSC(TIMING == 2 && elect, 32 + 16 * w + s);
                wg_fence();
#pragma unroll
                for (int k = 0; k < 8; k++)
                    wgmma_n128<1, 1>(acc2, mkdesc(da0 + (ro >> 4) + k * 128, dhi(128, 0)), mkdesc(db + k * 128, dhi(1024, 1)));
                wg_commit();
                db = wo_next(db, sd + dlo(0, 16384), 4);
                if (s < 8 - LAST) {
                    bar_arrive(2 - w, 256);
                    if (s == 0) store_o(ST_B, 8);
                    wg_wait<0>();
                    if (elect) mbar_arrive(bars + 8 * (B_DONE + s) + 64 * w);
                }
            }
            mbar_wait(bars + 8 * B_UPD, 0);
            int sl0, sl1;
            asm volatile("ld.shared.s8 %0, [%1];" : "=r"(sl0) : "r"(sb + OFF_ROWMAP + tw * 16 + g) : "memory");
            asm volatile("ld.shared.s8 %0, [%1];" : "=r"(sl1) : "r"(sb + OFF_ROWMAP + tw * 16 + 8 + g) : "memory");
            const uint32_t e0 = (sl0 >> 1) == (int)t ? 0x3f80u << ((sl0 & 1) * 16) : 0u, e1 = (sl1 >> 1) == (int)t ? 0x3f80u << ((sl1 & 1) * 16) : 0u;
            wg_fence();
            wgmma_rs_n128<1>(acc2, e0, e1, 0u, 0u, mkdesc(sd + dlo(OFF_FA, 0), dhi(128, 0)));
            wg_commit();
            bar_arrive(2 - w, 256);
            wg_wait<0>();
#pragma unroll
            for (int i = 0; i < 64; i++) asm volatile("" : "+f"(acc2[i]) :: "memory");
            TSC(elect, 7 + 8 * w);
#pragma unroll
            for (int j = 0; j < 16; j += 2) {
                const int ch = (j & 7) + (l2 >> 4);
                asm volatile("stmatrix.sync.aligned.m8n8.x4.shared.b16 [%0], {%1,%2,%3,%4};" ::"r"(mad + (j >> 3) * OFF_X1 + ((ch ^ (l2 & 7)) << 4)),
                             "r"(pack_bf16(acc2[4 * j], acc2[4 * j + 1])), "r"(pack_bf16(acc2[4 * j + 2], acc2[4 * j + 3])),
                             "r"(pack_bf16(acc2[4 * j + 4], acc2[4 * j + 5])), "r"(pack_bf16(acc2[4 * j + 6], acc2[4 * j + 7])) : "memory");
                if ((j & 7) == 6) {
                    fence_async_smem();
                    __syncwarp();
                    if (ln == 0) tma_store_2d(&mout, xs + (j >> 3) * OFF_X1, par * 1024 + cb * 128 + (j >> 3) * 64, j0 + hp * 128 + tw * 16);
                }
            }
            if (ln == 0) asm volatile("cp.async.bulk.commit_group;\ncp.async.bulk.wait_group.read 0;" ::: "memory");
            TSC(elect, 8 + 8 * w);
            TS_END();
        }
    }
}

typedef CUresult (*EncodeFn)(CUtensorMap*, CUtensorMapDataType, cuuint32_t, void*, const cuuint64_t*, const cuuint64_t*, const cuuint32_t*,
                             const cuuint32_t*, CUtensorMapInterleave, CUtensorMapSwizzle, CUtensorMapL2promotion, CUtensorMapFloatOOBfill);

CUtensorMap make_map(EncodeFn fn, const void* base, int rank, const cuuint64_t* dims, const cuuint64_t* strides, const cuuint32_t* box,
                     CUtensorMapSwizzle swz = CU_TENSOR_MAP_SWIZZLE_128B, CUtensorMapL2promotion pro = CU_TENSOR_MAP_L2_PROMOTION_L2_256B) {
    CUtensorMap m;
    cuuint32_t es[5] = {1, 1, 1, 1, 1};
    fn(&m, CU_TENSOR_MAP_DATA_TYPE_BFLOAT16, rank, (void*)base, dims, strides, box, es, CU_TENSOR_MAP_INTERLEAVE_NONE,
       swz, pro, CU_TENSOR_MAP_FLOAT_OOB_FILL_NONE);
    return m;
}

}

extern "C" void kernel_launch(void* const* d_in, const int* in_sizes, int n_in, void* d_out, int out_size) {
    (void)in_sizes; (void)n_in; (void)out_size;
    const __nv_bfloat16* x = (const __nv_bfloat16*)d_in[0];
    const __nv_bfloat16* wqkv = (const __nv_bfloat16*)d_in[1];
    const char* wo = (const char*)d_in[2];
    const __nv_bfloat16* wr = (const __nv_bfloat16*)d_in[4];
    const char* wg = (const char*)d_in[5];
    const char* wu = (const char*)d_in[6];
    const char* wd = (const char*)d_in[7];
    static EncodeFn fn = nullptr;
    static int by_sm = 0;
    static Scratch* scr = nullptr;
    if (!fn) {
        void* p = nullptr; cudaDriverEntryPointQueryResult q;
        cudaGetDriverEntryPoint("cuTensorMapEncodeTiled", &p, cudaEnableDefault, &q);
        fn = (EncodeFn)p;
        cudaFuncSetAttribute(fused_kernel, cudaFuncAttributeMaxDynamicSharedMemorySize, SMEM_LAUNCH);
        cudaGetSymbolAddress((void**)&scr, g_scr);
        int dev = 0, sms = 0;
        cudaGetDevice(&dev);
        cudaDeviceGetAttribute(&sms, cudaDevAttrMultiProcessorCount, dev);
        by_sm = sms == 132;
    }
    Roles roles;
    for (int i = 0; i < 132; i++) {
        const int T = i >> 1, T8 = T < 32 ? T : T + 1 + (T - 32) / 7, fb = (T < 60 ? (~T8 & 7) * 8 + (T8 >> 3) : T < 62 ? T + 4 : T - 2) * 2 + (i & 1);
        roles.v[i] = fb | ((fb & ~31) | (fb & 1) << 4 | (fb & 31) >> 1) << 8;
    }
    const cuuint64_t xd[4] = {2048, 16, 32, 2}, xs[3] = {4096, 131072, 65536};
    const cuuint32_t xb[4] = {64, 16, 4, 2};
    const cuuint64_t wdm[3] = {1024, 1024, 3}, wst[2] = {6144, 2048};
    const cuuint32_t wb[3] = {64, 64, 3};
    const cuuint64_t od[4] = {64, 64, 16, 16}, ost[3] = {2048, 131072, 128};
    const cuuint32_t ob[4] = {64, 8, 16, 2};
    const cuuint64_t yd[2] = {2048, 1024}, yst[1] = {4096};
    const cuuint32_t yb[2] = {64, 16};
    const cuuint64_t sd[3] = {64, 1024, 32}, sst[2] = {4096, 128};
    const cuuint32_t sbx[3] = {64, 16, 4};
    CUtensorMap mxs = make_map(fn, x, 3, sd, sst, sbx);
    const cuuint64_t cd[3] = {3072, 64, 16}, cst[2] = {6144, 393216};
    const cuuint32_t cbx[3] = {64, 8, 2};
    CUtensorMap mcs = make_map(fn, wqkv, 3, cd, cst, cbx, CU_TENSOR_MAP_SWIZZLE_NONE);
    CUtensorMap mx = make_map(fn, x, 4, xd, xs, xb), mw = make_map(fn, wqkv, 3, wdm, wst, wb);
    CUtensorMap mwo = make_map(fn, wo, 4, od, ost, ob), mout = make_map(fn, d_out, 2, yd, yst, yb);
    const cuuint64_t gd[3] = {3584, 1024, 2}, gst[2] = {7168, (cuuint64_t)(wu < wg ? wg - wu : wu - wg)};
    const cuuint32_t gb[3] = {32, 128, 2};
    const cuuint64_t dd[2] = {1024, 3584}, dst[1] = {2048};
    const cuuint32_t db[2] = {64, 64};
    CUtensorMap mgu = make_map(fn, wu < wg ? wu : wg, 3, gd, gst, gb, CU_TENSOR_MAP_SWIZZLE_64B, CU_TENSOR_MAP_L2_PROMOTION_L2_128B);
    CUtensorMap mwd = make_map(fn, wd, 2, dd, dst, db, CU_TENSOR_MAP_SWIZZLE_128B, CU_TENSOR_MAP_L2_PROMOTION_L2_128B);
    fused_kernel<<<132, 512, SMEM_LAUNCH, cudaStreamPerThread>>>(by_sm, x, wqkv, wr, scr, wg, wu, wd, wo, roles, mw, mx, mwo, mxs, mcs, mout, mgu, mwd);
}
```

```cpp
#include <cuda_runtime.h>
#include <cuda.h>
#include <cuda_bf16.h>
#include <stdint.h>

namespace {

constexpr int STAGE = 57344;
constexpr int OFF_FW = 3 * STAGE;
constexpr int OFF_FA = OFF_FW + 49152;
constexpr int OFF_CS = OFF_FA + 6144;
constexpr int OFF_STAT = OFF_CS + 1232;
constexpr int OFF_ROWMAP = OFF_STAT + 2112;
constexpr int OFF_TAG = OFF_ROWMAP + 128;
constexpr int OFF_BAR = OFF_TAG + 8;
constexpr int OFF_F2X = 16384, OFF_HALO = 24576, OFF_O1 = 24576, OFF_O0 = 90112, NWO = 3, OFF_MEAN = 2 * STAGE, OFF_X1 = 2 * STAGE + 8192;
constexpr int OFF_WO0 = OFF_X1 + 16384, OFF_WO1 = STAGE, OFF_WO2 = OFF_FW;
static_assert(OFF_WO0 + 32768 == OFF_FW && OFF_WO1 + 32768 == OFF_O0 && OFF_O0 + 32768 == OFF_X1 && OFF_O1 + 32768 == STAGE, "alias");
__host__ __device__ constexpr uint32_t wo_next(uint32_t o, uint32_t base, int sh) { return o == base + (OFF_WO0 >> sh) ? base + (OFF_WO1 >> sh) : o == base + (OFF_WO1 >> sh) ? base + (OFF_WO2 >> sh) : base + (OFF_WO0 >> sh); }
constexpr int B_FULLA = 0, B_FULLB = 3, B_ROW = 6, B_FFULL = 11, B_F2DONE = 14, B_SW = 15, B_CS = 16, B_FDONE = 22, B_WOFULL = B_FDONE + 8, B_OFULL = B_WOFULL + 8,
              B_DONE = B_OFULL + 16;
constexpr int B_EMPTY = B_DONE + 16, B_XR = B_EMPTY + 3, B_G1DONE = B_XR + 1;
constexpr int B_UPD = B_G1DONE + 1, B_F2FULL = B_UPD + 1;
constexpr int B_AUX = B_F2FULL + 1, B_PART = B_AUX + 1, B_ATT = B_PART + 1, B_CSDONE = B_ATT + 1, B_AST = B_CSDONE + 1, NBAR = B_AST + 1;
constexpr int SMEM_BYTES = OFF_BAR + NBAR * 8;
static_assert(SMEM_BYTES <= 232448 && OFF_BAR % 8 == 0, "smem");
#define P_PART 13
#define F1_MASK (0x6a005a00u >> (14 - P_PART))
#define PF_CNT 0x2aaaaacu
#define N_S1 1
#define N_S2 3
#define ST_A 2
#define ST_B 5
#define T_H 0
#define T_O1 250
#define T_O 1750
#define T_S1 128
#define T_S2 950
#define N_GA 4
#define N_X 1
#define D_X 2
#define D_R 3
#define N_ROW 5
#define N_W 5
#define K_W1 5
#define K_W2 10
#define N_CS 3
#define N_F1 4
#define LAST 2
#define N_HA 4
#define N_A2 4
#define PFM 5
#define EARLY_HINT 900
#define SPREAD 1
#define SKIP_UPD 1
#define POLL_NS 100
constexpr int SPIN_LIMIT = 1 << 18;

struct Scratch {
    uint8_t o[2048 * 1024 * 2];
    uint2 rec[2048];
    float cs[8][3072];
    uint32_t halo[128][512];
    uint32_t h[14336];
    float ypart[8][8][1024];
    uint2 sel[16];
    uint32_t hint[128][8];
    uint32_t epoch;
};
__device__ __align__(1024) Scratch g_scr;

#define TS(i) do {} while (0)
#define TS_END() do {} while (0)
constexpr int SMEM_LAUNCH = SMEM_BYTES;
#define TSC(c, i) do {} while (0)
#define NRETRY() do {} while (0)
__device__ __forceinline__ uint32_t smem_u32(const void* p) { return (uint32_t)__cvta_generic_to_shared(p); }
__device__ __forceinline__ void mbar_init(uint32_t bar, uint32_t cnt) { asm volatile("mbarrier.init.shared::cta.b64 [%0], %1;" ::"r"(bar), "r"(cnt) : "memory"); }
__device__ __forceinline__ void mbar_expect_tx(uint32_t bar, uint32_t bytes) { asm volatile("mbarrier.arrive.expect_tx.shared::cta.b64 _, [%0], %1;" ::"r"(bar), "r"(bytes) : "memory"); }
__device__ __forceinline__ void mbar_arrive(uint32_t bar) { asm volatile("mbarrier.arrive.shared::cta.b64 _, [%0];" ::"r"(bar) : "memory"); }
__device__ __forceinline__ void mbar_arrive_after(uint32_t bar, uint32_t lane, uint32_t dep) {
    asm volatile("{\n.reg .pred p;\n.reg .b32 t;\nsetp.eq.u32 p, %1, 0;\nmad.lo.u32 t, %1, %2, %0;\n@p mbarrier.arrive.shared::cta.b64 _, [t];\n}" ::"r"(bar), "r"(lane), "r"(dep) : "memory");
}
__device__ __forceinline__ void mbar_wait(uint32_t bar, uint32_t parity) {
    asm volatile("{\n.reg .pred P1;\nLAB_WAIT:\nmbarrier.try_wait.parity.shared::cta.b64 P1, [%0], %1;\n@!P1 bra LAB_WAIT;\n}" ::"r"(bar), "r"(parity) : "memory");
}
__device__ __forceinline__ void tma_3d(uint32_t dst, const CUtensorMap* m, uint32_t bar, int c0, int c1, int c2) {
    asm volatile("cp.async.bulk.tensor.3d.shared::cluster.global.mbarrier::complete_tx::bytes [%0], [%1, {%3, %4, %5}], [%2];" ::"r"(dst), "l"(m), "r"(bar), "r"(c0), "r"(c1), "r"(c2) : "memory");
}
__device__ __forceinline__ void tma_2d_once(uint32_t dst, const CUtensorMap* m, uint32_t bar, int c0, int c1) {
    asm volatile("cp.async.bulk.tensor.2d.shared::cluster.global.mbarrier::complete_tx::bytes.L2::cache_hint [%0], [%1, {%3, %4}], [%2], %5;" ::"r"(dst), "l"(m), "r"(bar), "r"(c0), "r"(c1), "l"(0x12F0000000000000ull) : "memory");
}
__device__ __forceinline__ void tma_3d_once(uint32_t dst, const CUtensorMap* m, uint32_t bar, int c0, int c1, int c2) {
    asm volatile("cp.async.bulk.tensor.3d.shared::cluster.global.mbarrier::complete_tx::bytes.L2::cache_hint [%0], [%1, {%3, %4, %5}], [%2], %6;" ::"r"(dst), "l"(m), "r"(bar), "r"(c0), "r"(c1), "r"(c2), "l"(0x12F0000000000000ull) : "memory");
}
__device__ __forceinline__ void tma_4d(uint32_t dst, const CUtensorMap* m, uint32_t bar, int c0, int c1, int c2, int c3) {
    asm volatile("cp.async.bulk.tensor.4d.shared::cluster.global.mbarrier::complete_tx::bytes [%0], [%1, {%3, %4, %5, %6}], [%2];" ::"r"(dst), "l"(m), "r"(bar), "r"(c0), "r"(c1), "r"(c2), "r"(c3) : "memory");
}
__device__ __forceinline__ void tma_store_2d(const CUtensorMap* m, uint32_t src, int c0, int c1) {
    asm volatile("cp.async.bulk.tensor.2d.global.shared::cta.bulk_group [%0, {%2, %3}], [%1];" ::"l"(m), "r"(src), "r"(c0), "r"(c1) : "memory");
}
__device__ __forceinline__ void bulk_g2s(uint32_t dst, const void* src, uint32_t bytes, uint32_t bar) {
    asm volatile("cp.async.bulk.shared::cluster.global.mbarrier::complete_tx::bytes [%0], [%1], %2, [%3];" ::"r"(dst), "l"(src), "r"(bytes), "r"(bar) : "memory");
}
__device__ __forceinline__ void bulk_prefetch(const void* p, uint32_t bytes) { asm volatile("cp.async.bulk.prefetch.L2.global [%0], %1;" ::"l"(p), "r"(bytes) : "memory"); }
__device__ __forceinline__ void prefetch_map(const CUtensorMap* m) { asm volatile("prefetch.tensormap [%0];" ::"l"(m) : "memory"); }
__device__ __forceinline__ void fence_async_smem() { asm volatile("fence.proxy.async.shared::cta;" ::: "memory"); }
__device__ __forceinline__ void wg_fence() { asm volatile("wgmma.fence.sync.aligned;" ::: "memory"); }
__device__ __forceinline__ void wg_commit() { asm volatile("wgmma.commit_group.sync.aligned;" ::: "memory"); }
template <int N> __device__ __forceinline__ void wg_wait() { asm volatile("wgmma.wait_group.sync.aligned %0;" ::"n"(N) : "memory"); }
__device__ __forceinline__ uint64_t mkdesc(uint32_t lo, uint32_t hi) { return ((uint64_t)hi << 32) | lo; }
__host__ __device__ constexpr uint32_t dhi(uint32_t sbo, uint32_t mode) { return (sbo >> 4) | (mode << 30); }
__host__ __device__ constexpr uint32_t dlo(uint32_t off, uint32_t lbo) { return (off >> 4) + ((lbo >> 4) << 16); }
__device__ __forceinline__ bool elect_one() {
    uint32_t e;
    asm volatile("{\n.reg .pred p;\nelect.sync _|p, 0xffffffff;\nselp.u32 %0, 1, 0, p;\n}" : "=r"(e));
    return e;
}
template <int R> __device__ __forceinline__ void reg_inc() { asm volatile("setmaxnreg.inc.sync.aligned.u32 %0;" ::"n"(R)); }
template <int R> __device__ __forceinline__ void reg_dec() { asm volatile("setmaxnreg.dec.sync.aligned.u32 %0;" ::"n"(R)); }
__device__ __forceinline__ void bar_sync(int id, int n) { asm volatile("bar.sync %0, %1;" ::"r"(id), "r"(n) : "memory"); }
__device__ __forceinline__ void bar_arrive(int id, int n) { asm volatile("bar.arrive %0, %1;" ::"r"(id), "r"(n) : "memory"); }
__device__ __forceinline__ uint32_t pack_bf16(float lo, float hi) { uint32_t r; asm("cvt.rn.bf16x2.f32 %0, %1, %2;" : "=r"(r) : "f"(hi), "f"(lo)); return r; }
__device__ __forceinline__ float bf_lo(uint32_t u) { return __uint_as_float(u << 16); }
__device__ __forceinline__ float bf_hi(uint32_t u) { return __uint_as_float(u & 0xffff0000u); }
__device__ __forceinline__ float bf16r(float v) { return bf_lo(pack_bf16(v, 0.f)); }
__device__ __forceinline__ uint32_t tagw(uint32_t w, uint32_t m, uint32_t tag) { uint32_t r; asm("lop3.b32 %0, %1, %2, %3, 0xb8;" : "=r"(r) : "r"(w), "r"(m), "r"(tag)); return r; }
__device__ __forceinline__ uint32_t tagf(float f, uint32_t tag) { return tagw(__float_as_uint(f), 1u, tag); }
__device__ __forceinline__ uint32_t movm(uint32_t a) { uint32_t d; asm volatile("movmatrix.sync.aligned.m8n8.trans.b16 %0, %1;" : "=r"(d) : "r"(a)); return d; }
__device__ __forceinline__ void mma16816(float (&c)[4], uint32_t a0, uint32_t a1, uint32_t a2, uint32_t a3, uint32_t b0, uint32_t b1) {
    asm volatile("mma.sync.aligned.m16n8k16.row.col.f32.bf16.bf16.f32 {%0,%1,%2,%3}, {%4,%5,%6,%7}, {%8,%9}, {%0,%1,%2,%3};"
                 : "+f"(c[0]), "+f"(c[1]), "+f"(c[2]), "+f"(c[3]) : "r"(a0), "r"(a1), "r"(a2), "r"(a3), "r"(b0), "r"(b1));
}
__device__ __forceinline__ void mma1688(float (&c)[4], uint32_t a0, uint32_t a1, uint32_t b0) {
    asm volatile("mma.sync.aligned.m16n8k8.row.col.f32.bf16.bf16.f32 {%0,%1,%2,%3}, {%4,%5}, {%6}, {%0,%1,%2,%3};"
                 : "+f"(c[0]), "+f"(c[1]), "+f"(c[2]), "+f"(c[3]) : "r"(a0), "r"(a1), "r"(b0));
}
__device__ __forceinline__ uint32_t ld_rlx(const void* p) { uint32_t v; asm volatile("ld.relaxed.gpu.global.u32 %0, [%1];" : "=r"(v) : "l"(p) : "memory"); return v; }
__device__ __forceinline__ uint2 ld_rlx2(const void* p) { uint2 v; asm volatile("ld.relaxed.gpu.global.v2.u32 {%0,%1}, [%2];" : "=r"(v.x), "=r"(v.y) : "l"(p) : "memory"); return v; }
__device__ __forceinline__ uint4 ld_rlx4(const void* p) { uint4 v; asm volatile("ld.relaxed.gpu.global.v4.u32 {%0,%1,%2,%3}, [%4];" : "=r"(v.x), "=r"(v.y), "=r"(v.z), "=r"(v.w) : "l"(p) : "memory"); return v; }
__device__ __forceinline__ void st_rlx(void* p, uint32_t v) { asm volatile("st.relaxed.gpu.global.u32 [%0], %1;" ::"l"(p), "r"(v) : "memory"); }
__device__ __forceinline__ void st_rlx2(void* p, uint32_t a, uint32_t b) { asm volatile("st.relaxed.gpu.global.v2.u32 [%0], {%1,%2};" ::"l"(p), "r"(a), "r"(b) : "memory"); }
__device__ __forceinline__ void st_rlx4(void* p, uint32_t a, uint32_t b, uint32_t c, uint32_t d) { asm volatile("st.relaxed.gpu.global.v4.u32 [%0], {%1,%2,%3,%4};" ::"l"(p), "r"(a), "r"(b), "r"(c), "r"(d) : "memory"); }
__device__ __forceinline__ uint4 ldg_nc(const void* p) { uint4 v; asm volatile("ld.global.nc.v4.u32 {%0,%1,%2,%3}, [%4];" : "=r"(v.x), "=r"(v.y), "=r"(v.z), "=r"(v.w) : "l"(p)); return v; }
__device__ __forceinline__ uint32_t mism(uint32_t a, uint32_t b, uint32_t tag) { uint32_t r; asm("lop3.b32 %0, %1, %2, %3, 0x7e;" : "=r"(r) : "r"(a), "r"(b), "r"(tag)); return r; }
__device__ __forceinline__ uint32_t mism(const uint4& v, uint32_t tag) { return mism(v.x, v.y, tag) | mism(v.z, v.w, tag); }
__device__ __forceinline__ void prefetch_l2(const void* p) { asm volatile("prefetch.global.L2 [%0];" ::"l"(p)); }
__device__ __forceinline__ void nap(int n) {
#pragma unroll 1
    for (int i = 0; i < n; i++) __nanosleep(100);
}
__device__ __forceinline__ uint32_t now() { uint32_t t; asm volatile("mov.u32 %0, %%globaltimer_lo;" : "=r"(t)); return t; }
__device__ __forceinline__ void until(uint32_t t) {
    while (t - now() - 1 < 16384u) __nanosleep(50);
}
__device__ __forceinline__ uint32_t opaque(uint32_t v) { return __shfl_xor_sync(0xffffffffu, v, 0); }
__device__ __forceinline__ void sts4(uint32_t a, uint32_t x, uint32_t y, uint32_t z, uint32_t w) { asm volatile("st.shared.v4.u32 [%0], {%1,%2,%3,%4};" ::"r"(a), "r"(x), "r"(y), "r"(z), "r"(w) : "memory"); }
__device__ __forceinline__ void sts2(uint32_t a, uint32_t x, uint32_t y) { asm volatile("st.shared.v2.u32 [%0], {%1,%2};" ::"r"(a), "r"(x), "r"(y) : "memory"); }
__device__ __forceinline__ uint4 lds4(uint32_t a) { uint4 v; asm volatile("ld.shared.v4.u32 {%0,%1,%2,%3}, [%4];" : "=r"(v.x), "=r"(v.y), "=r"(v.z), "=r"(v.w) : "r"(a) : "memory"); return v; }
__device__ __forceinline__ float4 lds4f(uint32_t a) { float4 v; asm volatile("ld.shared.v4.f32 {%0,%1,%2,%3}, [%4];" : "=f"(v.x), "=f"(v.y), "=f"(v.z), "=f"(v.w) : "r"(a) : "memory"); return v; }
__device__ __forceinline__ uint2 lds2(uint32_t a) { uint2 v; asm volatile("ld.shared.v2.u32 {%0,%1}, [%2];" : "=r"(v.x), "=r"(v.y) : "r"(a) : "memory"); return v; }
__device__ __forceinline__ float2 lds2f(uint32_t a) { float2 v; asm volatile("ld.shared.v2.f32 {%0,%1}, [%2];" : "=f"(v.x), "=f"(v.y) : "r"(a) : "memory"); return v; }
__device__ __forceinline__ uint32_t lds1(uint32_t a) { uint32_t v; asm volatile("ld.shared.u32 %0, [%1];" : "=r"(v) : "r"(a) : "memory"); return v; }
__device__ __forceinline__ float lds1f(uint32_t a) { return __uint_as_float(lds1(a)); }
__device__ __forceinline__ void sts1(uint32_t a, uint32_t v) { asm volatile("st.shared.u32 [%0], %1;" ::"r"(a), "r"(v) : "memory"); }
__device__ __forceinline__ uint32_t redux_max(uint32_t v) { uint32_t r; asm volatile("redux.sync.max.u32 %0, %1, 0xffffffff;" : "=r"(r) : "r"(v)); return r; }
__device__ __forceinline__ float ex2(float x) { float r; asm("ex2.approx.ftz.f32 %0, %1;" : "=f"(r) : "f"(x)); return r; }
__device__ __forceinline__ float rcp(float x) { float r; asm("rcp.approx.ftz.f32 %0, %1;" : "=f"(r) : "f"(x)); return r; }
__device__ __forceinline__ float sigmoidf(float v) { return rcp(1.f + ex2(v * -1.4426950408889634f)); }

template <int TA, int TB>
__device__ __forceinline__ void wgmma_n192(float (&d)[96], uint64_t da, uint64_t db, int acc = 1) {
    asm volatile("{\n.reg .pred p;\nsetp.ne.b32 p, %100, 0;\n"
        "wgmma.mma_async.sync.aligned.m64n192k16.f32.bf16.bf16 "
        "{%0, %1, %2, %3, %4, %5, %6, %7, %8, %9, %10, %11, %12, %13, %14, %15, "
        "%16, %17, %18, %19, %20, %21, %22, %23, %24, %25, %26, %27, %28, %29, %30, %31, "
        "%32, %33, %34, %35, %36, %37, %38, %39, %40, %41, %42, %43, %44, %45, %46, %47, "
        "%48, %49, %50, %51, %52, %53, %54, %55, %56, %57, %58, %59, %60, %61, %62, %63, "
        "%64, %65, %66, %67, %68, %69, %70, %71, %72, %73, %74, %75, %76, %77, %78, %79, "
        "%80, %81, %82, %83, %84, %85, %86, %87, %88, %89, %90, %91, %92, %93, %94, %95}, "
        "%96, %97, p, 1, 1, %98, %99;\n}\n"
        : "+f"(d[0]), "+f"(d[1]), "+f"(d[2]), "+f"(d[3]), "+f"(d[4]), "+f"(d[5]), "+f"(d[6]), "+f"(d[7]),
          "+f"(d[8]), "+f"(d[9]), "+f"(d[10]), "+f"(d[11]), "+f"(d[12]), "+f"(d[13]), "+f"(d[14]), "+f"(d[15]),
          "+f"(d[16]), "+f"(d[17]), "+f"(d[18]), "+f"(d[19]), "+f"(d[20]), "+f"(d[21]), "+f"(d[22]), "+f"(d[23]),
          "+f"(d[24]), "+f"(d[25]), "+f"(d[26]), "+f"(d[27]), "+f"(d[28]), "+f"(d[29]), "+f"(d[30]), "+f"(d[31]),
          "+f"(d[32]), "+f"(d[33]), "+f"(d[34]), "+f"(d[35]), "+f"(d[36]), "+f"(d[37]), "+f"(d[38]), "+f"(d[39]),
          "+f"(d[40]), "+f"(d[41]), "+f"(d[42]), "+f"(d[43]), "+f"(d[44]), "+f"(d[45]), "+f"(d[46]), "+f"(d[47]),
          "+f"(d[48]), "+f"(d[49]), "+f"(d[50]), "+f"(d[51]), "+f"(d[52]), "+f"(d[53]), "+f"(d[54]), "+f"(d[55]),
          "+f"(d[56]), "+f"(d[57]), "+f"(d[58]), "+f"(d[59]), "+f"(d[60]), "+f"(d[61]), "+f"(d[62]), "+f"(d[63]),
          "+f"(d[64]), "+f"(d[65]), "+f"(d[66]), "+f"(d[67]), "+f"(d[68]), "+f"(d[69]), "+f"(d[70]), "+f"(d[71]),
          "+f"(d[72]), "+f"(d[73]), "+f"(d[74]), "+f"(d[75]), "+f"(d[76]), "+f"(d[77]), "+f"(d[78]), "+f"(d[79]),
          "+f"(d[80]), "+f"(d[81]), "+f"(d[82]), "+f"(d[83]), "+f"(d[84]), "+f"(d[85]), "+f"(d[86]), "+f"(d[87]),
          "+f"(d[88]), "+f"(d[89]), "+f"(d[90]), "+f"(d[91]), "+f"(d[92]), "+f"(d[93]), "+f"(d[94]), "+f"(d[95])
        : "l"(da), "l"(db), "n"(TA), "n"(TB), "r"(acc));
}
template <int TA, int TB>
__device__ __forceinline__ void wgmma_n128(float (&d)[64], uint64_t da, uint64_t db, int acc = 1) {
    asm volatile("{\n.reg .pred p;\nsetp.ne.b32 p, %68, 0;\n"
        "wgmma.mma_async.sync.aligned.m64n128k16.f32.bf16.bf16 "
        "{%0, %1, %2, %3, %4, %5, %6, %7, %8, %9, %10, %11, %12, %13, %14, %15, "
        "%16, %17, %18, %19, %20, %21, %22, %23, %24, %25, %26, %27, %28, %29, %30, %31, "
        "%32, %33, %34, %35, %36, %37, %38, %39, %40, %41, %42, %43, %44, %45, %46, %47, "
        "%48, %49, %50, %51, %52, %53, %54, %55, %56, %57, %58, %59, %60, %61, %62, %63}, "
        "%64, %65, p, 1, 1, %66, %67;\n}\n"
        : "+f"(d[0]), "+f"(d[1]), "+f"(d[2]), "+f"(d[3]), "+f"(d[4]), "+f"(d[5]), "+f"(d[6]), "+f"(d[7]),
          "+f"(d[8]), "+f"(d[9]), "+f"(d[10]), "+f"(d[11]), "+f"(d[12]), "+f"(d[13]), "+f"(d[14]), "+f"(d[15]),
          "+f"(d[16]), "+f"(d[17]), "+f"(d[18]), "+f"(d[19]), "+f"(d[20]), "+f"(d[21]), "+f"(d[22]), "+f"(d[23]),
          "+f"(d[24]), "+f"(d[25]), "+f"(d[26]), "+f"(d[27]), "+f"(d[28]), "+f"(d[29]), "+f"(d[30]), "+f"(d[31]),
          "+f"(d[32]), "+f"(d[33]), "+f"(d[34]), "+f"(d[35]), "+f"(d[36]), "+f"(d[37]), "+f"(d[38]), "+f"(d[39]),
          "+f"(d[40]), "+f"(d[41]), "+f"(d[42]), "+f"(d[43]), "+f"(d[44]), "+f"(d[45]), "+f"(d[46]), "+f"(d[47]),
          "+f"(d[48]), "+f"(d[49]), "+f"(d[50]), "+f"(d[51]), "+f"(d[52]), "+f"(d[53]), "+f"(d[54]), "+f"(d[55]),
          "+f"(d[56]), "+f"(d[57]), "+f"(d[58]), "+f"(d[59]), "+f"(d[60]), "+f"(d[61]), "+f"(d[62]), "+f"(d[63])
        : "l"(da), "l"(db), "n"(TA), "n"(TB), "r"(acc));
}
template <int TB>
__device__ __forceinline__ void wgmma_rs_n128(float (&d)[64], uint32_t a0, uint32_t a1, uint32_t a2, uint32_t a3, uint64_t db) {
    asm volatile("{\n.reg .pred p;\nsetp.ne.b32 p, 1, 0;\n"
        "wgmma.mma_async.sync.aligned.m64n128k16.f32.bf16.bf16 "
        "{%0, %1, %2, %3, %4, %5, %6, %7, %8, %9, %10, %11, %12, %13, %14, %15, "
        "%16, %17, %18, %19, %20, %21, %22, %23, %24, %25, %26, %27, %28, %29, %30, %31, "
        "%32, %33, %34, %35, %36, %37, %38, %39, %40, %41, %42, %43, %44, %45, %46, %47, "
        "%48, %49, %50, %51, %52, %53, %54, %55, %56, %57, %58, %59, %60, %61, %62, %63}, "
        "{%64, %65, %66, %67}, %68, p, 1, 1, %69;\n}\n"
        : "+f"(d[0]), "+f"(d[1]), "+f"(d[2]), "+f"(d[3]), "+f"(d[4]), "+f"(d[5]), "+f"(d[6]), "+f"(d[7]),
          "+f"(d[8]), "+f"(d[9]), "+f"(d[10]), "+f"(d[11]), "+f"(d[12]), "+f"(d[13]), "+f"(d[14]), "+f"(d[15]),
          "+f"(d[16]), "+f"(d[17]), "+f"(d[18]), "+f"(d[19]), "+f"(d[20]), "+f"(d[21]), "+f"(d[22]), "+f"(d[23]),
          "+f"(d[24]), "+f"(d[25]), "+f"(d[26]), "+f"(d[27]), "+f"(d[28]), "+f"(d[29]), "+f"(d[30]), "+f"(d[31]),
          "+f"(d[32]), "+f"(d[33]), "+f"(d[34]), "+f"(d[35]), "+f"(d[36]), "+f"(d[37]), "+f"(d[38]), "+f"(d[39]),
          "+f"(d[40]), "+f"(d[41]), "+f"(d[42]), "+f"(d[43]), "+f"(d[44]), "+f"(d[45]), "+f"(d[46]), "+f"(d[47]),
          "+f"(d[48]), "+f"(d[49]), "+f"(d[50]), "+f"(d[51]), "+f"(d[52]), "+f"(d[53]), "+f"(d[54]), "+f"(d[55]),
          "+f"(d[56]), "+f"(d[57]), "+f"(d[58]), "+f"(d[59]), "+f"(d[60]), "+f"(d[61]), "+f"(d[62]), "+f"(d[63])
        : "r"(a0), "r"(a1), "r"(a2), "r"(a3), "l"(db), "n"(TB));
}
template <int TA, int TB>
__device__ __forceinline__ void wgmma_n8(float (&d)[4], uint64_t da, uint64_t db, int acc = 1) {
    asm volatile("{\n.reg .pred p;\nsetp.ne.b32 p, %8, 0;\n"
        "wgmma.mma_async.sync.aligned.m64n8k16.f32.bf16.bf16 "
        "{%0, %1, %2, %3}, "
        "%4, %5, p, 1, 1, %6, %7;\n}\n"
        : "+f"(d[0]), "+f"(d[1]), "+f"(d[2]), "+f"(d[3])
        : "l"(da), "l"(db), "n"(TA), "n"(TB), "r"(acc));
}

__device__ __forceinline__ uint32_t sub2(uint32_t a, uint32_t b) { uint32_t r; asm("sub.rn.bf16x2 %0, %1, %2;" : "=r"(r) : "r"(a), "r"(b)); return r; }

struct Roles { uint16_t v[132]; };

__global__ void __launch_bounds__(512, 1)
fused_kernel(int by_sm, const __nv_bfloat16* __restrict__ x, const __nv_bfloat16* __restrict__ wqkv, const __nv_bfloat16* __restrict__ wr,
             Scratch* const S, const char* __restrict__ wg, const char* __restrict__ wu, const char* __restrict__ wd, const char* __restrict__ wo,
             const __grid_constant__ Roles roles,
             const __grid_constant__ CUtensorMap mw, const __grid_constant__ CUtensorMap mx, const __grid_constant__ CUtensorMap mwo,
             const __grid_constant__ CUtensorMap mxs, const __grid_constant__ CUtensorMap mcs, const __grid_constant__ CUtensorMap mout, const __grid_constant__ CUtensorMap mgu, const __grid_constant__ CUtensorMap mwd) {
    extern __shared__ __align__(1024) uint8_t smem[];
    constexpr uint32_t sb = 1024, bars = sb + OFF_BAR, sd = sb >> 4;
    const int tid = threadIdx.x, lane = tid & 31;
    asm volatile("{\n.reg .pred p, q;\nsetp.lt.u32 p, %2, 16;\nsetp.lt.u32 q, %2, 24;\n@p prefetch.global.L2 [%0];\n@p prefetch.global.L2 [%0 + 128];\n@q prefetch.global.L2 [%1];\n}" ::
                 "l"((const char*)x + (blockIdx.x * 16 + tid - 32) % 2048 * 2048), "l"((const char*)wqkv + (blockIdx.x * 24 + tid - 32) * 128), "r"(tid - 32));
    const int warp = __shfl_sync(0xffffffffu, tid >> 5, 0);
    uint32_t smid;
    asm volatile("mov.u32 %0, %%smid;" : "=r"(smid));
    const int role = roles.v[by_sm ? smid : blockIdx.x], fb = role & 255, b = role >> 8, kc = fb >> 4, c2 = fb & 15;
    const int mt = b >> 4, nt = b & 15, hp = b & 1, cb = nt >> 1;
    const int par = mt >> 2, j0 = (mt & 3) * 256;
    uint8_t* const g_o = S->o;

    auto load_stage = [&](int p, uint32_t so, int bi) {
        const uint32_t fullA = bars + 8 * (B_FULLA + bi), fullB = bars + 8 * (B_FULLB + bi);
        mbar_expect_tx(fullA, 40960);
        tma_3d(sb + so + 16384, &mw, fullA, nt * 64, p * 64, 0);
        tma_4d(sb + so, &mx, fullA, par * 1024 + p * 64, 0, (j0 >> 5) + 4, 0);
        mbar_expect_tx(fullB, 16384);
        tma_4d(sb + so + 40960, &mx, fullB, par * 1024 + p * 64, 0, j0 >> 5, 0);
    };
    if (warp == 0 && fb < 128 && elect_one()) {
        mbar_init(bars + 8 * B_FULLA, 1); mbar_init(bars + 8 * B_FULLB, 1);
        load_stage(0, STAGE, 0);
    }
    if (fb >= 128) {
        if (fb > 128) { nap(16); TS_END(); return; }
        const uint32_t tag = (ld_rlx(&S->epoch) & 1) - 1;
        if (tid < 8) st_rlx2(&S->sel[tid], ~tag, ~tag);
        uint4 ra, rb;
#pragma unroll 1
        for (int it = 0; it < SPIN_LIMIT; it++) {
            ra = ld_rlx4(&S->rec[tid * 2]); rb = ld_rlx4(&S->rec[1024 + tid * 2]);
            if (!__any_sync(0xffffffffu, (mism(ra.x, ra.z, tag) | mism(rb.x, rb.z, tag)) & 0x8000u)) break;
        }
        __syncwarp();
        TSC(tid == 0, 31);
        sts4(sb + 1024 + tid * 16, ra.y, rb.y, ra.w, rb.w);
        uint4 k = make_uint4(ra.x, ra.z, rb.x, rb.z);
        uint32_t cand;
#pragma unroll 1
        for (int pass = 0; pass < 2; pass++) {
            const uint32_t a0 = max(k.x, k.y), a1 = min(k.x, k.y), a2 = max(k.z, k.w), a3 = min(k.z, k.w), c1 = min(a0, a2), c2 = max(a1, a3);
            k = make_uint4(max(a0, a2), max(c1, c2), min(c1, c2), min(a1, a3));
#pragma unroll
            for (int r = 0; r < 8; r++) {
                const uint32_t m = redux_max(k.x);
                if (lane == r) cand = m;
                if (k.x == m) k = make_uint4(k.y, k.z, k.w, 0);
            }
            if (pass) break;
            if (lane < 8) sts1(sb + (warp * 8 + lane) * 4, cand);
            __syncthreads();
            if (warp) { TS_END(); return; }
            k = lds4(sb + lane * 16);
            TSC(TIMING == 12 && tid == 0 && k.x != 0x12345, 40);
        }
        if (lane < 8) st_rlx2(&S->sel[lane], cand, lds1(sb + 1024 + (~cand & 0x7ffu) * 4));
        TSC(tid == 0, 20);
        TS_END();
        return;
    }
    auto ffn_w = [&](int n, int s) {
        const uint32_t dst = sb + OFF_FW + s * 16384;
        if (n < 8) {
            mbar_expect_tx(bars + 8 * (B_FFULL + s), 16384);
            tma_3d_once(dst, &mgu, bars + 8 * (B_FFULL + s), fb * 32, n * 128, 0);
        } else {
            mbar_expect_tx(bars + 8 * B_F2FULL, 16384);
            tma_2d_once(dst, &mwd, bars + 8 * B_F2FULL, c2 * 64, kc * 448 + 64 + s * 128);
            tma_2d_once(dst + 8192, &mwd, bars + 8 * B_F2FULL, c2 * 64, kc * 448 + 128 + s * 128);
        }
    };
    if (warp == 1 && elect_one()) {
#pragma unroll
        for (int i = 0; i < B_FDONE; i++)
            if (i != B_FULLA && i != B_FULLB) mbar_init(bars + 8 * i, i >= B_FFULL && i < B_F2DONE ? 2 : 1);
    }
    if (warp == 4 && elect_one()) {
#pragma unroll
        for (int i = B_EMPTY; i < NBAR; i++) mbar_init(bars + 8 * i, i < B_UPD ? 2 : i < B_AUX ? 4 : i == B_AUX ? 7 : i == B_CSDONE ? 3 : 8);
    }
    if (warp >= 8 && elect_one()) {
#pragma unroll
        for (int i = 0; i < (B_EMPTY - B_FDONE) / 8; i++) mbar_init(bars + 8 * (B_FDONE + 8 * i - 8 + warp), 1);
    }
    uint32_t epoch;
    if (warp >> 2 == 2) epoch = ld_rlx(&S->epoch);
    __syncthreads();

    if (warp >= 12) {
        reg_dec<24>();
        if (warp > 12) {
            const int p = warp - 13;
            if (p == 1) {
                float sw = 0.f;
                mbar_wait(bars + 8 * (B_ROW + 4), 0);
#pragma unroll 1
                for (int i = 0; i < 16; i++) { const uint32_t q = lds1(sb + OFF_FA + i * 128 + lane * 4); sw += bf_lo(q) + bf_hi(q); }
#pragma unroll 1
                for (int o = 1; o < 32; o <<= 1) sw += __shfl_xor_sync(0xffffffffu, sw, o);
                if (lane == 0) { sts1(sb + OFF_TAG + 4, __float_as_uint(sw)); mbar_arrive(bars + 8 * B_SW); }
            } else {
#pragma unroll 1
                for (int q = 0; q < 4; q++) {
                    nap(p ? (q ? D_R : N_ROW) : (q ? D_X : N_X));
                    if (p == 0) {
                        const __nv_bfloat16* xp = x + (size_t)((j0 + nt * 16 + (lane >> 1)) * 2 + par) * 1024 + q * 256 + (lane & 1) * 64;
                        prefetch_l2(xp); prefetch_l2(xp + 128);
                    } else if (elect_one()) {
                        mbar_expect_tx(bars + 8 * (B_ROW + q), 8192);
                        tma_3d(sb + OFF_FW + q * 8192, &mxs, bars + 8 * (B_ROW + q), 0, j0 + nt * 16, par * 16 + q * 4);
                    }
                }
                if (p == 0) nap(N_CS);
            }
            const uint32_t stg = sb + OFF_FW + 32768 + p * 4096 + lane * 16;
            float c[8];
#pragma unroll
            for (int i = 0; i < 8; i++) c[i] = 0.f;
#pragma unroll 1
            for (int n = 0; n < 10; n++) {
                const uint32_t bo = (n & 1) * 2048, bar = bars + 8 * (B_CS + 2 * p + (n & 1));
                if (n >= 2) {
                    mbar_wait(bar, ~(n >> 1) & 1);
#pragma unroll 2
                    for (int i = 0; i < 4; i++) {
                        const uint4 v = lds4(stg + bo + i * 512);
                        c[0] += bf_lo(v.x); c[1] += bf_hi(v.x); c[2] += bf_lo(v.y); c[3] += bf_hi(v.y);
                        c[4] += bf_lo(v.z); c[5] += bf_hi(v.z); c[6] += bf_lo(v.w); c[7] += bf_hi(v.w);
                    }
                    asm volatile("" :: "f"(c[7]));
                    __syncwarp();
                }
                if (n < 8 && elect_one()) {
                    mbar_expect_tx(bar, 2048);
                    tma_3d(sb + OFF_FW + 32768 + p * 4096 + bo, &mcs, bar, p * 1024 + nt * 64, mt * 8, 2 * n);
                }
            }
            sts4(stg + lane * 16, __float_as_uint(c[0]), __float_as_uint(c[1]), __float_as_uint(c[2]), __float_as_uint(c[3]));
            sts4(stg + lane * 16 + 16, __float_as_uint(c[4]), __float_as_uint(c[5]), __float_as_uint(c[6]), __float_as_uint(c[7]));
            bar_sync(13, 128);
            const uint32_t tag = lds1(sb + OFF_TAG);
            float* gcs = &S->cs[0][p * 1024 + nt * 64];
            {
                const float2 a0 = lds2f(stg - lane * 8), a1 = lds2f(stg - lane * 8 + 256), a2 = lds2f(stg - lane * 8 + 512), a3 = lds2f(stg - lane * 8 + 768);
                st_rlx2(gcs + mt * 3072 + lane * 2, tagf((a0.x + a1.x) + (a2.x + a3.x), tag), __float_as_uint((a0.y + a1.y) + (a2.y + a3.y)));
            }
            fence_async_smem();
            __syncwarp();
            if (lane == 0) mbar_arrive(bars + 8 * B_CSDONE);
            TSC(warp == 13 && lane == 0, 19);
            {
                uint4 v[4];
                const float* src = gcs + (lane >> 4) * 4 * 3072 + (lane & 15) * 4;
#pragma unroll 1
                for (int it = 0; it < SPIN_LIMIT; it++) {
#pragma unroll
                    for (int m = 0; m < 4; m++) v[m] = ld_rlx4(src + m * 3072);
                    if (!__any_sync(0xffffffffu, (mism(v[0].x, v[1].x, tag) | mism(v[2].x, v[3].x, tag)) & 1)) break;
                }
                __syncwarp();
#pragma unroll
                for (int c = 0; c < 4; c++) {
                    const float a = (__uint_as_float((&v[0].x)[c]) + __uint_as_float((&v[1].x)[c])) + (__uint_as_float((&v[2].x)[c]) + __uint_as_float((&v[3].x)[c]));
                    (&v[0].x)[c] = __float_as_uint(a + __shfl_xor_sync(0xffffffffu, a, 16));
                }
                const uint32_t ca = sb + OFF_CS + p * 384 + ((lane & 15) >> 1) * 48 + (lane & 1) * 8;
#pragma unroll 1
                for (int r = 0; r < 3; r++) {
                    const uint32_t u0 = pack_bf16(__uint_as_float(v[0].x), __uint_as_float(v[0].y)), u1 = pack_bf16(__uint_as_float(v[0].z), __uint_as_float(v[0].w));
                    sts2(ca + r * 16, u0, u1);
                    v[0].x = __float_as_uint(__uint_as_float(v[0].x) - bf_lo(u0)); v[0].y = __float_as_uint(__uint_as_float(v[0].y) - bf_hi(u0));
                    v[0].z = __float_as_uint(__uint_as_float(v[0].z) - bf_lo(u1)); v[0].w = __float_as_uint(__uint_as_float(v[0].w) - bf_hi(u1));
                }
                if (lane < 20) sts1(sb + OFF_CS + 1152 + lane * 4, 0);
                fence_async_smem();
            }
            if (p == 1) { if (lane < 2) st_rlx4(&S->hint[b][lane * 4], ~tag, ~tag, ~tag, ~tag); }
            else { st_rlx4(&S->halo[b][p * 128 + lane * 4], ~tag, ~tag, ~tag, ~tag); st_rlx4(&S->halo[b][p * 128 + 128 + lane * 4], ~tag, ~tag, ~tag, ~tag); }
            __syncwarp();
            if (lane == 0) mbar_arrive(bars + 8 * B_AUX);
            TSC(warp == 13 && lane == 0, 21);
            mbar_wait(bars + 8 * B_PART, 0);
            if (p == 0 || !EARLY_HINT) mbar_wait(bars + 8 * (B_EMPTY + 2), 0);
            if (p == 0) {
                if (j0) {
                    nap(N_HA);
#pragma unroll 1
                    for (int it = 0; it < SPIN_LIMIT; it++) {
                        TSC(TIMING == 15 && lane == 0 && it < 8, 40 + it);
                        if (elect_one()) { mbar_expect_tx(bars + 8 * B_CS, 2048); bulk_g2s(sb + OFF_HALO, S->halo[b - 16], 2048, bars + 8 * B_CS); }
                        mbar_wait(bars + 8 * B_CS, it & 1);
                        const uint32_t a = sb + OFF_HALO + lane * 16;
                        if (!__any_sync(0xffffffffu, (mism(lds1(a), lds1(a + 512), tag) | mism(lds1(a + 1024), lds1(a + 1536), tag)) & 1)) break;
                    }
                } else {
#pragma unroll
                    for (int c = 0; c < 4; c++) sts4(sb + OFF_HALO + c * 512 + lane * 16, 0, 0, 0, 0);
                }
                __syncwarp();
                bar_arrive(3, 64);
                TSC(TIMING >= 11 && lane == 0, 34);
            } else {
                const int w = p - 1;
                const uint8_t* osrc = g_o + (size_t)((mt * 2 + hp) * 2 + w) * 131072;
                const bool far = w > hp && j0 && lane >= 16;
                const uint32_t* hsrc = &S->hint[b & 0x70][0] + ((lane & 15) - (far ? 16 : 0)) * 8;
                if (lane == 0 && !w) st_rlx(&S->hint[b][0], tagw(now(), 1u, tag));
                uint32_t hv;
#pragma unroll 1
                for (int it = 0; it < SPIN_LIMIT; it++) {
                    hv = ld_rlx(hsrc);
                    if (!__any_sync(0xffffffffu, (hv ^ tag) & 1)) break;
                }
                TSC(TIMING == 11 && lane == 0, 32 + w);
                const uint32_t tn = __shfl_sync(0xffffffffu, hv, 0) - 0x40000000u;
                hv = redux_max(hv - tn + (far ? T_H : 0)) + tn + T_O + EARLY_HINT + w * T_O1;
                mbar_wait(bars + 8 * (w ? B_AST : B_G1DONE), 0);
                if (elect_one()) {
#pragma unroll 1
                    for (int st = 0; st < 8; st++) {
                        const uint32_t full = bars + 8 * (B_OFULL + 8 * w + st);
                        if (st >= 2) mbar_wait(full + 8 * (B_DONE - B_OFULL - 2), 0);
                        if (st < 3) until(hv + (st == 2 ? T_S2 : st * T_S1));
                        TSC(st == 0, 28 + w);
                        mbar_expect_tx(full, 16384);
                        bulk_g2s(sb + (w ? OFF_O1 : OFF_O0) + (st & 1) * 16384, osrc + st * 16384, 16384, full);
                    }
                }
            }
            TS_END();
            return;
        }
        if (elect_one()) {
            auto load_wo = [&](int s, uint32_t ws) {
                mbar_expect_tx(bars + 8 * (B_WOFULL + s), 32768);
                tma_4d(ws, &mwo, bars + 8 * (B_WOFULL + s), 0, s * 8, 0, cb * 2);
            };
            uint32_t so = 2 * STAGE, ph = 1, cnt = PF_CNT << 4;
            int bi = 1, q = 0;
            mbar_expect_tx(bars + 8 * (B_ROW + 4), 2048);
            bulk_g2s(sb + OFF_FA, wr, 2048, bars + 8 * (B_ROW + 4));
            if (smem_u32(smem) != sb) __trap();
            if (PFM & 1) { prefetch_map(&mxs); prefetch_map(&mcs); }
            if (PFM & 2) { prefetch_map(&mgu); prefetch_map(&mwd); prefetch_map(&mwo); prefetch_map(&mout); }
            const char* pf = (b < 64 ? wg : wu) + (b & 63) * 7168;
#pragma unroll 1
            for (int p = 1; p < 16; p++) {
                if (p < 3) nap(p == 1 ? N_S1 : N_S2);
                mbar_wait(bars + 8 * (B_EMPTY + bi), ph);
                load_stage(p, so, bi);
                if (p >= 2 && p < 5) {
                    const int k0 = p == 2 ? 3 : p == 3 ? K_W1 : K_W2, n = ((p == 2 ? K_W1 : p == 3 ? K_W2 : 16) - k0) * 3072;
                    if (p == 2) nap(N_W);
                    bulk_prefetch((const char*)wqkv + k0 * 393216 + b * n, n);
                }
#pragma unroll 1
                for (int e = q + (cnt & 3); q < e; q++) {
                    if (q == 16) pf = wd + mt * 7 * 131072 + nt * 8192;
                    if (q == 23) pf = wo + b * 8192;
                    bulk_prefetch(pf, q < 16 ? 7168 : 8192);
                    pf += q < 16 ? 64 * 7168 : q < 23 ? 131072 : 1048576;
                }
                cnt >>= 2;
                so = so == 2 * STAGE ? 0 : so + STAGE;
                if (++bi == 3) { bi = 0; ph ^= 1; }
            }
            TS(27);
            if (PFM & 8) { prefetch_map(&mwo); }
            uint32_t ws = sb + OFF_WO0;
#pragma unroll 1
            for (int i = 0; i < 8; i++) {
                if (i < 2) {
                    mbar_wait(bars + 8 * (B_EMPTY + 1 + i), 0);
                    mbar_expect_tx(bars + 8 * B_XR, 16384);
                    tma_4d(sb + (i ? 0 : OFF_X1), &mx, bars + 8 * B_XR, par * 1024 + cb * 128 + 64 - i * 64, 0, (j0 >> 5) + hp * 4, 0);
                }
                if (i == 1) {
                    mbar_expect_tx(bars + 8 * B_F2FULL, 8192);
                    tma_2d_once(sb + OFF_F2X, &mwd, bars + 8 * B_F2FULL, c2 * 64, kc * 448);
                }
                if (i) {
                    mbar_wait(bars + 8 * (i == 1 ? B_G1DONE : i == 2 ? B_F2DONE : B_DONE - NWO + i), 0);
                    if (i > 1) mbar_wait(bars + 8 * (i == 2 ? B_OFULL + 8 : B_DONE + 8 - NWO + i), 0);
                }
                load_wo(i, ws);
                if ((PFM & 4) && i == 4) prefetch_map(&mout);
                ws = wo_next(ws, sb, 0);
            }
        }
        TS_END();
    } else if (warp >= 8) {
        reg_dec<40>();
        const int p = warp - 8;
        const bool f1 = fb < 112;
        const uint32_t tag = (epoch & 1) - 1;
        {
            const int ta = tid - 256;
            if (ta < 48) st_rlx4(&S->cs[mt][(ta >> 4) * 1024 + nt * 64 + (ta & 15) * 4], ~tag, ~tag, ~tag, ~tag);
        }
        float s1 = 0.f, s2 = 0.f, sr = 0.f, sw, sh = 0.f;
        {
            const uint32_t xa = sb + OFF_FW + p * 512 + lane * 16, wa = sb + OFF_FA + (((p * 4 + (lane >> 3)) ^ lane) & 7) * 16;
            TSC(TIMING == 12 && lane == 0, 50 + p);
            mbar_wait(bars + 8 * (B_ROW + 4), 0);
            {
                float c1 = 0.f, c2 = 0.f, cr = 0.f;
#pragma unroll 1
                for (int q = 0; q < 4; q++) {
                mbar_wait(bars + 8 * (B_ROW + q), 0);
                TSC(TIMING == 12 && tid == 256 + 96, 32 + q);
                TSC(tid == 256 && q == 3, 17);
#pragma unroll
                for (int i = 0; i < 4; i++) {
                    const uint4 u = lds4(xa + q * 8192 + i * 2048), w4 = lds4(wa + q * 512 + i * 128);
                    const float a0 = bf_lo(u.x), a1 = bf_hi(u.x), a2 = bf_lo(u.y), a3 = bf_hi(u.y), a4 = bf_lo(u.z), a5 = bf_hi(u.z), a6 = bf_lo(u.w), a7 = bf_hi(u.w);
                    s1 += a0 + a1; c1 += a4 + a5; s1 += a2 + a3; c1 += a6 + a7;
                    s2 = fmaf(a0, a0, s2); c2 = fmaf(a4, a4, c2); sr = fmaf(a0, bf_lo(w4.x), sr); cr = fmaf(a4, bf_lo(w4.z), cr);
                    s2 = fmaf(a1, a1, s2); c2 = fmaf(a5, a5, c2); sr = fmaf(a1, bf_hi(w4.x), sr); cr = fmaf(a5, bf_hi(w4.z), cr);
                    s2 = fmaf(a2, a2, s2); c2 = fmaf(a6, a6, c2); sr = fmaf(a2, bf_lo(w4.y), sr); cr = fmaf(a6, bf_lo(w4.w), cr);
                    s2 = fmaf(a3, a3, s2); c2 = fmaf(a7, a7, c2); sr = fmaf(a3, bf_hi(w4.y), sr); cr = fmaf(a7, bf_hi(w4.w), cr);
                }
                }
                s1 += c1; s2 += c2; sr += cr;
            }
            mbar_wait(bars + 8 * B_SW, 0);
            sw = lds1f(sb + OFF_TAG + 4);
#pragma unroll 1
            for (int pass = 0;; pass++) {
#pragma unroll
                for (int o = 1; o < 8; o <<= 1) {
                    s1 += __shfl_xor_sync(0xffffffffu, s1, o); s2 += __shfl_xor_sync(0xffffffffu, s2, o); sr += __shfl_xor_sync(0xffffffffu, sr, o);
                }
                s1 *= 1.f / 1024.f;
                s2 = fmaf(-s1, s1, s2 * (1.f / 1024.f));
                if (!__any_sync(0xffffffffu, !pass && s1 * s1 > 256.f * s2)) break;
                sh = bf16r(s1); s1 = 0.f; s2 = 0.f; sr = 0.f;
#pragma unroll 1
                for (uint32_t o = 0; o < 2048; o = opaque(o + ((o & 12) == 12 ? 116 : 4))) {
                    const uint32_t u = lds1(xa + (o >> 7) * 2048 + (o & 12)), q = lds1(wa + o);
                    const float a0 = bf_lo(u) - sh, a1 = bf_hi(u) - sh;
                    s1 += a0 + a1; s2 = fmaf(a0, a0, fmaf(a1, a1, s2)); sr = fmaf(a0, bf_lo(q), fmaf(a1, bf_hi(q), sr));
                }
            }
        }
        const int ta = opaque(tid) - 256, lane = ta & 31, g = lane >> 2, t = lane & 3;
        {
            if ((lane & 7) == 0) {
                const int s = b * 16 + p * 4 + (lane >> 3);
                const float mb = bf16r(sh + s1);
                float den;
                asm("sqrt.approx.f32 %0, %1;" : "=f"(den) : "f"(bf16r(bf16r(s2) + 1e-5f)));
                den = bf16r(den);
                uint32_t rb = pack_bf16(fmaf(sh - mb, sw, sr) * rcp(den), 0.f);
                if (rb == 0x8000u) rb = 0;
                uint32_t ord = (rb & 0x8000u) ? (~rb & 0xffffu) : (rb | 0x8000u);
                if ((rb & 0x7fffu) > 0x7f80u) ord = 0;
                st_rlx2(&S->rec[s], (ord << 16) | (tag & 0x8000u) | (0x47ffu - (s & 1023) * 2 - par), pack_bf16(mb, den));
            }
            TSC(TIMING == 12 && lane == 0, 36 + p);
            bar_sync(12, 128);
            if (p == 1) sts1(sb + OFF_ROWMAP + lane * 4, 0xffffffffu);
            if (p == 0) {
                if (lane == 0) {
                    sts1(sb + OFF_TAG, tag);
                }
                __syncwarp();
                bar_arrive(13, 128);
            }
            TSC(ta == 0, 18);
        }
        {
            uint2 r[3];
            nap(N_GA);
            const uint2* src = &S->rec[mt * 256 + ta];
            const int l2 = ta < 8 && j0 ? -8 : 0;
#pragma unroll 1
            for (int it = 0; it < SPIN_LIMIT; it++) {
                r[0] = ld_rlx2(src + l2); r[1] = ld_rlx2(src); r[2] = ld_rlx2(src + 128);
                if (!__any_sync(0xffffffffu, (mism(r[0].x, r[1].x, tag) | (r[2].x ^ tag)) & 0x8000u)) break;
            }
#pragma unroll
            for (int n = 0; n < 3; n++)
                if (n || ta < 8) sts2(sb + OFF_STAT + (n ? n * 1024 - 960 : 0) + ta * 8, (r[n].y << 16) ^ 0x80000000u, __float_as_uint(rcp(bf_hi(r[n].y))));
        }
        __syncwarp();
        if (lane == 0) mbar_arrive(bars + 8 * B_AUX);
        TSC(ta == 0, 30);
        if (p == 1) nap(N_F1);
        if (f1 && p < 2 && elect_one()) ffn_w(p, p);
        uint2 sel;
#pragma unroll 1
        for (int it = 0; it < SPIN_LIMIT; it++) {
            sel = ld_rlx2(&S->sel[lane & 7]);
            if (!__any_sync(0xffffffffu, (sel.x ^ tag) & 0x8000u)) break;
            __nanosleep(POLL_NS);
        }
        TSC(ta == 0, 26);
        if (b == 0 && ta == 0) st_rlx(&S->epoch, epoch + 1);
        {
            const __nv_bfloat16* xp = x + (~sel.x & 0x7ffu) * 1024 + (lane >> 3) * 8;
            const uint32_t mb = __byte_perm(sel.y, 0, 0x1010);
            if (p >= 2) nap(N_A2);
#pragma unroll 1
            for (int n = p; n < (f1 ? 8 : 0); n += 4) {
                uint4 v[4];
#pragma unroll
                for (int c = 0; c < 4; c++) v[c] = ldg_nc(xp + n * 128 + c * 32);
                const int s = n % 3;
                if (n >= 2) {
                    mbar_wait(bars + 8 * (n == 2 ? B_CSDONE : B_FDONE + n - 3), 0);
                    if (elect_one()) ffn_w(n & 7, s);
                }
#pragma unroll
                for (int c = 0; c < 4; c++) sts4(sb + OFF_FA + s * 2048 + c * 512 + lane * 16, sub2(v[c].x, mb), sub2(v[c].y, mb), sub2(v[c].z, mb), sub2(v[c].w, mb));
                fence_async_smem();
                __syncwarp();
                if (lane == 0) mbar_arrive(bars + 8 * (B_FFULL + s));
                TSC(TIMING == 12 && lane == 0, 41 + n);
            }
            if (p < 3) {
                mbar_wait(bars + 8 * B_CSDONE, 0);
                mbar_wait(bars + 8 * (f1 ? B_FDONE + 5 + p : B_PART), 0);
                if (elect_one()) ffn_w(8, p ? p - 1 : 2);
            }
        }
        const bool hw = f1 && (p == 0 || p == 3);
        if (hw) st_rlx4(&S->h[fb * 128 + (p & 1) * 64 + (lane & 15) * 4], ~tag, ~tag, ~tag, ~tag);
        st_rlx4(&S->ypart[kc][ta >> 4][c2 * 64 + (ta & 15) * 4], ~tag, ~tag, ~tag, ~tag);
        const float ri[2] = {rcp(bf_hi(__shfl_sync(0xffffffffu, sel.y, 2 * t))), rcp(bf_hi(__shfl_sync(0xffffffffu, sel.y, 2 * t + 1)))};
        mbar_wait(bars + 8 * B_PART, 0);
        if (hw) {
            const uint32_t pa = sb + OFF_FA + (ta & 63) * 16, go = wu < wg ? 1024 : 0;
            const float4 g0 = lds4f(pa + go), g1 = lds4f(pa + 2048 + go), u0 = lds4f(pa + (go ^ 1024)), u1 = lds4f(pa + 2048 + (go ^ 1024));
            float hv[4];
#pragma unroll
            for (int c = 0; c < 4; c++) {
                const float ga = bf16r(((&g0.x)[c] + (&g1.x)[c]) * ri[c & 1]), up = bf16r(((&u0.x)[c] + (&u1.x)[c]) * ri[c & 1]);
                hv[c] = bf16r(ga * sigmoidf(ga)) * up;
            }
#pragma unroll
            for (int hh = 0; hh < 2; hh++) {
                const float o = __shfl_xor_sync(0xffffffffu, (g & 1) ? hv[2 * hh] : hv[2 * hh + 1], 4);
                st_rlx(&S->h[(fb * 4 + (p & 1) * 2 + hh) * 32 + (2 * t + (g & 1)) * 4 + (g >> 1)],
                       tagw((g & 1) ? pack_bf16(o, hv[2 * hh + 1]) : pack_bf16(hv[2 * hh], o), g < 2, tag));
            }
            TSC(ta == 0, 22);
        }
        {
            uint4 hq[4];
            const uint32_t* hp4 = S->h + kc * 1792 + ta * 4;
#pragma unroll 1
            for (int it = 0; it < SPIN_LIMIT; it++) {
#pragma unroll
                for (int n = 0; n < 4; n++) hq[n] = ld_rlx4(hp4 + (n < 3 ? n * 512 : p < 2 ? 1536 : 0));
                if (!__any_sync(0xffffffffu, (mism(hq[0].x, hq[1].x, tag) | mism(hq[2].x, hq[3].x, tag)) & 1)) break;
            }
            mbar_wait(bars + 8 * B_G1DONE, 0);
            bar_sync(12, 128);
#pragma unroll
            for (int n = 0; n < 4; n++) sts4(sb + OFF_FA + ta * 16 + (n < 3 ? n * 2048 : p < 2 ? 6144 : 0), hq[n].x, hq[n].y, hq[n].z, hq[n].w);
            fence_async_smem();
            bar_sync(12, 128);
            TSC(ta == 0, 25);
            mbar_wait(bars + 8 * B_F2FULL, 0);
            mbar_wait(bars + 8 * B_ATT, 0);
            float acc[4] = {0.f, 0.f, 0.f, 0.f};
            uint32_t da = sd + dlo(OFF_F2X, 8192), db = sd + dlo(OFF_FA, 128);
#pragma unroll 1
            for (int q = 0; q < 7; q++) {
                wg_fence();
#pragma unroll
                for (int j = 0; j < 4; j++) wgmma_n8<1, 0>(acc, mkdesc(da + j * 128, dhi(1024, 1)), mkdesc(db + j * 16, dhi(128, 0)));
                wg_commit();
                da = sd + dlo(OFF_FW, 8192) + q * 512; db += 64;
            }
            wg_wait<0>();
            if (ta == 0) mbar_arrive(bars + 8 * B_F2DONE);
#pragma unroll
            for (int c = 0; c < 4; c++) st_rlx(&S->ypart[kc][2 * t + (c & 1)][c2 * 64 + p * 16 + (c >> 1) * 8 + g], tagf(acc[c], tag));
            TSC(ta == 0, 23);
            bar_sync(12, 128);
        }
#pragma unroll 1
        for (int j = 2 * p; j < 2 * p + 2; j++) {
            const uint32_t kj = __shfl_sync(0xffffffffu, sel.x, j);
            const int row = 0x7ff - (kj & 0x7ffu), jj = (row >> 1) - j0 - hp * 128;
            float a0 = 0.f, a1 = 0.f, a2 = 0.f, a3 = 0.f, sig = 0.f;
            if ((row & 1) == par && jj >= 0 && jj < 128) {
                sig = bf16r(sigmoidf(__uint_as_float(((int)kj < 0 ? kj ^ 0x80000000u : ~kj) & 0xffff0000u)));
#pragma unroll 1
                for (int hh = 0; hh < 8; hh += 4) {
                    uint4 v[4];
#pragma unroll 1
                    for (int it = 0; it < SPIN_LIMIT; it++) {
#pragma unroll
                        for (int m = 0; m < 4; m++) v[m] = ld_rlx4(&S->ypart[hh + m][j][cb * 128 + lane * 4]);
                        if (!__any_sync(0xffffffffu, (mism(v[0], tag) | mism(v[1], tag) | mism(v[2], tag) | mism(v[3], tag)) & 1)) break;
                    }
#pragma unroll
                    for (int m = 0; m < 4; m++) { a0 += __uint_as_float(v[m].x); a1 += __uint_as_float(v[m].y); a2 += __uint_as_float(v[m].z); a3 += __uint_as_float(v[m].w); }
                }
                asm volatile("st.shared.u8 [%0], %1;" ::"r"(sb + OFF_ROWMAP + jj), "r"(j) : "memory");
            }
            sts2(sb + OFF_FA + (lane >> 1) * 128 + j * 16 + (lane & 1) * 8, pack_bf16(bf16r(a0) * sig, bf16r(a1) * sig), pack_bf16(bf16r(a2) * sig, bf16r(a3) * sig));
        }
        fence_async_smem();
        __syncwarp();
        if (lane == 0) mbar_arrive(bars + 8 * B_UPD);
        TSC(ta == 0, 24);
        TS_END();
    } else {
        reg_inc<224>();
        const int w = warp >> 2, wi = warp & 3, tw = (1 - w) * 4 + wi;
        const bool elect = (tid & 127) == 0;
        const uint32_t ln = opaque(lane), g = ln >> 2, t = ln & 3;
        uint32_t tag, ow[8][4];
        auto store_o = [&](int f0, int f1) {
            uint8_t* ob = g_o + (size_t)((mt * 2 + 1 - w) * 2 + 1 - (wi >> 1)) * 131072 + nt * 1024 + (wi & 1) * 512 + ln * 4;
#pragma unroll
            for (int f = f0; f < f1; f++)
#pragma unroll
                for (int i = 3; i >= 0; i--)
                    st_rlx(ob + f * 16384 + i * 128, ow[f][i]);
        };
        {
            float acc[2][96];
            const uint32_t sta = opaque(sb + OFF_STAT + tw * 256 + 64 + g * 8);
            {
                float fa[4] = {0.f, 0.f, 0.f, 0.f};
                uint32_t so = STAGE >> 4, bo = bars, ph = 0;
                const uint32_t dx0 = sd + dlo(w ? 40960 : 0, 16), dw0 = sd + dlo(16384, 8192);
                int p = 0;
                if (w) bar_arrive(1, 256);
                uint32_t fm = fb < 112 ? F1_MASK >> (16 * w) : 0u, fph = 0, fd = bars + 8 * (B_FDONE + w);
                int fs = w;
#pragma unroll 1
                for (; p < 16; p++) {
                    mbar_wait(bo + 8 * B_FULLA, ph);
                    if (w) mbar_wait(bo + 8 * B_FULLB, ph);
                    TSC(elect && p == 0, 1 + 8 * w);
                    TSC(TIMING == 9 && elect && p >= 9 && p < 14, 32 + (p - 9) * 6 + w * 3);
                    bar_sync(1 + w, 256);
                    TSC(TIMING == 1 && tid == 0, 32 + p);
                    if (p == 15) {
                        wg_fence();
                        wgmma_n192<0, 1>(acc[1], mkdesc(sd + dlo(OFF_MEAN + 1024, 0) + w * 128, dhi(128, 0)), mkdesc(sd + dlo(OFF_CS, 0), dhi(48, 0)));
                        wgmma_n192<0, 1>(acc[0], mkdesc(sd + dlo(OFF_MEAN, 0) + w * 128, dhi(128, 0)), mkdesc(sd + dlo(OFF_CS, 0), dhi(48, 0)));
                        wg_commit();
                    }
                    wg_fence();
#pragma unroll
                    for (int h = 1; h >= 0; h--) {
#pragma unroll
                        for (int k = 0; k < 4; k++) wgmma_n192<0, 1>(acc[h], mkdesc(dx0 + so + h * 512 + k * 2, dhi(1024, 1)), mkdesc(dw0 + so + k * 128, dhi(1024, 1)), k ? 1 : p);
                        wg_commit();
                    }
                    if (fm & 1) {
                        mbar_wait(bars + 8 * (B_FFULL + fs), fph);
                        TSC(TIMING == 9 && elect && p >= 9, 33 + (p - 9) * 6 + w * 3);
                        wg_fence();
#pragma unroll
                        for (int j = 0; j < 8; j++)
                            wgmma_n8<1, 0>(fa, mkdesc(sd + dlo(OFF_FW, 8192) + fs * 1024 + j * 64, dhi(512, 2)), mkdesc(sd + dlo(OFF_FA, 128) + fs * 128 + j * 16, dhi(128, 0)));
                        wg_commit();
                    }
                    bar_arrive(2 - w, 256);
                    if (p == 15) break;
                    wg_wait<0>();
                    TSC(TIMING == 9 && elect && p >= 9 && p < 14, 34 + (p - 9) * 6 + w * 3);
                    if (wi == 0 && elect_one()) { mbar_arrive(bo + 8 * B_EMPTY); if (fm & 1) mbar_arrive(fd); }
                    so = so == 2 * (STAGE >> 4) ? 0 : so + (STAGE >> 4);
                    bo += 8;
                    if (bo == bars + 24) { bo = bars; ph ^= 1; }
                    if (fm & 1) { fd += 16; fs += 2; if (fs >= 3) { fs -= 3; fph ^= 1; } }
                    fm >>= 1;
                    if (p == P_PART) {
                        if (fb < 112) sts4(sb + OFF_FA + tid * 16, __float_as_uint(fa[0]), __float_as_uint(fa[1]), __float_as_uint(fa[2]), __float_as_uint(fa[3]));
                        __syncwarp();
                        if (lane == 0) mbar_arrive(bars + 8 * B_PART);
                    }
                    if (p != 14) continue;
                    mbar_wait(bars + 8 * B_AUX, 0);
                    mbar_wait(bars + 8 * (B_EMPTY + 1), 0);
                    const uint32_t hm = __float_as_uint(0.5f * lds1f(sb + OFF_STAT + 64 + tw * 256 + ln * 8)) >> 16;
                    sts4(sb + OFF_MEAN + w * 2048 + wi * 256 + (ln >> 4) * 1024 + (ln & 15) * 16, hm * 0x10001u, hm, 0, 0);
                    fence_async_smem();
                }
            }
            TSC(TIMING != 14 && elect, 2 + 8 * w);

            tag = lds1(sb + OFF_TAG);
            mbar_wait(bars + 8 * (B_EMPTY + 2), 0);
            wg_wait<1>();
#pragma unroll
            for (int i = 0; i < 96; i++) asm volatile("" : "+f"(acc[1][i]) :: "memory");
            uint32_t pk[4][24];
            const uint32_t hm = tw == 7 ? ~ln & 1 : 0;
            auto np = [&](int i, int j) {
                const float* a = &acc[i >> 1][4 * j + 2 * (i & 1)];
                pk[i][j] = pack_bf16(a[0], a[1]);
                if (j >= 16) pk[i][j] = movm(pk[i][j]);
                if (i == 3 && j >= 8 && !(j & 1)) pk[i][j] = tagw(pk[i][j], hm, tag);
            };
            const uint32_t ha = sb + OFF_HALO + tw * 2048 + ln * 8;
#pragma unroll
            for (int j = 8; j < 24; j += 2) {
                np(3, j); np(3, j + 1);
                sts2(ha + 2048 + (j - 8) * 128, pk[3][j], pk[3][j + 1]);
                asm volatile("{\n.reg .pred p;\nsetp.eq.u32 p, %3, 7;\n@p st.relaxed.gpu.global.v2.u32 [%0], {%1,%2};\n}" ::"l"((char*)&S->halo[b][ln * 2] + (j - 8) * 128),
                             "r"(pk[3][j]), "r"(pk[3][j + 1]), "r"(tw) : "memory");
            }
            bar_arrive(4 + tw, 64);
            TSC(TIMING == 15 && ln == 0 && tw == 7, 39);
            TSC(TIMING == 8 && ln == 0 && wi == 1, 32 + 8 * w);
            const bool u0 = 2 * t > g, u1 = 2 * t + 1 > g;
            const uint32_t mU = (u0 ? 0xffffu : 0u) | (u1 ? 0xffff0000u : 0u);
            uint2 hl[8];
            float rk[4][2], fq[4][2];
            auto factors = [&]() {
                const uint32_t ka = sb + OFF_STAT + tw * 256 + 4 + t * 16, k0 = opaque(ka + (u0 ? 0 : 64)), k1 = opaque(ka + (u1 ? 8 : 72));
#pragma unroll
                for (int i = 0; i < 4; i++) {
                    const float rq = lds1f(sta + i * 64 + 4) * (0.17677669529663687f * 1.4426950408889634f);
                    rk[i][0] = lds1f(k0 + i * 64); rk[i][1] = lds1f(k1 + i * 64);
                    fq[i][0] = rq * rk[i][0]; fq[i][1] = rq * rk[i][1];
                }
            };
#pragma unroll
            for (int jj = 0; jj < 12; jj++) { const int j = (jj >> 2) * 8 + (jj & 3); np(2, j); if (j < 8) np(3, j); }
            factors();
            wg_wait<0>();
#pragma unroll
            for (int i = 0; i < 96; i++) asm volatile("" : "+f"(acc[0][i]) :: "memory");
            if (elect) mbar_arrive(bars + 8 * B_G1DONE);
            const float mask = tw == 0 && j0 == 0 ? -INFINITY : 0.f;
#pragma unroll
            for (int hd = 0; hd < 2; hd++) {
#pragma unroll
                for (int jj = 0; jj < 12; jj++) {
                    const int j = (jj >> 2) * 8 + hd * 4 + (jj & 3);
                    np(0, j); np(1, j);
                    if (j & 4)
                    { np(2, j); if (j < 8) np(3, j); }
                }
                if (hd == 0) mbar_wait(bars + 8 * B_G1DONE, 0);
                float s[2][3][4];
#pragma unroll
                for (int h = 1; h >= 0; h--)
#pragma unroll
                    for (int n = 2; n >= 0; n--) {
                        if (h == 0 && n == 0 && hd == 0) {
                            TSC(TIMING == 8 && ln == 0 && wi == 1 && s[1][0][0] + s[0][1][0] != 123.456f, 33 + 8 * w);
                            bar_sync(3 + tw, 64);
#pragma unroll
                            for (int c = 0; c < 8; c++) hl[c] = lds2(ha + c * 256);
                        }
                        const int kg = 2 * h - 1 + n;
                        s[h][n][0] = s[h][n][1] = kg < 0 ? mask : 0.f; s[h][n][2] = s[h][n][3] = 0.f;
#pragma unroll
                        for (int ks = 0; ks < 2; ks++) {
                            const int q = hd * 4 + 2 * ks;
                            const uint32_t* k = kg < 0 ? &hl[hd * 2 + ks].x : &pk[kg < 0 ? 0 : kg][8 + q];
                            mma16816(s[h][n], pk[2 * h][q], pk[2 * h + 1][q], pk[2 * h][q + 1], pk[2 * h + 1][q + 1], k[0], k[1]);
                        }
                    }
                uint32_t pp[4], pc[4];
#pragma unroll
                for (int i = 0; i < 4; i++) {
                    const float* sp = &s[i >> 1][i & 1][2 * (i & 1)];
                    const float* sc = &s[i >> 1][(i & 1) + 1][2 * (i & 1)];
                    float a0 = (u0 ? sp[0] : sc[0]) * fq[i][0], a1 = (u1 ? sp[1] : sc[1]) * fq[i][1];
                    float m = fmaxf(a0, a1);
                    m = fmaxf(m, __shfl_xor_sync(0xffffffffu, m, 1));
                    m = fmaxf(m, __shfl_xor_sync(0xffffffffu, m, 2));
                    a0 = ex2(a0 - m); a1 = ex2(a1 - m);
                    float sum = a0 + a1;
                    sum += __shfl_xor_sync(0xffffffffu, sum, 1);
                    sum += __shfl_xor_sync(0xffffffffu, sum, 2);
                    const float inv = rcp(sum);
                    const uint32_t pw = pack_bf16(a0 * rk[i][0] * inv, a1 * rk[i][1] * inv);
                    pp[i] = pw & mU; pc[i] = pw & ~mU;
                }
                TSC(TIMING == 8 && ln == 0 && wi == 1 && pp[0] + pp[3] != 0x12345, 34 + 2 * hd + 8 * w);
#pragma unroll
                for (int fh = 0; fh < 2; fh++)
#pragma unroll
                    for (int i = 0; i < 4; i++) {
                        const int v = 16 + hd * 4 + 2 * fh;
                        const uint32_t* vp = i ? &pk[i ? i - 1 : 0][v] : &hl[4 + hd * 2 + fh].x;
                        float o[4] = {0.f, 0.f, 0.f, 0.f};
                        if (i & 1) mma16816(o, vp[0], vp[1], pk[i][v], pk[i][v + 1], pp[i], pc[i]);
                        else { mma1688(o, pk[i][v], pk[i][v + 1], pc[i]); mma1688(o, vp[0], vp[1], pp[i]); }
                        const uint32_t tm = (ln & 7) == (nt & 3) * 2 + (i & 1);
                        ow[hd * 4 + 2 * fh][i] = tagw(pack_bf16(o[0], o[1]), tm, tag); ow[hd * 4 + 2 * fh + 1][i] = tagw(pack_bf16(o[2], o[3]), tm, tag);
                    }
                store_o(hd ? ST_A : 0, hd ? ST_B : ST_A);
                TSC(TIMING == 11 && !hd && ln == 0 && wi == 3, 45 + w);
                if (!hd) mbar_arrive_after(bars + 8 * B_AST, ln, hl[2].x ^ hl[3].x ^ hl[5].x ^ hl[6].x ^ hl[7].x);
                mbar_wait(bars + 8 * B_G1DONE, 0);
                if (hd && ln == 0) mbar_arrive(bars + 8 * B_ATT);
                TSC(TIMING != 14 && elect && hd == 0, 3 + 8 * w);
                TSC(TIMING == 8 && ln == 0 && wi == 1, 35 + 2 * hd + 8 * w);
            }
        }
        TSC(TIMING != 14 && elect, 4 + 8 * w);
        float acc2[64];
        TSC(TIMING != 14 && elect, 5 + 8 * w);
        {
            const uint32_t ring = sb + (w ? OFF_O1 : OFF_O0), da0 = (ring >> 4) + dlo(0, 1024);
            const uint32_t l2 = opaque(ln), chk = ring + wi * 256 + (l2 >> 3) * 1032 + ((l2 >> 2) & 1) * 132 + (l2 & 3) * 32;
            const uint32_t xs = sb + (wi & 1) * 8192 + (tw >> 1) * 2048, mad = xs + (l2 & 15) * 128;
            auto residual = [&](float* base) {
                const uint32_t sta = sb + OFF_STAT + (8 + hp * 128 + tw * 16 + g) * 8;
                const float2 s0 = lds2f(sta), s1 = lds2f(sta + 64);
                const float m0 = s0.x * s0.y, r0 = 1.f + s0.y, m1 = s1.x * s1.y, r1 = 1.f + s1.y;
                mbar_wait(bars + 8 * B_XR, 0);
#pragma unroll
                for (int j = 0; j < 16; j += 2) {
                    uint32_t xr[4];
                    asm volatile("ldmatrix.sync.aligned.m8n8.x4.shared.b16 {%0,%1,%2,%3}, [%4];" : "=r"(xr[0]), "=r"(xr[1]), "=r"(xr[2]), "=r"(xr[3])
                                 : "r"(mad + (j >> 3) * OFF_X1 + ((((j & 7) + (l2 >> 4)) ^ (l2 & 7)) << 4)) : "memory");
#pragma unroll
                    for (int c = 0; c < 4; c++) {
                        base[4 * j + 2 * c] = fmaf(bf_lo(xr[c]), c & 1 ? r1 : r0, c & 1 ? m1 : m0); base[4 * j + 2 * c + 1] = fmaf(bf_hi(xr[c]), c & 1 ? r1 : r0, c & 1 ? m1 : m0);
                        asm volatile("" : "+f"(base[4 * j + 2 * c]), "+f"(base[4 * j + 2 * c + 1]) :: "memory");
                    }
                }
            };
            residual(acc2);
            uint32_t db = sd + dlo(OFF_WO0, 16384);
#pragma unroll 1
            for (int s = 0; s < 8; s++) {
                const uint32_t ro = (s & 1) * 16384;
                mbar_wait(bars + 8 * (B_WOFULL + s), 0);
                TSC(TIMING == 11 && tid == 0 && s == 0, 43);
                mbar_wait(bars + 8 * (B_OFULL + s) + 64 * w, 0);
                TSC(TIMING == 11 && tid == 0 && s == 0, 44);
#pragma unroll 1
                for (int it = 0; __any_sync(0xffffffffu, (mism(lds1(chk + ro), lds1(chk + ro + 4096), tag) | mism(lds1(chk + ro + 8192), lds1(chk + ro + 12288), tag)) & 1) && it < SPIN_LIMIT; it++) {
                    NRETRY();
                    const uint32_t fo = wi * 256 + (l2 >> 4) * 1024 + (l2 & 15) * 16;
                    uint4 v[8];
#pragma unroll
                    for (int c = 0; c < 8; c++) v[c] = ld_rlx4(g_o + (size_t)(((mt * 2 + hp) * 2 + w) * 8 + s) * 16384 + fo + c * 2048);
#pragma unroll
                    for (int c = 0; c < 8; c++) sts4(ring + ro + fo + c * 2048, v[c].x, v[c].y, v[c].z, v[c].w);
                    fence_async_smem();
                    __syncwarp();
                }
                if (s == 0) mbar_wait(bars + 8 * B_ATT, 0);
                if (s <= 8 - LAST) bar_sync(1 + w, 256);
                TSC(elect && s == 0, 6 + 8 * w);
                TSC(TIMING == 2 && elect, 32 + 16 * w + s);
                wg_fence();
#pragma unroll
                for (int k = 0; k < 8; k++)
                    wgmma_n128<1, 1>(acc2, mkdesc(da0 + (ro >> 4) + k * 128, dhi(128, 0)), mkdesc(db + k * 128, dhi(1024, 1)));
                wg_commit();
                db = wo_next(db, sd + dlo(0, 16384), 4);
                if (s < 8 - LAST) {
                    bar_arrive(2 - w, 256);
                    if (SPREAD < 0) { if (s == 0) store_o(ST_B, 8); }
                    else {
#pragma unroll
                        for (int f = ST_B; f < 8; f++)
                            if (s == f - ST_B + SPREAD) store_o(f, f + 1);
                    }
                    wg_wait<0>();
                    if (elect) mbar_arrive(bars + 8 * (B_DONE + s) + 64 * w);
                }
            }
            mbar_wait(bars + 8 * B_UPD, 0);
            int sl0, sl1;
            asm volatile("ld.shared.s8 %0, [%1];" : "=r"(sl0) : "r"(sb + OFF_ROWMAP + tw * 16 + g) : "memory");
            asm volatile("ld.shared.s8 %0, [%1];" : "=r"(sl1) : "r"(sb + OFF_ROWMAP + tw * 16 + 8 + g) : "memory");
            const uint32_t e0 = (sl0 >> 1) == (int)t ? 0x3f80u << ((sl0 & 1) * 16) : 0u, e1 = (sl1 >> 1) == (int)t ? 0x3f80u << ((sl1 & 1) * 16) : 0u;
            if (!SKIP_UPD || __any_sync(0xffffffffu, lds1(sb + OFF_ROWMAP + (1 - w) * 64 + (l2 & 15) * 4) != 0xffffffffu)) {
                wg_fence();
                wgmma_rs_n128<1>(acc2, e0, e1, 0u, 0u, mkdesc(sd + dlo(OFF_FA, 0), dhi(128, 0)));
                wg_commit();
            }
            bar_arrive(2 - w, 256);
            wg_wait<0>();
#pragma unroll
            for (int i = 0; i < 64; i++) asm volatile("" : "+f"(acc2[i]) :: "memory");
            TSC(elect, 7 + 8 * w);
#pragma unroll
            for (int j = 0; j < 16; j += 2) {
                const int ch = (j & 7) + (l2 >> 4);
                asm volatile("stmatrix.sync.aligned.m8n8.x4.shared.b16 [%0], {%1,%2,%3,%4};" ::"r"(mad + (j >> 3) * OFF_X1 + ((ch ^ (l2 & 7)) << 4)),
                             "r"(pack_bf16(acc2[4 * j], acc2[4 * j + 1])), "r"(pack_bf16(acc2[4 * j + 2], acc2[4 * j + 3])),
                             "r"(pack_bf16(acc2[4 * j + 4], acc2[4 * j + 5])), "r"(pack_bf16(acc2[4 * j + 6], acc2[4 * j + 7])) : "memory");
                if ((j & 7) == 6) {
                    fence_async_smem();
                    __syncwarp();
                    if (ln == 0) tma_store_2d(&mout, xs + (j >> 3) * OFF_X1, par * 1024 + cb * 128 + (j >> 3) * 64, j0 + hp * 128 + tw * 16);
                }
            }
            if (ln == 0) asm volatile("cp.async.bulk.commit_group;\ncp.async.bulk.wait_group.read 0;" ::: "memory");
            TSC(elect, 8 + 8 * w);
            TS_END();
        }
    }
}

typedef CUresult (*EncodeFn)(CUtensorMap*, CUtensorMapDataType, cuuint32_t, void*, const cuuint64_t*, const cuuint64_t*, const cuuint32_t*,
                             const cuuint32_t*, CUtensorMapInterleave, CUtensorMapSwizzle, CUtensorMapL2promotion, CUtensorMapFloatOOBfill);

CUtensorMap make_map(EncodeFn fn, const void* base, int rank, const cuuint64_t* dims, const cuuint64_t* strides, const cuuint32_t* box,
                     CUtensorMapSwizzle swz = CU_TENSOR_MAP_SWIZZLE_128B, CUtensorMapL2promotion pro = CU_TENSOR_MAP_L2_PROMOTION_L2_256B) {
    CUtensorMap m;
    cuuint32_t es[5] = {1, 1, 1, 1, 1};
    fn(&m, CU_TENSOR_MAP_DATA_TYPE_BFLOAT16, rank, (void*)base, dims, strides, box, es, CU_TENSOR_MAP_INTERLEAVE_NONE,
       swz, pro, CU_TENSOR_MAP_FLOAT_OOB_FILL_NONE);
    return m;
}

}

extern "C" void kernel_launch(void* const* d_in, const int* in_sizes, int n_in, void* d_out, int out_size) {
    (void)in_sizes; (void)n_in; (void)out_size;
    const __nv_bfloat16* x = (const __nv_bfloat16*)d_in[0];
    const __nv_bfloat16* wqkv = (const __nv_bfloat16*)d_in[1];
    const char* wo = (const char*)d_in[2];
    const __nv_bfloat16* wr = (const __nv_bfloat16*)d_in[4];
    const char* wg = (const char*)d_in[5];
    const char* wu = (const char*)d_in[6];
    const char* wd = (const char*)d_in[7];
    static EncodeFn fn = nullptr;
    static int by_sm = 0;
    static Scratch* scr = nullptr;
    if (!fn) {
        void* p = nullptr; cudaDriverEntryPointQueryResult q;
        cudaGetDriverEntryPoint("cuTensorMapEncodeTiled", &p, cudaEnableDefault, &q);
        fn = (EncodeFn)p;
        cudaFuncSetAttribute(fused_kernel, cudaFuncAttributeMaxDynamicSharedMemorySize, SMEM_LAUNCH);
        cudaGetSymbolAddress((void**)&scr, g_scr);
        int dev = 0, sms = 0;
        cudaGetDevice(&dev);
        cudaDeviceGetAttribute(&sms, cudaDevAttrMultiProcessorCount, dev);
        by_sm = sms == 132;
    }
    Roles roles;
    for (int i = 0; i < 132; i++) {
        const int T = i >> 1, T8 = T < 32 ? T : T + 1 + (T - 32) / 7, fb = (T < 60 ? (~T8 & 7) * 8 + (T8 >> 3) : T < 62 ? T + 4 : T - 2) * 2 + (i & 1);
        roles.v[i] = fb | ((fb & ~31) | (fb & 1) << 4 | (fb & 31) >> 1) << 8;
    }
    const cuuint64_t xd[4] = {2048, 16, 32, 2}, xs[3] = {4096, 131072, 65536};
    const cuuint32_t xb[4] = {64, 16, 4, 2};
    const cuuint64_t wdm[3] = {1024, 1024, 3}, wst[2] = {6144, 2048};
    const cuuint32_t wb[3] = {64, 64, 3};
    const cuuint64_t od[4] = {64, 64, 16, 16}, ost[3] = {2048, 131072, 128};
    const cuuint32_t ob[4] = {64, 8, 16, 2};
    const cuuint64_t yd[2] = {2048, 1024}, yst[1] = {4096};
    const cuuint32_t yb[2] = {64, 16};
    const cuuint64_t sd[3] = {64, 1024, 32}, sst[2] = {4096, 128};
    const cuuint32_t sbx[3] = {64, 16, 4};
    CUtensorMap mxs = make_map(fn, x, 3, sd, sst, sbx);
    const cuuint64_t cd[3] = {3072, 64, 16}, cst[2] = {6144, 393216};
    const cuuint32_t cbx[3] = {64, 8, 2};
    CUtensorMap mcs = make_map(fn, wqkv, 3, cd, cst, cbx, CU_TENSOR_MAP_SWIZZLE_NONE);
    CUtensorMap mx = make_map(fn, x, 4, xd, xs, xb), mw = make_map(fn, wqkv, 3, wdm, wst, wb);
    CUtensorMap mwo = make_map(fn, wo, 4, od, ost, ob), mout = make_map(fn, d_out, 2, yd, yst, yb);
    const cuuint64_t gd[3] = {3584, 1024, 2}, gst[2] = {7168, (cuuint64_t)(wu < wg ? wg - wu : wu - wg)};
    const cuuint32_t gb[3] = {32, 128, 2};
    const cuuint64_t dd[2] = {1024, 3584}, dst[1] = {2048};
    const cuuint32_t db[2] = {64, 64};
    CUtensorMap mgu = make_map(fn, wu < wg ? wu : wg, 3, gd, gst, gb, CU_TENSOR_MAP_SWIZZLE_64B, CU_TENSOR_MAP_L2_PROMOTION_L2_128B);
    CUtensorMap mwd = make_map(fn, wd, 2, dd, dst, db, CU_TENSOR_MAP_SWIZZLE_128B, CU_TENSOR_MAP_L2_PROMOTION_L2_128B);
    fused_kernel<<<132, 512, SMEM_LAUNCH, cudaStreamPerThread>>>(by_sm, x, wqkv, wr, scr, wg, wu, wd, wo, roles, mw, mx, mwo, mxs, mcs, mout, mgu, mwd);
}
```

```cpp
#include <cuda_runtime.h>
#include <cuda.h>
#include <cuda_bf16.h>
#include <stdint.h>

namespace {

constexpr int STAGE = 57344;
constexpr int OFF_FW = 3 * STAGE;
constexpr int OFF_FA = OFF_FW + 49152;
constexpr int OFF_CS = OFF_FA + 6144;
constexpr int OFF_STAT = OFF_CS + 1232;
constexpr int OFF_ROWMAP = OFF_STAT + 2112;
constexpr int OFF_TAG = OFF_ROWMAP + 128;
constexpr int OFF_BAR = OFF_TAG + 8;
constexpr int OFF_F2X = 16384, OFF_HALO = 24576, OFF_O1 = 24576, OFF_O0 = 90112, NWO = 3, OFF_MEAN = 2 * STAGE, OFF_X1 = 2 * STAGE + 8192;
constexpr int OFF_WO0 = OFF_X1 + 16384, OFF_WO1 = STAGE, OFF_WO2 = OFF_FW;
static_assert(OFF_WO0 + 32768 == OFF_FW && OFF_WO1 + 32768 == OFF_O0 && OFF_O0 + 32768 == OFF_X1 && OFF_O1 + 32768 == STAGE, "alias");
__host__ __device__ constexpr uint32_t wo_next(uint32_t o, uint32_t base, int sh) { return o == base + (OFF_WO0 >> sh) ? base + (OFF_WO1 >> sh) : o == base + (OFF_WO1 >> sh) ? base + (OFF_WO2 >> sh) : base + (OFF_WO0 >> sh); }
constexpr int B_FULLA = 0, B_FULLB = 3, B_ROW = 6, B_FFULL = 11, B_F2DONE = 14, B_SW = 15, B_CS = 16, B_FDONE = 22, B_WOFULL = B_FDONE + 8, B_OFULL = B_WOFULL + 8,
              B_DONE = B_OFULL + 16;
constexpr int B_EMPTY = B_DONE + 16, B_XR = B_EMPTY + 3, B_G1DONE = B_XR + 1;
constexpr int B_UPD = B_G1DONE + 1, B_F2FULL = B_UPD + 1;
constexpr int B_AUX = B_F2FULL + 1, B_PART = B_AUX + 1, B_ATT = B_PART + 1, B_CSDONE = B_ATT + 1, B_AST = B_CSDONE + 1, NBAR = B_AST + 1;
constexpr int SMEM_BYTES = OFF_BAR + NBAR * 8;
static_assert(SMEM_BYTES <= 232448 && OFF_BAR % 8 == 0, "smem");
#define P_PART 13
#define F1_MASK (0x6a005a00u >> (14 - P_PART))
#define PF_CNT 0x2aaaaacu
#define N_S1 1
#define N_S2 3
#define ST_A 2
#define ST_B 5
#define T_H 0
#define T_O1 250
#define T_O 1750
#define T_S1 128
#define T_S2 950
#define N_GA 4
#define N_X 1
#define D_X 2
#define D_R 3
#define N_ROW 5
#define N_W 5
#define K_W1 5
#define K_W2 10
#define N_CS 3
#define N_F1 4
#define LAST 2
#define N_HA 4
#define N_A2 4
#define TAIL 1
#define POLL_NS 100
constexpr int SPIN_LIMIT = 1 << 18;

struct Scratch {
    uint8_t o[2048 * 1024 * 2];
    uint2 rec[2048];
    float cs[8][3072];
    uint32_t halo[128][512];
    uint32_t h[14336];
    float ypart[8][8][1024];
    uint2 sel[16];
    uint32_t hint[128][8];
    uint32_t epoch;
};
__device__ __align__(1024) Scratch g_scr;

#define TS(i) do {} while (0)
#define TS_END() do {} while (0)
constexpr int SMEM_LAUNCH = SMEM_BYTES;
#define TSC(c, i) do {} while (0)
#define NRETRY() do {} while (0)
__device__ __forceinline__ uint32_t smem_u32(const void* p) { return (uint32_t)__cvta_generic_to_shared(p); }
__device__ __forceinline__ void mbar_init(uint32_t bar, uint32_t cnt) { asm volatile("mbarrier.init.shared::cta.b64 [%0], %1;" ::"r"(bar), "r"(cnt) : "memory"); }
__device__ __forceinline__ void mbar_expect_tx(uint32_t bar, uint32_t bytes) { asm volatile("mbarrier.arrive.expect_tx.shared::cta.b64 _, [%0], %1;" ::"r"(bar), "r"(bytes) : "memory"); }
__device__ __forceinline__ void mbar_arrive(uint32_t bar) { asm volatile("mbarrier.arrive.shared::cta.b64 _, [%0];" ::"r"(bar) : "memory"); }
__device__ __forceinline__ void mbar_arrive_after(uint32_t bar, uint32_t lane, uint32_t dep) {
    asm volatile("{\n.reg .pred p;\n.reg .b32 t;\nsetp.eq.u32 p, %1, 0;\nmad.lo.u32 t, %1, %2, %0;\n@p mbarrier.arrive.shared::cta.b64 _, [t];\n}" ::"r"(bar), "r"(lane), "r"(dep) : "memory");
}
__device__ __forceinline__ void mbar_wait(uint32_t bar, uint32_t parity) {
    asm volatile("{\n.reg .pred P1;\nLAB_WAIT:\nmbarrier.try_wait.parity.shared::cta.b64 P1, [%0], %1;\n@!P1 bra LAB_WAIT;\n}" ::"r"(bar), "r"(parity) : "memory");
}
__device__ __forceinline__ void tma_3d(uint32_t dst, const CUtensorMap* m, uint32_t bar, int c0, int c1, int c2) {
    asm volatile("cp.async.bulk.tensor.3d.shared::cluster.global.mbarrier::complete_tx::bytes [%0], [%1, {%3, %4, %5}], [%2];" ::"r"(dst), "l"(m), "r"(bar), "r"(c0), "r"(c1), "r"(c2) : "memory");
}
__device__ __forceinline__ void tma_2d_once(uint32_t dst, const CUtensorMap* m, uint32_t bar, int c0, int c1) {
    asm volatile("cp.async.bulk.tensor.2d.shared::cluster.global.mbarrier::complete_tx::bytes.L2::cache_hint [%0], [%1, {%3, %4}], [%2], %5;" ::"r"(dst), "l"(m), "r"(bar), "r"(c0), "r"(c1), "l"(0x12F0000000000000ull) : "memory");
}
__device__ __forceinline__ void tma_3d_once(uint32_t dst, const CUtensorMap* m, uint32_t bar, int c0, int c1, int c2) {
    asm volatile("cp.async.bulk.tensor.3d.shared::cluster.global.mbarrier::complete_tx::bytes.L2::cache_hint [%0], [%1, {%3, %4, %5}], [%2], %6;" ::"r"(dst), "l"(m), "r"(bar), "r"(c0), "r"(c1), "r"(c2), "l"(0x12F0000000000000ull) : "memory");
}
__device__ __forceinline__ void tma_4d(uint32_t dst, const CUtensorMap* m, uint32_t bar, int c0, int c1, int c2, int c3) {
    asm volatile("cp.async.bulk.tensor.4d.shared::cluster.global.mbarrier::complete_tx::bytes [%0], [%1, {%3, %4, %5, %6}], [%2];" ::"r"(dst), "l"(m), "r"(bar), "r"(c0), "r"(c1), "r"(c2), "r"(c3) : "memory");
}
__device__ __forceinline__ void tma_store_2d(const CUtensorMap* m, uint32_t src, int c0, int c1) {
    asm volatile("cp.async.bulk.tensor.2d.global.shared::cta.bulk_group [%0, {%2, %3}], [%1];" ::"l"(m), "r"(src), "r"(c0), "r"(c1) : "memory");
}
__device__ __forceinline__ void bulk_g2s(uint32_t dst, const void* src, uint32_t bytes, uint32_t bar) {
    asm volatile("cp.async.bulk.shared::cluster.global.mbarrier::complete_tx::bytes [%0], [%1], %2, [%3];" ::"r"(dst), "l"(src), "r"(bytes), "r"(bar) : "memory");
}
__device__ __forceinline__ void bulk_prefetch(const void* p, uint32_t bytes) { asm volatile("cp.async.bulk.prefetch.L2.global [%0], %1;" ::"l"(p), "r"(bytes) : "memory"); }
__device__ __forceinline__ void prefetch_map(const CUtensorMap* m) { asm volatile("prefetch.tensormap [%0];" ::"l"(m) : "memory"); }
__device__ __forceinline__ void fence_async_smem() { asm volatile("fence.proxy.async.shared::cta;" ::: "memory"); }
__device__ __forceinline__ void wg_fence() { asm volatile("wgmma.fence.sync.aligned;" ::: "memory"); }
__device__ __forceinline__ void wg_commit() { asm volatile("wgmma.commit_group.sync.aligned;" ::: "memory"); }
template <int N> __device__ __forceinline__ void wg_wait() { asm volatile("wgmma.wait_group.sync.aligned %0;" ::"n"(N) : "memory"); }
__device__ __forceinline__ uint64_t mkdesc(uint32_t lo, uint32_t hi) { return ((uint64_t)hi << 32) | lo; }
__host__ __device__ constexpr uint32_t dhi(uint32_t sbo, uint32_t mode) { return (sbo >> 4) | (mode << 30); }
__host__ __device__ constexpr uint32_t dlo(uint32_t off, uint32_t lbo) { return (off >> 4) + ((lbo >> 4) << 16); }
__device__ __forceinline__ bool elect_one() {
    uint32_t e;
    asm volatile("{\n.reg .pred p;\nelect.sync _|p, 0xffffffff;\nselp.u32 %0, 1, 0, p;\n}" : "=r"(e));
    return e;
}
template <int R> __device__ __forceinline__ void reg_inc() { asm volatile("setmaxnreg.inc.sync.aligned.u32 %0;" ::"n"(R)); }
template <int R> __device__ __forceinline__ void reg_dec() { asm volatile("setmaxnreg.dec.sync.aligned.u32 %0;" ::"n"(R)); }
__device__ __forceinline__ void bar_sync(int id, int n) { asm volatile("bar.sync %0, %1;" ::"r"(id), "r"(n) : "memory"); }
__device__ __forceinline__ void bar_arrive(int id, int n) { asm volatile("bar.arrive %0, %1;" ::"r"(id), "r"(n) : "memory"); }
__device__ __forceinline__ uint32_t pack_bf16(float lo, float hi) { uint32_t r; asm("cvt.rn.bf16x2.f32 %0, %1, %2;" : "=r"(r) : "f"(hi), "f"(lo)); return r; }
__device__ __forceinline__ float bf_lo(uint32_t u) { return __uint_as_float(u << 16); }
__device__ __forceinline__ float bf_hi(uint32_t u) { return __uint_as_float(u & 0xffff0000u); }
__device__ __forceinline__ float bf16r(float v) { return bf_lo(pack_bf16(v, 0.f)); }
__device__ __forceinline__ uint32_t tagw(uint32_t w, uint32_t m, uint32_t tag) { uint32_t r; asm("lop3.b32 %0, %1, %2, %3, 0xb8;" : "=r"(r) : "r"(w), "r"(m), "r"(tag)); return r; }
__device__ __forceinline__ uint32_t tagf(float f, uint32_t tag) { return tagw(__float_as_uint(f), 1u, tag); }
__device__ __forceinline__ uint32_t movm(uint32_t a) { uint32_t d; asm volatile("movmatrix.sync.aligned.m8n8.trans.b16 %0, %1;" : "=r"(d) : "r"(a)); return d; }
__device__ __forceinline__ void mma16816(float (&c)[4], uint32_t a0, uint32_t a1, uint32_t a2, uint32_t a3, uint32_t b0, uint32_t b1) {
    asm volatile("mma.sync.aligned.m16n8k16.row.col.f32.bf16.bf16.f32 {%0,%1,%2,%3}, {%4,%5,%6,%7}, {%8,%9}, {%0,%1,%2,%3};"
                 : "+f"(c[0]), "+f"(c[1]), "+f"(c[2]), "+f"(c[3]) : "r"(a0), "r"(a1), "r"(a2), "r"(a3), "r"(b0), "r"(b1));
}
__device__ __forceinline__ void mma1688(float (&c)[4], uint32_t a0, uint32_t a1, uint32_t b0) {
    asm volatile("mma.sync.aligned.m16n8k8.row.col.f32.bf16.bf16.f32 {%0,%1,%2,%3}, {%4,%5}, {%6}, {%0,%1,%2,%3};"
                 : "+f"(c[0]), "+f"(c[1]), "+f"(c[2]), "+f"(c[3]) : "r"(a0), "r"(a1), "r"(b0));
}
__device__ __forceinline__ uint32_t ld_rlx(const void* p) { uint32_t v; asm volatile("ld.relaxed.gpu.global.u32 %0, [%1];" : "=r"(v) : "l"(p) : "memory"); return v; }
__device__ __forceinline__ uint2 ld_rlx2(const void* p) { uint2 v; asm volatile("ld.relaxed.gpu.global.v2.u32 {%0,%1}, [%2];" : "=r"(v.x), "=r"(v.y) : "l"(p) : "memory"); return v; }
__device__ __forceinline__ uint4 ld_rlx4(const void* p) { uint4 v; asm volatile("ld.relaxed.gpu.global.v4.u32 {%0,%1,%2,%3}, [%4];" : "=r"(v.x), "=r"(v.y), "=r"(v.z), "=r"(v.w) : "l"(p) : "memory"); return v; }
__device__ __forceinline__ void st_rlx(void* p, uint32_t v) { asm volatile("st.relaxed.gpu.global.u32 [%0], %1;" ::"l"(p), "r"(v) : "memory"); }
__device__ __forceinline__ void st_rlx2(void* p, uint32_t a, uint32_t b) { asm volatile("st.relaxed.gpu.global.v2.u32 [%0], {%1,%2};" ::"l"(p), "r"(a), "r"(b) : "memory"); }
__device__ __forceinline__ void st_rlx4(void* p, uint32_t a, uint32_t b, uint32_t c, uint32_t d) { asm volatile("st.relaxed.gpu.global.v4.u32 [%0], {%1,%2,%3,%4};" ::"l"(p), "r"(a), "r"(b), "r"(c), "r"(d) : "memory"); }
__device__ __forceinline__ uint4 ldg_nc(const void* p) { uint4 v; asm volatile("ld.global.nc.v4.u32 {%0,%1,%2,%3}, [%4];" : "=r"(v.x), "=r"(v.y), "=r"(v.z), "=r"(v.w) : "l"(p)); return v; }
__device__ __forceinline__ uint32_t mism(uint32_t a, uint32_t b, uint32_t tag) { uint32_t r; asm("lop3.b32 %0, %1, %2, %3, 0x7e;" : "=r"(r) : "r"(a), "r"(b), "r"(tag)); return r; }
__device__ __forceinline__ uint32_t mism(const uint4& v, uint32_t tag) { return mism(v.x, v.y, tag) | mism(v.z, v.w, tag); }
__device__ __forceinline__ void prefetch_l2(const void* p) { asm volatile("prefetch.global.L2 [%0];" ::"l"(p)); }
__device__ __forceinline__ void nap(int n) {
#pragma unroll 1
    for (int i = 0; i < n; i++) __nanosleep(100);
}
__device__ __forceinline__ uint32_t now() { uint32_t t; asm volatile("mov.u32 %0, %%globaltimer_lo;" : "=r"(t)); return t; }
__device__ __forceinline__ void until(uint32_t t) {
    while (t - now() - 1 < 16384u) __nanosleep(50);
}
__device__ __forceinline__ uint32_t opaque(uint32_t v) { return __shfl_xor_sync(0xffffffffu, v, 0); }
__device__ __forceinline__ void sts4(uint32_t a, uint32_t x, uint32_t y, uint32_t z, uint32_t w) { asm volatile("st.shared.v4.u32 [%0], {%1,%2,%3,%4};" ::"r"(a), "r"(x), "r"(y), "r"(z), "r"(w) : "memory"); }
__device__ __forceinline__ void sts2(uint32_t a, uint32_t x, uint32_t y) { asm volatile("st.shared.v2.u32 [%0], {%1,%2};" ::"r"(a), "r"(x), "r"(y) : "memory"); }
__device__ __forceinline__ uint4 lds4(uint32_t a) { uint4 v; asm volatile("ld.shared.v4.u32 {%0,%1,%2,%3}, [%4];" : "=r"(v.x), "=r"(v.y), "=r"(v.z), "=r"(v.w) : "r"(a) : "memory"); return v; }
__device__ __forceinline__ float4 lds4f(uint32_t a) { float4 v; asm volatile("ld.shared.v4.f32 {%0,%1,%2,%3}, [%4];" : "=f"(v.x), "=f"(v.y), "=f"(v.z), "=f"(v.w) : "r"(a) : "memory"); return v; }
__device__ __forceinline__ uint2 lds2(uint32_t a) { uint2 v; asm volatile("ld.shared.v2.u32 {%0,%1}, [%2];" : "=r"(v.x), "=r"(v.y) : "r"(a) : "memory"); return v; }
__device__ __forceinline__ float2 lds2f(uint32_t a) { float2 v; asm volatile("ld.shared.v2.f32 {%0,%1}, [%2];" : "=f"(v.x), "=f"(v.y) : "r"(a) : "memory"); return v; }
__device__ __forceinline__ uint32_t lds1(uint32_t a) { uint32_t v; asm volatile("ld.shared.u32 %0, [%1];" : "=r"(v) : "r"(a) : "memory"); return v; }
__device__ __forceinline__ float lds1f(uint32_t a) { return __uint_as_float(lds1(a)); }
__device__ __forceinline__ void sts1(uint32_t a, uint32_t v) { asm volatile("st.shared.u32 [%0], %1;" ::"r"(a), "r"(v) : "memory"); }
__device__ __forceinline__ uint32_t redux_max(uint32_t v) { uint32_t r; asm volatile("redux.sync.max.u32 %0, %1, 0xffffffff;" : "=r"(r) : "r"(v)); return r; }
__device__ __forceinline__ float ex2(float x) { float r; asm("ex2.approx.ftz.f32 %0, %1;" : "=f"(r) : "f"(x)); return r; }
__device__ __forceinline__ float rcp(float x) { float r; asm("rcp.approx.ftz.f32 %0, %1;" : "=f"(r) : "f"(x)); return r; }
__device__ __forceinline__ float sigmoidf(float v) { return rcp(1.f + ex2(v * -1.4426950408889634f)); }

template <int TA, int TB>
__device__ __forceinline__ void wgmma_n192(float (&d)[96], uint64_t da, uint64_t db, int acc = 1) {
    asm volatile("{\n.reg .pred p;\nsetp.ne.b32 p, %100, 0;\n"
        "wgmma.mma_async.sync.aligned.m64n192k16.f32.bf16.bf16 "
        "{%0, %1, %2, %3, %4, %5, %6, %7, %8, %9, %10, %11, %12, %13, %14, %15, "
        "%16, %17, %18, %19, %20, %21, %22, %23, %24, %25, %26, %27, %28, %29, %30, %31, "
        "%32, %33, %34, %35, %36, %37, %38, %39, %40, %41, %42, %43, %44, %45, %46, %47, "
        "%48, %49, %50, %51, %52, %53, %54, %55, %56, %57, %58, %59, %60, %61, %62, %63, "
        "%64, %65, %66, %67, %68, %69, %70, %71, %72, %73, %74, %75, %76, %77, %78, %79, "
        "%80, %81, %82, %83, %84, %85, %86, %87, %88, %89, %90, %91, %92, %93, %94, %95}, "
        "%96, %97, p, 1, 1, %98, %99;\n}\n"
        : "+f"(d[0]), "+f"(d[1]), "+f"(d[2]), "+f"(d[3]), "+f"(d[4]), "+f"(d[5]), "+f"(d[6]), "+f"(d[7]),
          "+f"(d[8]), "+f"(d[9]), "+f"(d[10]), "+f"(d[11]), "+f"(d[12]), "+f"(d[13]), "+f"(d[14]), "+f"(d[15]),
          "+f"(d[16]), "+f"(d[17]), "+f"(d[18]), "+f"(d[19]), "+f"(d[20]), "+f"(d[21]), "+f"(d[22]), "+f"(d[23]),
          "+f"(d[24]), "+f"(d[25]), "+f"(d[26]), "+f"(d[27]), "+f"(d[28]), "+f"(d[29]), "+f"(d[30]), "+f"(d[31]),
          "+f"(d[32]), "+f"(d[33]), "+f"(d[34]), "+f"(d[35]), "+f"(d[36]), "+f"(d[37]), "+f"(d[38]), "+f"(d[39]),
          "+f"(d[40]), "+f"(d[41]), "+f"(d[42]), "+f"(d[43]), "+f"(d[44]), "+f"(d[45]), "+f"(d[46]), "+f"(d[47]),
          "+f"(d[48]), "+f"(d[49]), "+f"(d[50]), "+f"(d[51]), "+f"(d[52]), "+f"(d[53]), "+f"(d[54]), "+f"(d[55]),
          "+f"(d[56]), "+f"(d[57]), "+f"(d[58]), "+f"(d[59]), "+f"(d[60]), "+f"(d[61]), "+f"(d[62]), "+f"(d[63]),
          "+f"(d[64]), "+f"(d[65]), "+f"(d[66]), "+f"(d[67]), "+f"(d[68]), "+f"(d[69]), "+f"(d[70]), "+f"(d[71]),
          "+f"(d[72]), "+f"(d[73]), "+f"(d[74]), "+f"(d[75]), "+f"(d[76]), "+f"(d[77]), "+f"(d[78]), "+f"(d[79]),
          "+f"(d[80]), "+f"(d[81]), "+f"(d[82]), "+f"(d[83]), "+f"(d[84]), "+f"(d[85]), "+f"(d[86]), "+f"(d[87]),
          "+f"(d[88]), "+f"(d[89]), "+f"(d[90]), "+f"(d[91]), "+f"(d[92]), "+f"(d[93]), "+f"(d[94]), "+f"(d[95])
        : "l"(da), "l"(db), "n"(TA), "n"(TB), "r"(acc));
}
template <int TA, int TB>
__device__ __forceinline__ void wgmma_n128(float (&d)[64], uint64_t da, uint64_t db, int acc = 1) {
    asm volatile("{\n.reg .pred p;\nsetp.ne.b32 p, %68, 0;\n"
        "wgmma.mma_async.sync.aligned.m64n128k16.f32.bf16.bf16 "
        "{%0, %1, %2, %3, %4, %5, %6, %7, %8, %9, %10, %11, %12, %13, %14, %15, "
        "%16, %17, %18, %19, %20, %21, %22, %23, %24, %25, %26, %27, %28, %29, %30, %31, "
        "%32, %33, %34, %35, %36, %37, %38, %39, %40, %41, %42, %43, %44, %45, %46, %47, "
        "%48, %49, %50, %51, %52, %53, %54, %55, %56, %57, %58, %59, %60, %61, %62, %63}, "
        "%64, %65, p, 1, 1, %66, %67;\n}\n"
        : "+f"(d[0]), "+f"(d[1]), "+f"(d[2]), "+f"(d[3]), "+f"(d[4]), "+f"(d[5]), "+f"(d[6]), "+f"(d[7]),
          "+f"(d[8]), "+f"(d[9]), "+f"(d[10]), "+f"(d[11]), "+f"(d[12]), "+f"(d[13]), "+f"(d[14]), "+f"(d[15]),
          "+f"(d[16]), "+f"(d[17]), "+f"(d[18]), "+f"(d[19]), "+f"(d[20]), "+f"(d[21]), "+f"(d[22]), "+f"(d[23]),
          "+f"(d[24]), "+f"(d[25]), "+f"(d[26]), "+f"(d[27]), "+f"(d[28]), "+f"(d[29]), "+f"(d[30]), "+f"(d[31]),
          "+f"(d[32]), "+f"(d[33]), "+f"(d[34]), "+f"(d[35]), "+f"(d[36]), "+f"(d[37]), "+f"(d[38]), "+f"(d[39]),
          "+f"(d[40]), "+f"(d[41]), "+f"(d[42]), "+f"(d[43]), "+f"(d[44]), "+f"(d[45]), "+f"(d[46]), "+f"(d[47]),
          "+f"(d[48]), "+f"(d[49]), "+f"(d[50]), "+f"(d[51]), "+f"(d[52]), "+f"(d[53]), "+f"(d[54]), "+f"(d[55]),
          "+f"(d[56]), "+f"(d[57]), "+f"(d[58]), "+f"(d[59]), "+f"(d[60]), "+f"(d[61]), "+f"(d[62]), "+f"(d[63])
        : "l"(da), "l"(db), "n"(TA), "n"(TB), "r"(acc));
}
template <int TB>
__device__ __forceinline__ void wgmma_rs_n128(float (&d)[64], uint32_t a0, uint32_t a1, uint32_t a2, uint32_t a3, uint64_t db) {
    asm volatile("{\n.reg .pred p;\nsetp.ne.b32 p, 1, 0;\n"
        "wgmma.mma_async.sync.aligned.m64n128k16.f32.bf16.bf16 "
        "{%0, %1, %2, %3, %4, %5, %6, %7, %8, %9, %10, %11, %12, %13, %14, %15, "
        "%16, %17, %18, %19, %20, %21, %22, %23, %24, %25, %26, %27, %28, %29, %30, %31, "
        "%32, %33, %34, %35, %36, %37, %38, %39, %40, %41, %42, %43, %44, %45, %46, %47, "
        "%48, %49, %50, %51, %52, %53, %54, %55, %56, %57, %58, %59, %60, %61, %62, %63}, "
        "{%64, %65, %66, %67}, %68, p, 1, 1, %69;\n}\n"
        : "+f"(d[0]), "+f"(d[1]), "+f"(d[2]), "+f"(d[3]), "+f"(d[4]), "+f"(d[5]), "+f"(d[6]), "+f"(d[7]),
          "+f"(d[8]), "+f"(d[9]), "+f"(d[10]), "+f"(d[11]), "+f"(d[12]), "+f"(d[13]), "+f"(d[14]), "+f"(d[15]),
          "+f"(d[16]), "+f"(d[17]), "+f"(d[18]), "+f"(d[19]), "+f"(d[20]), "+f"(d[21]), "+f"(d[22]), "+f"(d[23]),
          "+f"(d[24]), "+f"(d[25]), "+f"(d[26]), "+f"(d[27]), "+f"(d[28]), "+f"(d[29]), "+f"(d[30]), "+f"(d[31]),
          "+f"(d[32]), "+f"(d[33]), "+f"(d[34]), "+f"(d[35]), "+f"(d[36]), "+f"(d[37]), "+f"(d[38]), "+f"(d[39]),
          "+f"(d[40]), "+f"(d[41]), "+f"(d[42]), "+f"(d[43]), "+f"(d[44]), "+f"(d[45]), "+f"(d[46]), "+f"(d[47]),
          "+f"(d[48]), "+f"(d[49]), "+f"(d[50]), "+f"(d[51]), "+f"(d[52]), "+f"(d[53]), "+f"(d[54]), "+f"(d[55]),
          "+f"(d[56]), "+f"(d[57]), "+f"(d[58]), "+f"(d[59]), "+f"(d[60]), "+f"(d[61]), "+f"(d[62]), "+f"(d[63])
        : "r"(a0), "r"(a1), "r"(a2), "r"(a3), "l"(db), "n"(TB));
}
template <int TA, int TB>
__device__ __forceinline__ void wgmma_n8(float (&d)[4], uint64_t da, uint64_t db, int acc = 1) {
    asm volatile("{\n.reg .pred p;\nsetp.ne.b32 p, %8, 0;\n"
        "wgmma.mma_async.sync.aligned.m64n8k16.f32.bf16.bf16 "
        "{%0, %1, %2, %3}, "
        "%4, %5, p, 1, 1, %6, %7;\n}\n"
        : "+f"(d[0]), "+f"(d[1]), "+f"(d[2]), "+f"(d[3])
        : "l"(da), "l"(db), "n"(TA), "n"(TB), "r"(acc));
}

__device__ __forceinline__ uint32_t sub2(uint32_t a, uint32_t b) { uint32_t r; asm("sub.rn.bf16x2 %0, %1, %2;" : "=r"(r) : "r"(a), "r"(b)); return r; }

struct Roles { uint16_t v[132]; };

__global__ void __launch_bounds__(512, 1)
fused_kernel(int by_sm, const __nv_bfloat16* __restrict__ x, const __nv_bfloat16* __restrict__ wqkv, const __nv_bfloat16* __restrict__ wr,
             Scratch* const S, const char* __restrict__ wg, const char* __restrict__ wu, const char* __restrict__ wd, const char* __restrict__ wo, uint8_t* __restrict__ out,
             const __grid_constant__ Roles roles,
             const __grid_constant__ CUtensorMap mw, const __grid_constant__ CUtensorMap mx, const __grid_constant__ CUtensorMap mwo,
             const __grid_constant__ CUtensorMap mxs, const __grid_constant__ CUtensorMap mcs, const __grid_constant__ CUtensorMap mout, const __grid_constant__ CUtensorMap mgu, const __grid_constant__ CUtensorMap mwd) {
    extern __shared__ __align__(1024) uint8_t smem[];
    constexpr uint32_t sb = 1024, bars = sb + OFF_BAR, sd = sb >> 4;
    const int tid = threadIdx.x, lane = tid & 31;
    asm volatile("{\n.reg .pred p, q;\nsetp.lt.u32 p, %2, 16;\nsetp.lt.u32 q, %2, 24;\n@p prefetch.global.L2 [%0];\n@p prefetch.global.L2 [%0 + 128];\n@q prefetch.global.L2 [%1];\n}" ::
                 "l"((const char*)x + (blockIdx.x * 16 + tid - 32) % 2048 * 2048), "l"((const char*)wqkv + (blockIdx.x * 24 + tid - 32) * 128), "r"(tid - 32));
    const int warp = __shfl_sync(0xffffffffu, tid >> 5, 0);
    uint32_t smid;
    asm volatile("mov.u32 %0, %%smid;" : "=r"(smid));
    const int role = roles.v[by_sm ? smid : blockIdx.x], fb = role & 255, b = role >> 8, kc = fb >> 4, c2 = fb & 15;
    const int mt = b >> 4, nt = b & 15, hp = b & 1, cb = nt >> 1;
    const int par = mt >> 2, j0 = (mt & 3) * 256;
    uint8_t* const g_o = S->o;

    auto load_stage = [&](int p, uint32_t so, int bi) {
        const uint32_t fullA = bars + 8 * (B_FULLA + bi), fullB = bars + 8 * (B_FULLB + bi);
        mbar_expect_tx(fullA, 40960);
        tma_3d(sb + so + 16384, &mw, fullA, nt * 64, p * 64, 0);
        tma_4d(sb + so, &mx, fullA, par * 1024 + p * 64, 0, (j0 >> 5) + 4, 0);
        mbar_expect_tx(fullB, 16384);
        tma_4d(sb + so + 40960, &mx, fullB, par * 1024 + p * 64, 0, j0 >> 5, 0);
    };
    if (warp == 0 && fb < 128 && elect_one()) {
        mbar_init(bars + 8 * B_FULLA, 1); mbar_init(bars + 8 * B_FULLB, 1);
        load_stage(0, STAGE, 0);
    }
    if (fb >= 128) {
        if (fb > 128) { nap(16); TS_END(); return; }
        const uint32_t tag = (ld_rlx(&S->epoch) & 1) - 1;
        if (tid < 8) st_rlx2(&S->sel[tid], ~tag, ~tag);
        uint4 ra, rb;
#pragma unroll 1
        for (int it = 0; it < SPIN_LIMIT; it++) {
            ra = ld_rlx4(&S->rec[tid * 2]); rb = ld_rlx4(&S->rec[1024 + tid * 2]);
            if (!__any_sync(0xffffffffu, (mism(ra.x, ra.z, tag) | mism(rb.x, rb.z, tag)) & 0x8000u)) break;
        }
        __syncwarp();
        TSC(tid == 0, 31);
        sts4(sb + 1024 + tid * 16, ra.y, rb.y, ra.w, rb.w);
        uint4 k = make_uint4(ra.x, ra.z, rb.x, rb.z);
        uint32_t cand;
#pragma unroll 1
        for (int pass = 0; pass < 2; pass++) {
            const uint32_t a0 = max(k.x, k.y), a1 = min(k.x, k.y), a2 = max(k.z, k.w), a3 = min(k.z, k.w), c1 = min(a0, a2), c2 = max(a1, a3);
            k = make_uint4(max(a0, a2), max(c1, c2), min(c1, c2), min(a1, a3));
#pragma unroll
            for (int r = 0; r < 8; r++) {
                const uint32_t m = redux_max(k.x);
                if (lane == r) cand = m;
                if (k.x == m) k = make_uint4(k.y, k.z, k.w, 0);
            }
            if (pass) break;
            if (lane < 8) sts1(sb + (warp * 8 + lane) * 4, cand);
            __syncthreads();
            if (warp) { TS_END(); return; }
            k = lds4(sb + lane * 16);
            TSC(TIMING == 12 && tid == 0 && k.x != 0x12345, 40);
        }
        if (lane < 8) st_rlx2(&S->sel[lane], cand, lds1(sb + 1024 + (~cand & 0x7ffu) * 4));
        TSC(tid == 0, 20);
        TS_END();
        return;
    }
    auto ffn_w = [&](int n, int s) {
        const uint32_t dst = sb + OFF_FW + s * 16384;
        if (n < 8) {
            mbar_expect_tx(bars + 8 * (B_FFULL + s), 16384);
            tma_3d_once(dst, &mgu, bars + 8 * (B_FFULL + s), fb * 32, n * 128, 0);
        } else {
            mbar_expect_tx(bars + 8 * B_F2FULL, 16384);
            tma_2d_once(dst, &mwd, bars + 8 * B_F2FULL, c2 * 64, kc * 448 + 64 + s * 128);
            tma_2d_once(dst + 8192, &mwd, bars + 8 * B_F2FULL, c2 * 64, kc * 448 + 128 + s * 128);
        }
    };
    if (warp == 1 && elect_one()) {
#pragma unroll
        for (int i = 0; i < B_FDONE; i++)
            if (i != B_FULLA && i != B_FULLB) mbar_init(bars + 8 * i, i >= B_FFULL && i < B_F2DONE ? 2 : 1);
    }
    if (warp == 4 && elect_one()) {
#pragma unroll
        for (int i = B_EMPTY; i < NBAR; i++) mbar_init(bars + 8 * i, i < B_UPD ? 2 : i < B_AUX ? 4 : i == B_AUX ? 7 : i == B_CSDONE ? 3 : 8);
    }
    if (warp >= 8 && elect_one()) {
#pragma unroll
        for (int i = 0; i < (B_EMPTY - B_FDONE) / 8; i++) mbar_init(bars + 8 * (B_FDONE + 8 * i - 8 + warp), 1);
    }
    uint32_t epoch;
    if (warp >> 2 == 2) epoch = ld_rlx(&S->epoch);
    __syncthreads();

    if (warp >= 12) {
        reg_dec<24>();
        if (warp > 12) {
            const int p = warp - 13;
            if (p == 1) {
                float sw = 0.f;
                mbar_wait(bars + 8 * (B_ROW + 4), 0);
#pragma unroll 1
                for (int i = 0; i < 16; i++) { const uint32_t q = lds1(sb + OFF_FA + i * 128 + lane * 4); sw += bf_lo(q) + bf_hi(q); }
#pragma unroll 1
                for (int o = 1; o < 32; o <<= 1) sw += __shfl_xor_sync(0xffffffffu, sw, o);
                if (lane == 0) { sts1(sb + OFF_TAG + 4, __float_as_uint(sw)); mbar_arrive(bars + 8 * B_SW); }
            } else {
#pragma unroll 1
                for (int q = 0; q < 4; q++) {
                    nap(p ? (q ? D_R : N_ROW) : (q ? D_X : N_X));
                    if (p == 0) {
                        const __nv_bfloat16* xp = x + (size_t)((j0 + nt * 16 + (lane >> 1)) * 2 + par) * 1024 + q * 256 + (lane & 1) * 64;
                        prefetch_l2(xp); prefetch_l2(xp + 128);
                    } else if (elect_one()) {
                        mbar_expect_tx(bars + 8 * (B_ROW + q), 8192);
                        tma_3d(sb + OFF_FW + q * 8192, &mxs, bars + 8 * (B_ROW + q), 0, j0 + nt * 16, par * 16 + q * 4);
                    }
                }
                if (p == 0) nap(N_CS);
            }
            const uint32_t stg = sb + OFF_FW + 32768 + p * 4096 + lane * 16;
            float c[8];
#pragma unroll
            for (int i = 0; i < 8; i++) c[i] = 0.f;
#pragma unroll 1
            for (int n = 0; n < 10; n++) {
                const uint32_t bo = (n & 1) * 2048, bar = bars + 8 * (B_CS + 2 * p + (n & 1));
                if (n >= 2) {
                    mbar_wait(bar, ~(n >> 1) & 1);
#pragma unroll 2
                    for (int i = 0; i < 4; i++) {
                        const uint4 v = lds4(stg + bo + i * 512);
                        c[0] += bf_lo(v.x); c[1] += bf_hi(v.x); c[2] += bf_lo(v.y); c[3] += bf_hi(v.y);
                        c[4] += bf_lo(v.z); c[5] += bf_hi(v.z); c[6] += bf_lo(v.w); c[7] += bf_hi(v.w);
                    }
                    asm volatile("" :: "f"(c[7]));
                    __syncwarp();
                }
                if (n < 8 && elect_one()) {
                    mbar_expect_tx(bar, 2048);
                    tma_3d(sb + OFF_FW + 32768 + p * 4096 + bo, &mcs, bar, p * 1024 + nt * 64, mt * 8, 2 * n);
                }
            }
            sts4(stg + lane * 16, __float_as_uint(c[0]), __float_as_uint(c[1]), __float_as_uint(c[2]), __float_as_uint(c[3]));
            sts4(stg + lane * 16 + 16, __float_as_uint(c[4]), __float_as_uint(c[5]), __float_as_uint(c[6]), __float_as_uint(c[7]));
            bar_sync(13, 128);
            const uint32_t tag = lds1(sb + OFF_TAG);
            float* gcs = &S->cs[0][p * 1024 + nt * 64];
            {
                const float2 a0 = lds2f(stg - lane * 8), a1 = lds2f(stg - lane * 8 + 256), a2 = lds2f(stg - lane * 8 + 512), a3 = lds2f(stg - lane * 8 + 768);
                st_rlx2(gcs + mt * 3072 + lane * 2, tagf((a0.x + a1.x) + (a2.x + a3.x), tag), __float_as_uint((a0.y + a1.y) + (a2.y + a3.y)));
            }
            fence_async_smem();
            __syncwarp();
            if (lane == 0) mbar_arrive(bars + 8 * B_CSDONE);
            TSC(warp == 13 && lane == 0, 19);
            {
                uint4 v[4];
                const float* src = gcs + (lane >> 4) * 4 * 3072 + (lane & 15) * 4;
#pragma unroll 1
                for (int it = 0; it < SPIN_LIMIT; it++) {
#pragma unroll
                    for (int m = 0; m < 4; m++) v[m] = ld_rlx4(src + m * 3072);
                    if (!__any_sync(0xffffffffu, (mism(v[0].x, v[1].x, tag) | mism(v[2].x, v[3].x, tag)) & 1)) break;
                }
                __syncwarp();
#pragma unroll
                for (int c = 0; c < 4; c++) {
                    const float a = (__uint_as_float((&v[0].x)[c]) + __uint_as_float((&v[1].x)[c])) + (__uint_as_float((&v[2].x)[c]) + __uint_as_float((&v[3].x)[c]));
                    (&v[0].x)[c] = __float_as_uint(a + __shfl_xor_sync(0xffffffffu, a, 16));
                }
                const uint32_t ca = sb + OFF_CS + p * 384 + ((lane & 15) >> 1) * 48 + (lane & 1) * 8;
#pragma unroll 1
                for (int r = 0; r < 3; r++) {
                    const uint32_t u0 = pack_bf16(__uint_as_float(v[0].x), __uint_as_float(v[0].y)), u1 = pack_bf16(__uint_as_float(v[0].z), __uint_as_float(v[0].w));
                    sts2(ca + r * 16, u0, u1);
                    v[0].x = __float_as_uint(__uint_as_float(v[0].x) - bf_lo(u0)); v[0].y = __float_as_uint(__uint_as_float(v[0].y) - bf_hi(u0));
                    v[0].z = __float_as_uint(__uint_as_float(v[0].z) - bf_lo(u1)); v[0].w = __float_as_uint(__uint_as_float(v[0].w) - bf_hi(u1));
                }
                if (lane < 20) sts1(sb + OFF_CS + 1152 + lane * 4, 0);
                fence_async_smem();
            }
            if (p == 1) { if (lane < 2) st_rlx4(&S->hint[b][lane * 4], ~tag, ~tag, ~tag, ~tag); }
            else { st_rlx4(&S->halo[b][p * 128 + lane * 4], ~tag, ~tag, ~tag, ~tag); st_rlx4(&S->halo[b][p * 128 + 128 + lane * 4], ~tag, ~tag, ~tag, ~tag); }
            __syncwarp();
            if (lane == 0) mbar_arrive(bars + 8 * B_AUX);
            TSC(warp == 13 && lane == 0, 21);
            mbar_wait(bars + 8 * B_PART, 0);
            mbar_wait(bars + 8 * (B_EMPTY + 2), 0);
            if (p == 0) {
                if (j0) {
                    nap(N_HA);
#pragma unroll 1
                    for (int it = 0; it < SPIN_LIMIT; it++) {
                        TSC(TIMING == 15 && lane == 0 && it < 8, 40 + it);
                        if (elect_one()) { mbar_expect_tx(bars + 8 * B_CS, 2048); bulk_g2s(sb + OFF_HALO, S->halo[b - 16], 2048, bars + 8 * B_CS); }
                        mbar_wait(bars + 8 * B_CS, it & 1);
                        const uint32_t a = sb + OFF_HALO + lane * 16;
                        if (!__any_sync(0xffffffffu, (mism(lds1(a), lds1(a + 512), tag) | mism(lds1(a + 1024), lds1(a + 1536), tag)) & 1)) break;
                    }
                } else {
#pragma unroll
                    for (int c = 0; c < 4; c++) sts4(sb + OFF_HALO + c * 512 + lane * 16, 0, 0, 0, 0);
                }
                __syncwarp();
                bar_arrive(3, 64);
                TSC(TIMING >= 11 && lane == 0, 34);
            } else {
                const int w = p - 1;
                const uint8_t* osrc = g_o + (size_t)((mt * 2 + hp) * 2 + w) * 131072;
                const bool far = w > hp && j0 && lane >= 16;
                const uint32_t* hsrc = &S->hint[b & 0x70][0] + ((lane & 15) - (far ? 16 : 0)) * 8;
                if (lane == 0 && !w) st_rlx(&S->hint[b][0], tagw(now(), 1u, tag));
                uint32_t hv;
#pragma unroll 1
                for (int it = 0; it < SPIN_LIMIT; it++) {
                    hv = ld_rlx(hsrc);
                    if (!__any_sync(0xffffffffu, (hv ^ tag) & 1)) break;
                }
                TSC(TIMING == 11 && lane == 0, 32 + w);
                const uint32_t tn = __shfl_sync(0xffffffffu, hv, 0) - 0x40000000u;
                hv = redux_max(hv - tn + (far ? T_H : 0)) + tn + T_O + w * T_O1;
                mbar_wait(bars + 8 * (w ? B_AST : B_G1DONE), 0);
                if (elect_one()) {
#pragma unroll 1
                    for (int st = 0; st < 8; st++) {
                        const uint32_t full = bars + 8 * (B_OFULL + 8 * w + st);
                        if (st >= 2) mbar_wait(full + 8 * (B_DONE - B_OFULL - 2), 0);
                        if (st < 3) until(hv + (st == 2 ? T_S2 : st * T_S1));
                        TSC(st == 0, 28 + w);
                        mbar_expect_tx(full, 16384);
                        bulk_g2s(sb + (w ? OFF_O1 : OFF_O0) + (st & 1) * 16384, osrc + st * 16384, 16384, full);
                    }
                }
            }
            TS_END();
            return;
        }
        if (elect_one()) {
            auto load_wo = [&](int s, uint32_t ws) {
                mbar_expect_tx(bars + 8 * (B_WOFULL + s), 32768);
                tma_4d(ws, &mwo, bars + 8 * (B_WOFULL + s), 0, s * 8, 0, cb * 2);
            };
            uint32_t so = 2 * STAGE, ph = 1, cnt = PF_CNT << 4;
            int bi = 1, q = 0;
            mbar_expect_tx(bars + 8 * (B_ROW + 4), 2048);
            bulk_g2s(sb + OFF_FA, wr, 2048, bars + 8 * (B_ROW + 4));
            if (smem_u32(smem) != sb) __trap();
            prefetch_map(&mxs); prefetch_map(&mcs);
            const char* pf = (b < 64 ? wg : wu) + (b & 63) * 7168;
#pragma unroll 1
            for (int p = 1; p < 16; p++) {
                if (p < 3) nap(p == 1 ? N_S1 : N_S2);
                mbar_wait(bars + 8 * (B_EMPTY + bi), ph);
                load_stage(p, so, bi);
                if (p >= 2 && p < 5) {
                    const int k0 = p == 2 ? 3 : p == 3 ? K_W1 : K_W2, n = ((p == 2 ? K_W1 : p == 3 ? K_W2 : 16) - k0) * 3072;
                    if (p == 2) nap(N_W);
                    bulk_prefetch((const char*)wqkv + k0 * 393216 + b * n, n);
                }
#pragma unroll 1
                for (int e = q + (cnt & 3); q < e; q++) {
                    if (q == 16) pf = wd + mt * 7 * 131072 + nt * 8192;
                    if (q == 23) pf = wo + b * 8192;
                    bulk_prefetch(pf, q < 16 ? 7168 : 8192);
                    pf += q < 16 ? 64 * 7168 : q < 23 ? 131072 : 1048576;
                }
                cnt >>= 2;
                so = so == 2 * STAGE ? 0 : so + STAGE;
                if (++bi == 3) { bi = 0; ph ^= 1; }
            }
            TS(27);
            uint32_t ws = sb + OFF_WO0;
#pragma unroll 1
            for (int i = 0; i < 8; i++) {
                if (i < 2) {
                    mbar_wait(bars + 8 * (B_EMPTY + 1 + i), 0);
                    mbar_expect_tx(bars + 8 * B_XR, 16384);
                    tma_4d(sb + (i ? 0 : OFF_X1), &mx, bars + 8 * B_XR, par * 1024 + cb * 128 + 64 - i * 64, 0, (j0 >> 5) + hp * 4, 0);
                }
                if (i == 1) {
                    mbar_expect_tx(bars + 8 * B_F2FULL, 8192);
                    tma_2d_once(sb + OFF_F2X, &mwd, bars + 8 * B_F2FULL, c2 * 64, kc * 448);
                }
                if (i) {
                    mbar_wait(bars + 8 * (i == 1 ? B_G1DONE : i == 2 ? B_F2DONE : B_DONE - NWO + i), 0);
                    if (i > 1) mbar_wait(bars + 8 * (i == 2 ? B_OFULL + 8 : B_DONE + 8 - NWO + i), 0);
                }
                load_wo(i, ws);
                if (i == 4) prefetch_map(&mout);
                ws = wo_next(ws, sb, 0);
            }
        }
        TS_END();
    } else if (warp >= 8) {
        reg_dec<40>();
        const int p = warp - 8;
        const bool f1 = fb < 112;
        const uint32_t tag = (epoch & 1) - 1;
        {
            const int ta = tid - 256;
            if (ta < 48) st_rlx4(&S->cs[mt][(ta >> 4) * 1024 + nt * 64 + (ta & 15) * 4], ~tag, ~tag, ~tag, ~tag);
        }
        float s1 = 0.f, s2 = 0.f, sr = 0.f, sw, sh = 0.f;
        {
            const uint32_t xa = sb + OFF_FW + p * 512 + lane * 16, wa = sb + OFF_FA + (((p * 4 + (lane >> 3)) ^ lane) & 7) * 16;
            TSC(TIMING == 12 && lane == 0, 50 + p);
            mbar_wait(bars + 8 * (B_ROW + 4), 0);
            {
                float c1 = 0.f, c2 = 0.f, cr = 0.f;
#pragma unroll 1
                for (int q = 0; q < 4; q++) {
                mbar_wait(bars + 8 * (B_ROW + q), 0);
                TSC(TIMING == 12 && tid == 256 + 96, 32 + q);
                TSC(tid == 256 && q == 3, 17);
#pragma unroll
                for (int i = 0; i < 4; i++) {
                    const uint4 u = lds4(xa + q * 8192 + i * 2048), w4 = lds4(wa + q * 512 + i * 128);
                    const float a0 = bf_lo(u.x), a1 = bf_hi(u.x), a2 = bf_lo(u.y), a3 = bf_hi(u.y), a4 = bf_lo(u.z), a5 = bf_hi(u.z), a6 = bf_lo(u.w), a7 = bf_hi(u.w);
                    s1 += a0 + a1; c1 += a4 + a5; s1 += a2 + a3; c1 += a6 + a7;
                    s2 = fmaf(a0, a0, s2); c2 = fmaf(a4, a4, c2); sr = fmaf(a0, bf_lo(w4.x), sr); cr = fmaf(a4, bf_lo(w4.z), cr);
                    s2 = fmaf(a1, a1, s2); c2 = fmaf(a5, a5, c2); sr = fmaf(a1, bf_hi(w4.x), sr); cr = fmaf(a5, bf_hi(w4.z), cr);
                    s2 = fmaf(a2, a2, s2); c2 = fmaf(a6, a6, c2); sr = fmaf(a2, bf_lo(w4.y), sr); cr = fmaf(a6, bf_lo(w4.w), cr);
                    s2 = fmaf(a3, a3, s2); c2 = fmaf(a7, a7, c2); sr = fmaf(a3, bf_hi(w4.y), sr); cr = fmaf(a7, bf_hi(w4.w), cr);
                }
                }
                s1 += c1; s2 += c2; sr += cr;
            }
            mbar_wait(bars + 8 * B_SW, 0);
            sw = lds1f(sb + OFF_TAG + 4);
#pragma unroll 1
            for (int pass = 0;; pass++) {
#pragma unroll
                for (int o = 1; o < 8; o <<= 1) {
                    s1 += __shfl_xor_sync(0xffffffffu, s1, o); s2 += __shfl_xor_sync(0xffffffffu, s2, o); sr += __shfl_xor_sync(0xffffffffu, sr, o);
                }
                s1 *= 1.f / 1024.f;
                s2 = fmaf(-s1, s1, s2 * (1.f / 1024.f));
                if (!__any_sync(0xffffffffu, !pass && s1 * s1 > 256.f * s2)) break;
                sh = bf16r(s1); s1 = 0.f; s2 = 0.f; sr = 0.f;
#pragma unroll 1
                for (uint32_t o = 0; o < 2048; o = opaque(o + ((o & 12) == 12 ? 116 : 4))) {
                    const uint32_t u = lds1(xa + (o >> 7) * 2048 + (o & 12)), q = lds1(wa + o);
                    const float a0 = bf_lo(u) - sh, a1 = bf_hi(u) - sh;
                    s1 += a0 + a1; s2 = fmaf(a0, a0, fmaf(a1, a1, s2)); sr = fmaf(a0, bf_lo(q), fmaf(a1, bf_hi(q), sr));
                }
            }
        }
        const int ta = opaque(tid) - 256, lane = ta & 31, g = lane >> 2, t = lane & 3;
        {
            if ((lane & 7) == 0) {
                const int s = b * 16 + p * 4 + (lane >> 3);
                const float mb = bf16r(sh + s1);
                float den;
                asm("sqrt.approx.f32 %0, %1;" : "=f"(den) : "f"(bf16r(bf16r(s2) + 1e-5f)));
                den = bf16r(den);
                uint32_t rb = pack_bf16(fmaf(sh - mb, sw, sr) * rcp(den), 0.f);
                if (rb == 0x8000u) rb = 0;
                uint32_t ord = (rb & 0x8000u) ? (~rb & 0xffffu) : (rb | 0x8000u);
                if ((rb & 0x7fffu) > 0x7f80u) ord = 0;
                st_rlx2(&S->rec[s], (ord << 16) | (tag & 0x8000u) | (0x47ffu - (s & 1023) * 2 - par), pack_bf16(mb, den));
            }
            TSC(TIMING == 12 && lane == 0, 36 + p);
            bar_sync(12, 128);
            if (p == 1) sts1(sb + OFF_ROWMAP + lane * 4, 0xffffffffu);
            if (p == 0) {
                if (lane == 0) {
                    sts1(sb + OFF_TAG, tag);
                }
                __syncwarp();
                bar_arrive(13, 128);
            }
            TSC(ta == 0, 18);
        }
        {
            uint2 r[3];
            nap(N_GA);
            const uint2* src = &S->rec[mt * 256 + ta];
            const int l2 = ta < 8 && j0 ? -8 : 0;
#pragma unroll 1
            for (int it = 0; it < SPIN_LIMIT; it++) {
                r[0] = ld_rlx2(src + l2); r[1] = ld_rlx2(src); r[2] = ld_rlx2(src + 128);
                if (!__any_sync(0xffffffffu, (mism(r[0].x, r[1].x, tag) | (r[2].x ^ tag)) & 0x8000u)) break;
            }
#pragma unroll
            for (int n = 0; n < 3; n++)
                if (n || ta < 8) sts2(sb + OFF_STAT + (n ? n * 1024 - 960 : 0) + ta * 8, (r[n].y << 16) ^ 0x80000000u, __float_as_uint(rcp(bf_hi(r[n].y))));
        }
        __syncwarp();
        if (lane == 0) mbar_arrive(bars + 8 * B_AUX);
        TSC(ta == 0, 30);
        if (p == 1) nap(N_F1);
        if (f1 && p < 2 && elect_one()) ffn_w(p, p);
        uint2 sel;
#pragma unroll 1
        for (int it = 0; it < SPIN_LIMIT; it++) {
            sel = ld_rlx2(&S->sel[lane & 7]);
            if (!__any_sync(0xffffffffu, (sel.x ^ tag) & 0x8000u)) break;
            __nanosleep(POLL_NS);
        }
        TSC(ta == 0, 26);
        if (b == 0 && ta == 0) st_rlx(&S->epoch, epoch + 1);
        {
            const __nv_bfloat16* xp = x + (~sel.x & 0x7ffu) * 1024 + (lane >> 3) * 8;
            const uint32_t mb = __byte_perm(sel.y, 0, 0x1010);
            if (p >= 2) nap(N_A2);
#pragma unroll 1
            for (int n = p; n < (f1 ? 8 : 0); n += 4) {
                uint4 v[4];
#pragma unroll
                for (int c = 0; c < 4; c++) v[c] = ldg_nc(xp + n * 128 + c * 32);
                const int s = n % 3;
                if (n >= 2) {
                    mbar_wait(bars + 8 * (n == 2 ? B_CSDONE : B_FDONE + n - 3), 0);
                    if (elect_one()) ffn_w(n & 7, s);
                }
#pragma unroll
                for (int c = 0; c < 4; c++) sts4(sb + OFF_FA + s * 2048 + c * 512 + lane * 16, sub2(v[c].x, mb), sub2(v[c].y, mb), sub2(v[c].z, mb), sub2(v[c].w, mb));
                fence_async_smem();
                __syncwarp();
                if (lane == 0) mbar_arrive(bars + 8 * (B_FFULL + s));
                TSC(TIMING == 12 && lane == 0, 41 + n);
            }
            if (p < 3) {
                mbar_wait(bars + 8 * B_CSDONE, 0);
                mbar_wait(bars + 8 * (f1 ? B_FDONE + 5 + p : B_PART), 0);
                if (elect_one()) ffn_w(8, p ? p - 1 : 2);
            }
        }
        const bool hw = f1 && (p == 0 || p == 3);
        if (hw) st_rlx4(&S->h[fb * 128 + (p & 1) * 64 + (lane & 15) * 4], ~tag, ~tag, ~tag, ~tag);
        st_rlx4(&S->ypart[kc][ta >> 4][c2 * 64 + (ta & 15) * 4], ~tag, ~tag, ~tag, ~tag);
        const float ri[2] = {rcp(bf_hi(__shfl_sync(0xffffffffu, sel.y, 2 * t))), rcp(bf_hi(__shfl_sync(0xffffffffu, sel.y, 2 * t + 1)))};
        mbar_wait(bars + 8 * B_PART, 0);
        if (hw) {
            const uint32_t pa = sb + OFF_FA + (ta & 63) * 16, go = wu < wg ? 1024 : 0;
            const float4 g0 = lds4f(pa + go), g1 = lds4f(pa + 2048 + go), u0 = lds4f(pa + (go ^ 1024)), u1 = lds4f(pa + 2048 + (go ^ 1024));
            float hv[4];
#pragma unroll
            for (int c = 0; c < 4; c++) {
                const float ga = bf16r(((&g0.x)[c] + (&g1.x)[c]) * ri[c & 1]), up = bf16r(((&u0.x)[c] + (&u1.x)[c]) * ri[c & 1]);
                hv[c] = bf16r(ga * sigmoidf(ga)) * up;
            }
#pragma unroll
            for (int hh = 0; hh < 2; hh++) {
                const float o = __shfl_xor_sync(0xffffffffu, (g & 1) ? hv[2 * hh] : hv[2 * hh + 1], 4);
                st_rlx(&S->h[(fb * 4 + (p & 1) * 2 + hh) * 32 + (2 * t + (g & 1)) * 4 + (g >> 1)],
                       tagw((g & 1) ? pack_bf16(o, hv[2 * hh + 1]) : pack_bf16(hv[2 * hh], o), g < 2, tag));
            }
            TSC(ta == 0, 22);
        }
        {
            uint4 hq[4];
            const uint32_t* hp4 = S->h + kc * 1792 + ta * 4;
#pragma unroll 1
            for (int it = 0; it < SPIN_LIMIT; it++) {
#pragma unroll
                for (int n = 0; n < 4; n++) hq[n] = ld_rlx4(hp4 + (n < 3 ? n * 512 : p < 2 ? 1536 : 0));
                if (!__any_sync(0xffffffffu, (mism(hq[0].x, hq[1].x, tag) | mism(hq[2].x, hq[3].x, tag)) & 1)) break;
            }
            mbar_wait(bars + 8 * B_G1DONE, 0);
            bar_sync(12, 128);
#pragma unroll
            for (int n = 0; n < 4; n++) sts4(sb + OFF_FA + ta * 16 + (n < 3 ? n * 2048 : p < 2 ? 6144 : 0), hq[n].x, hq[n].y, hq[n].z, hq[n].w);
            fence_async_smem();
            bar_sync(12, 128);
            TSC(ta == 0, 25);
            mbar_wait(bars + 8 * B_F2FULL, 0);
            mbar_wait(bars + 8 * B_AST, 0);
            float acc[4] = {0.f, 0.f, 0.f, 0.f};
            uint32_t da = sd + dlo(OFF_F2X, 8192), db = sd + dlo(OFF_FA, 128);
#pragma unroll 1
            for (int q = 0; q < 7; q++) {
                wg_fence();
#pragma unroll
                for (int j = 0; j < 4; j++) wgmma_n8<1, 0>(acc, mkdesc(da + j * 128, dhi(1024, 1)), mkdesc(db + j * 16, dhi(128, 0)));
                wg_commit();
                if (q == 2) mbar_wait(bars + 8 * B_ATT, 0);
                da = sd + dlo(OFF_FW, 8192) + q * 512; db += 64;
            }
            wg_wait<0>();
            if (ta == 0) mbar_arrive(bars + 8 * B_F2DONE);
#pragma unroll
            for (int c = 0; c < 4; c++) st_rlx(&S->ypart[kc][2 * t + (c & 1)][c2 * 64 + p * 16 + (c >> 1) * 8 + g], tagf(acc[c], tag));
            TSC(ta == 0, 23);
            bar_sync(12, 128);
        }
#pragma unroll 1
        for (int j = 2 * p; j < 2 * p + 2; j++) {
            const uint32_t kj = __shfl_sync(0xffffffffu, sel.x, j);
            const int row = 0x7ff - (kj & 0x7ffu), jj = (row >> 1) - j0 - hp * 128;
            float a0 = 0.f, a1 = 0.f, a2 = 0.f, a3 = 0.f, sig = 0.f;
            if ((row & 1) == par && jj >= 0 && jj < 128) {
                sig = bf16r(sigmoidf(__uint_as_float(((int)kj < 0 ? kj ^ 0x80000000u : ~kj) & 0xffff0000u)));
#pragma unroll 1
                for (int hh = 0; hh < 8; hh += 4) {
                    uint4 v[4];
#pragma unroll 1
                    for (int it = 0; it < SPIN_LIMIT; it++) {
#pragma unroll
                        for (int m = 0; m < 4; m++) v[m] = ld_rlx4(&S->ypart[hh + m][j][cb * 128 + lane * 4]);
                        if (!__any_sync(0xffffffffu, (mism(v[0], tag) | mism(v[1], tag) | mism(v[2], tag) | mism(v[3], tag)) & 1)) break;
                    }
#pragma unroll
                    for (int m = 0; m < 4; m++) { a0 += __uint_as_float(v[m].x); a1 += __uint_as_float(v[m].y); a2 += __uint_as_float(v[m].z); a3 += __uint_as_float(v[m].w); }
                }
                asm volatile("st.shared.u8 [%0], %1;" ::"r"(sb + OFF_ROWMAP + jj), "r"(j) : "memory");
            }
            sts2(sb + OFF_FA + (lane >> 1) * 128 + j * 16 + (lane & 1) * 8, pack_bf16(bf16r(a0) * sig, bf16r(a1) * sig), pack_bf16(bf16r(a2) * sig, bf16r(a3) * sig));
        }
        fence_async_smem();
        __syncwarp();
        if (lane == 0) mbar_arrive(bars + 8 * B_UPD);
        TSC(ta == 0, 24);
        TS_END();
    } else {
        reg_inc<224>();
        const int w = warp >> 2, wi = warp & 3, tw = (1 - w) * 4 + wi;
        const bool elect = (tid & 127) == 0;
        const uint32_t ln = opaque(lane), g = ln >> 2, t = ln & 3;
        uint32_t tag, ow[8][4];
        auto store_o = [&](int f0, int f1) {
            uint8_t* ob = g_o + (size_t)((mt * 2 + 1 - w) * 2 + 1 - (wi >> 1)) * 131072 + nt * 1024 + (wi & 1) * 512 + ln * 4;
#pragma unroll
            for (int f = f0; f < f1; f++)
#pragma unroll
                for (int i = 3; i >= 0; i--)
                    st_rlx(ob + f * 16384 + i * 128, ow[f][i]);
        };
        {
            float acc[2][96];
            const uint32_t sta = opaque(sb + OFF_STAT + tw * 256 + 64 + g * 8);
            {
                float fa[4] = {0.f, 0.f, 0.f, 0.f};
                uint32_t so = STAGE >> 4, bo = bars, ph = 0;
                const uint32_t dx0 = sd + dlo(w ? 40960 : 0, 16), dw0 = sd + dlo(16384, 8192);
                int p = 0;
                if (w) bar_arrive(1, 256);
                uint32_t fm = fb < 112 ? F1_MASK >> (16 * w) : 0u, fph = 0, fd = bars + 8 * (B_FDONE + w);
                int fs = w;
#pragma unroll 1
                for (; p < 16; p++) {
                    mbar_wait(bo + 8 * B_FULLA, ph);
                    if (w) mbar_wait(bo + 8 * B_FULLB, ph);
                    TSC(elect && p == 0, 1 + 8 * w);
                    TSC(TIMING == 9 && elect && p >= 9 && p < 14, 32 + (p - 9) * 6 + w * 3);
                    bar_sync(1 + w, 256);
                    TSC(TIMING == 1 && tid == 0, 32 + p);
                    if (p == 15) {
                        wg_fence();
                        wgmma_n192<0, 1>(acc[1], mkdesc(sd + dlo(OFF_MEAN + 1024, 0) + w * 128, dhi(128, 0)), mkdesc(sd + dlo(OFF_CS, 0), dhi(48, 0)));
                        wgmma_n192<0, 1>(acc[0], mkdesc(sd + dlo(OFF_MEAN, 0) + w * 128, dhi(128, 0)), mkdesc(sd + dlo(OFF_CS, 0), dhi(48, 0)));
                        wg_commit();
                    }
                    wg_fence();
#pragma unroll
                    for (int h = 1; h >= 0; h--) {
#pragma unroll
                        for (int k = 0; k < 4; k++) wgmma_n192<0, 1>(acc[h], mkdesc(dx0 + so + h * 512 + k * 2, dhi(1024, 1)), mkdesc(dw0 + so + k * 128, dhi(1024, 1)), k ? 1 : p);
                        wg_commit();
                    }
                    if (fm & 1) {
                        mbar_wait(bars + 8 * (B_FFULL + fs), fph);
                        TSC(TIMING == 9 && elect && p >= 9, 33 + (p - 9) * 6 + w * 3);
                        wg_fence();
#pragma unroll
                        for (int j = 0; j < 8; j++)
                            wgmma_n8<1, 0>(fa, mkdesc(sd + dlo(OFF_FW, 8192) + fs * 1024 + j * 64, dhi(512, 2)), mkdesc(sd + dlo(OFF_FA, 128) + fs * 128 + j * 16, dhi(128, 0)));
                        wg_commit();
                    }
                    bar_arrive(2 - w, 256);
                    if (p == 15) break;
                    wg_wait<0>();
                    TSC(TIMING == 9 && elect && p >= 9 && p < 14, 34 + (p - 9) * 6 + w * 3);
                    if (wi == 0 && elect_one()) { mbar_arrive(bo + 8 * B_EMPTY); if (fm & 1) mbar_arrive(fd); }
                    so = so == 2 * (STAGE >> 4) ? 0 : so + (STAGE >> 4);
                    bo += 8;
                    if (bo == bars + 24) { bo = bars; ph ^= 1; }
                    if (fm & 1) { fd += 16; fs += 2; if (fs >= 3) { fs -= 3; fph ^= 1; } }
                    fm >>= 1;
                    if (p == P_PART) {
                        if (fb < 112) sts4(sb + OFF_FA + tid * 16, __float_as_uint(fa[0]), __float_as_uint(fa[1]), __float_as_uint(fa[2]), __float_as_uint(fa[3]));
                        __syncwarp();
                        if (lane == 0) mbar_arrive(bars + 8 * B_PART);
                    }
                    if (p != 14) continue;
                    mbar_wait(bars + 8 * B_AUX, 0);
                    mbar_wait(bars + 8 * (B_EMPTY + 1), 0);
                    const uint32_t hm = __float_as_uint(0.5f * lds1f(sb + OFF_STAT + 64 + tw * 256 + ln * 8)) >> 16;
                    sts4(sb + OFF_MEAN + w * 2048 + wi * 256 + (ln >> 4) * 1024 + (ln & 15) * 16, hm * 0x10001u, hm, 0, 0);
                    fence_async_smem();
                }
            }
            TSC(TIMING != 14 && elect, 2 + 8 * w);

            tag = lds1(sb + OFF_TAG);
            mbar_wait(bars + 8 * (B_EMPTY + 2), 0);
            wg_wait<1>();
#pragma unroll
            for (int i = 0; i < 96; i++) asm volatile("" : "+f"(acc[1][i]) :: "memory");
            uint32_t pk[4][24];
            const uint32_t hm = tw == 7 ? ~ln & 1 : 0;
            auto np = [&](int i, int j) {
                const float* a = &acc[i >> 1][4 * j + 2 * (i & 1)];
                pk[i][j] = pack_bf16(a[0], a[1]);
                if (j >= 16) pk[i][j] = movm(pk[i][j]);
                if (i == 3 && j >= 8 && !(j & 1)) pk[i][j] = tagw(pk[i][j], hm, tag);
            };
            const uint32_t ha = sb + OFF_HALO + tw * 2048 + ln * 8;
#pragma unroll
            for (int j = 8; j < 24; j += 2) {
                np(3, j); np(3, j + 1);
                sts2(ha + 2048 + (j - 8) * 128, pk[3][j], pk[3][j + 1]);
                asm volatile("{\n.reg .pred p;\nsetp.eq.u32 p, %3, 7;\n@p st.relaxed.gpu.global.v2.u32 [%0], {%1,%2};\n}" ::"l"((char*)&S->halo[b][ln * 2] + (j - 8) * 128),
                             "r"(pk[3][j]), "r"(pk[3][j + 1]), "r"(tw) : "memory");
            }
            bar_arrive(4 + tw, 64);
            TSC(TIMING == 15 && ln == 0 && tw == 7, 39);
            TSC(TIMING == 8 && ln == 0 && wi == 1, 32 + 8 * w);
            const bool u0 = 2 * t > g, u1 = 2 * t + 1 > g;
            const uint32_t mU = (u0 ? 0xffffu : 0u) | (u1 ? 0xffff0000u : 0u);
            uint2 hl[8];
            float rk[4][2], fq[4][2];
            auto factors = [&]() {
                const uint32_t ka = sb + OFF_STAT + tw * 256 + 4 + t * 16, k0 = opaque(ka + (u0 ? 0 : 64)), k1 = opaque(ka + (u1 ? 8 : 72));
#pragma unroll
                for (int i = 0; i < 4; i++) {
                    const float rq = lds1f(sta + i * 64 + 4) * (0.17677669529663687f * 1.4426950408889634f);
                    rk[i][0] = lds1f(k0 + i * 64); rk[i][1] = lds1f(k1 + i * 64);
                    fq[i][0] = rq * rk[i][0]; fq[i][1] = rq * rk[i][1];
                }
            };
#pragma unroll
            for (int jj = 0; jj < 12; jj++) { const int j = (jj >> 2) * 8 + (jj & 3); np(2, j); if (j < 8) np(3, j); }
            factors();
            wg_wait<0>();
#pragma unroll
            for (int i = 0; i < 96; i++) asm volatile("" : "+f"(acc[0][i]) :: "memory");
            if (elect) mbar_arrive(bars + 8 * B_G1DONE);
            const float mask = tw == 0 && j0 == 0 ? -INFINITY : 0.f;
#pragma unroll
            for (int hd = 0; hd < 2; hd++) {
#pragma unroll
                for (int jj = 0; jj < 12; jj++) {
                    const int j = (jj >> 2) * 8 + hd * 4 + (jj & 3);
                    np(0, j); np(1, j);
                    if (j & 4)
                    { np(2, j); if (j < 8) np(3, j); }
                }
                if (hd == 0) mbar_wait(bars + 8 * B_G1DONE, 0);
                float s[2][3][4];
#pragma unroll
                for (int h = 1; h >= 0; h--)
#pragma unroll
                    for (int n = 2; n >= 0; n--) {
                        if (h == 0 && n == 0 && hd == 0) {
                            TSC(TIMING == 8 && ln == 0 && wi == 1 && s[1][0][0] + s[0][1][0] != 123.456f, 33 + 8 * w);
                            bar_sync(3 + tw, 64);
#pragma unroll
                            for (int c = 0; c < 8; c++) hl[c] = lds2(ha + c * 256);
                        }
                        const int kg = 2 * h - 1 + n;
                        s[h][n][0] = s[h][n][1] = kg < 0 ? mask : 0.f; s[h][n][2] = s[h][n][3] = 0.f;
#pragma unroll
                        for (int ks = 0; ks < 2; ks++) {
                            const int q = hd * 4 + 2 * ks;
                            const uint32_t* k = kg < 0 ? &hl[hd * 2 + ks].x : &pk[kg < 0 ? 0 : kg][8 + q];
                            mma16816(s[h][n], pk[2 * h][q], pk[2 * h + 1][q], pk[2 * h][q + 1], pk[2 * h + 1][q + 1], k[0], k[1]);
                        }
                    }
                uint32_t pp[4], pc[4];
#pragma unroll
                for (int i = 0; i < 4; i++) {
                    const float* sp = &s[i >> 1][i & 1][2 * (i & 1)];
                    const float* sc = &s[i >> 1][(i & 1) + 1][2 * (i & 1)];
                    float a0 = (u0 ? sp[0] : sc[0]) * fq[i][0], a1 = (u1 ? sp[1] : sc[1]) * fq[i][1];
                    float m = fmaxf(a0, a1);
                    m = fmaxf(m, __shfl_xor_sync(0xffffffffu, m, 1));
                    m = fmaxf(m, __shfl_xor_sync(0xffffffffu, m, 2));
                    a0 = ex2(a0 - m); a1 = ex2(a1 - m);
                    float sum = a0 + a1;
                    sum += __shfl_xor_sync(0xffffffffu, sum, 1);
                    sum += __shfl_xor_sync(0xffffffffu, sum, 2);
                    const float inv = rcp(sum);
                    const uint32_t pw = pack_bf16(a0 * rk[i][0] * inv, a1 * rk[i][1] * inv);
                    pp[i] = pw & mU; pc[i] = pw & ~mU;
                }
                TSC(TIMING == 8 && ln == 0 && wi == 1 && pp[0] + pp[3] != 0x12345, 34 + 2 * hd + 8 * w);
#pragma unroll
                for (int fh = 0; fh < 2; fh++)
#pragma unroll
                    for (int i = 0; i < 4; i++) {
                        const int v = 16 + hd * 4 + 2 * fh;
                        const uint32_t* vp = i ? &pk[i ? i - 1 : 0][v] : &hl[4 + hd * 2 + fh].x;
                        float o[4] = {0.f, 0.f, 0.f, 0.f};
                        if (i & 1) mma16816(o, vp[0], vp[1], pk[i][v], pk[i][v + 1], pp[i], pc[i]);
                        else { mma1688(o, pk[i][v], pk[i][v + 1], pc[i]); mma1688(o, vp[0], vp[1], pp[i]); }
                        const uint32_t tm = (ln & 7) == (nt & 3) * 2 + (i & 1);
                        ow[hd * 4 + 2 * fh][i] = tagw(pack_bf16(o[0], o[1]), tm, tag); ow[hd * 4 + 2 * fh + 1][i] = tagw(pack_bf16(o[2], o[3]), tm, tag);
                    }
                store_o(hd ? ST_A : 0, hd ? ST_B : ST_A);
                TSC(TIMING == 11 && !hd && ln == 0 && wi == 3, 45 + w);
                if (!hd) mbar_arrive_after(bars + 8 * B_AST, ln, hl[2].x ^ hl[3].x ^ hl[5].x ^ hl[6].x ^ hl[7].x);
                mbar_wait(bars + 8 * B_G1DONE, 0);
                if (hd && ln == 0) mbar_arrive(bars + 8 * B_ATT);
                TSC(TIMING != 14 && elect && hd == 0, 3 + 8 * w);
                TSC(TIMING == 8 && ln == 0 && wi == 1, 35 + 2 * hd + 8 * w);
            }
        }
        TSC(TIMING != 14 && elect, 4 + 8 * w);
        float acc2[64];
        TSC(TIMING != 14 && elect, 5 + 8 * w);
        {
            const uint32_t ring = sb + (w ? OFF_O1 : OFF_O0), da0 = (ring >> 4) + dlo(0, 1024);
            const uint32_t l2 = opaque(ln), chk = ring + wi * 256 + (l2 >> 3) * 1032 + ((l2 >> 2) & 1) * 132 + (l2 & 3) * 32;
            const uint32_t xs = sb + (wi & 1) * 8192 + (tw >> 1) * 2048, mad = xs + (l2 & 15) * 128;
            auto residual = [&](float* base) {
                const uint32_t sta = sb + OFF_STAT + (8 + hp * 128 + tw * 16 + g) * 8;
                const float2 s0 = lds2f(sta), s1 = lds2f(sta + 64);
                const float m0 = s0.x * s0.y, r0 = 1.f + s0.y, m1 = s1.x * s1.y, r1 = 1.f + s1.y;
                mbar_wait(bars + 8 * B_XR, 0);
#pragma unroll
                for (int j = 0; j < 16; j += 2) {
                    uint32_t xr[4];
                    asm volatile("ldmatrix.sync.aligned.m8n8.x4.shared.b16 {%0,%1,%2,%3}, [%4];" : "=r"(xr[0]), "=r"(xr[1]), "=r"(xr[2]), "=r"(xr[3])
                                 : "r"(mad + (j >> 3) * OFF_X1 + ((((j & 7) + (l2 >> 4)) ^ (l2 & 7)) << 4)) : "memory");
#pragma unroll
                    for (int c = 0; c < 4; c++) {
                        base[4 * j + 2 * c] = fmaf(bf_lo(xr[c]), c & 1 ? r1 : r0, c & 1 ? m1 : m0); base[4 * j + 2 * c + 1] = fmaf(bf_hi(xr[c]), c & 1 ? r1 : r0, c & 1 ? m1 : m0);
                        asm volatile("" : "+f"(base[4 * j + 2 * c]), "+f"(base[4 * j + 2 * c + 1]) :: "memory");
                    }
                }
            };
            residual(acc2);
            uint32_t db = sd + dlo(OFF_WO0, 16384);
#pragma unroll 1
            for (int s = 0; s < 8; s++) {
                const uint32_t ro = (s & 1) * 16384;
                mbar_wait(bars + 8 * (B_WOFULL + s), 0);
                TSC(TIMING == 11 && tid == 0 && s == 0, 43);
                mbar_wait(bars + 8 * (B_OFULL + s) + 64 * w, 0);
                TSC(TIMING == 11 && tid == 0 && s == 0, 44);
#pragma unroll 1
                for (int it = 0; __any_sync(0xffffffffu, (mism(lds1(chk + ro), lds1(chk + ro + 4096), tag) | mism(lds1(chk + ro + 8192), lds1(chk + ro + 12288), tag)) & 1) && it < SPIN_LIMIT; it++) {
                    NRETRY();
                    const uint32_t fo = wi * 256 + (l2 >> 4) * 1024 + (l2 & 15) * 16;
                    uint4 v[8];
#pragma unroll
                    for (int c = 0; c < 8; c++) v[c] = ld_rlx4(g_o + (size_t)(((mt * 2 + hp) * 2 + w) * 8 + s) * 16384 + fo + c * 2048);
#pragma unroll
                    for (int c = 0; c < 8; c++) sts4(ring + ro + fo + c * 2048, v[c].x, v[c].y, v[c].z, v[c].w);
                    fence_async_smem();
                    __syncwarp();
                }
                if (s == 0) mbar_wait(bars + 8 * B_ATT, 0);
                if (s <= 8 - LAST) bar_sync(1 + w, 256);
                TSC(elect && s == 0, 6 + 8 * w);
                TSC(TIMING == 2 && elect, 32 + 16 * w + s);
                wg_fence();
#pragma unroll
                for (int k = 0; k < 8; k++)
                    wgmma_n128<1, 1>(acc2, mkdesc(da0 + (ro >> 4) + k * 128, dhi(128, 0)), mkdesc(db + k * 128, dhi(1024, 1)));
                wg_commit();
                db = wo_next(db, sd + dlo(0, 16384), 4);
                if (s < 8 - LAST) {
                    bar_arrive(2 - w, 256);
                    if (s == 0) store_o(ST_B, 8);
                    wg_wait<0>();
                    if (elect) mbar_arrive(bars + 8 * (B_DONE + s) + 64 * w);
                }
            }
            mbar_wait(bars + 8 * B_UPD, 0);
            int sl0, sl1;
            asm volatile("ld.shared.s8 %0, [%1];" : "=r"(sl0) : "r"(sb + OFF_ROWMAP + tw * 16 + g) : "memory");
            asm volatile("ld.shared.s8 %0, [%1];" : "=r"(sl1) : "r"(sb + OFF_ROWMAP + tw * 16 + 8 + g) : "memory");
            const uint32_t e0 = (sl0 >> 1) == (int)t ? 0x3f80u << ((sl0 & 1) * 16) : 0u, e1 = (sl1 >> 1) == (int)t ? 0x3f80u << ((sl1 & 1) * 16) : 0u;
            if (__any_sync(0xffffffffu, lds1(sb + OFF_ROWMAP + (1 - w) * 64 + (l2 & 15) * 4) != 0xffffffffu)) {
                wg_fence();
                wgmma_rs_n128<1>(acc2, e0, e1, 0u, 0u, mkdesc(sd + dlo(OFF_FA, 0), dhi(128, 0)));
                wg_commit();
            }
            bar_arrive(2 - w, 256);
            wg_wait<0>();
#pragma unroll
            for (int i = 0; i < 64; i++) asm volatile("" : "+f"(acc2[i]) :: "memory");
            TSC(elect, 7 + 8 * w);
#pragma unroll
            for (int j = 0; j < 16; j += 2) {
                const int ch = (j & 7) + (l2 >> 4);
                asm volatile("stmatrix.sync.aligned.m8n8.x4.shared.b16 [%0], {%1,%2,%3,%4};" ::"r"(mad + (j >> 3) * OFF_X1 + ((ch ^ (l2 & 7)) << 4)),
                             "r"(pack_bf16(acc2[4 * j], acc2[4 * j + 1])), "r"(pack_bf16(acc2[4 * j + 2], acc2[4 * j + 3])),
                             "r"(pack_bf16(acc2[4 * j + 4], acc2[4 * j + 5])), "r"(pack_bf16(acc2[4 * j + 6], acc2[4 * j + 7])) : "memory");
                if (TAIL && (TAIL == 2 || w) && (j & 7) == 6) {
                    __syncwarp();
                    uint8_t* op = out + (size_t)(j0 + hp * 128 + tw * 16 + (l2 >> 3)) * 4096 + par * 2048 + cb * 256 + (j >> 3) * 128;
#pragma unroll
                    for (int c = 0; c < 4; c++) {
                        const uint4 v = lds4(xs + (j >> 3) * OFF_X1 + c * 512 + l2 * 16);
                        *(uint4*)(op + c * 4 * 4096 + (((l2 ^ (c * 4 + (l2 >> 3))) & 7) << 4)) = v;
                    }
                } else if ((j & 7) == 6) {
                    fence_async_smem();
                    __syncwarp();
                    if (ln == 0) tma_store_2d(&mout, xs + (j >> 3) * OFF_X1, par * 1024 + cb * 128 + (j >> 3) * 64, j0 + hp * 128 + tw * 16);
                }
            }
            if (ln == 0) asm volatile("cp.async.bulk.commit_group;\ncp.async.bulk.wait_group.read 0;" ::: "memory");
            TSC(elect, 8 + 8 * w);
            TS_END();
        }
    }
}

typedef CUresult (*EncodeFn)(CUtensorMap*, CUtensorMapDataType, cuuint32_t, void*, const cuuint64_t*, const cuuint64_t*, const cuuint32_t*,
                             const cuuint32_t*, CUtensorMapInterleave, CUtensorMapSwizzle, CUtensorMapL2promotion, CUtensorMapFloatOOBfill);

CUtensorMap make_map(EncodeFn fn, const void* base, int rank, const cuuint64_t* dims, const cuuint64_t* strides, const cuuint32_t* box,
                     CUtensorMapSwizzle swz = CU_TENSOR_MAP_SWIZZLE_128B, CUtensorMapL2promotion pro = CU_TENSOR_MAP_L2_PROMOTION_L2_256B) {
    CUtensorMap m;
    cuuint32_t es[5] = {1, 1, 1, 1, 1};
    fn(&m, CU_TENSOR_MAP_DATA_TYPE_BFLOAT16, rank, (void*)base, dims, strides, box, es, CU_TENSOR_MAP_INTERLEAVE_NONE,
       swz, pro, CU_TENSOR_MAP_FLOAT_OOB_FILL_NONE);
    return m;
}

}

extern "C" void kernel_launch(void* const* d_in, const int* in_sizes, int n_in, void* d_out, int out_size) {
    (void)in_sizes; (void)n_in; (void)out_size;
    const __nv_bfloat16* x = (const __nv_bfloat16*)d_in[0];
    const __nv_bfloat16* wqkv = (const __nv_bfloat16*)d_in[1];
    const char* wo = (const char*)d_in[2];
    const __nv_bfloat16* wr = (const __nv_bfloat16*)d_in[4];
    const char* wg = (const char*)d_in[5];
    const char* wu = (const char*)d_in[6];
    const char* wd = (const char*)d_in[7];
    static EncodeFn fn = nullptr;
    static int by_sm = 0;
    static Scratch* scr = nullptr;
    if (!fn) {
        void* p = nullptr; cudaDriverEntryPointQueryResult q;
        cudaGetDriverEntryPoint("cuTensorMapEncodeTiled", &p, cudaEnableDefault, &q);
        fn = (EncodeFn)p;
        cudaFuncSetAttribute(fused_kernel, cudaFuncAttributeMaxDynamicSharedMemorySize, SMEM_LAUNCH);
        cudaGetSymbolAddress((void**)&scr, g_scr);
        int dev = 0, sms = 0;
        cudaGetDevice(&dev);
        cudaDeviceGetAttribute(&sms, cudaDevAttrMultiProcessorCount, dev);
        by_sm = sms == 132;
    }
    Roles roles;
    for (int i = 0; i < 132; i++) {
        const int T = i >> 1, T8 = T < 32 ? T : T + 1 + (T - 32) / 7, fb = (T < 60 ? (~T8 & 7) * 8 + (T8 >> 3) : T < 62 ? T + 4 : T - 2) * 2 + (i & 1);
        roles.v[i] = fb | ((fb & ~31) | (fb & 1) << 4 | (fb & 31) >> 1) << 8;
    }
    const cuuint64_t xd[4] = {2048, 16, 32, 2}, xs[3] = {4096, 131072, 65536};
    const cuuint32_t xb[4] = {64, 16, 4, 2};
    const cuuint64_t wdm[3] = {1024, 1024, 3}, wst[2] = {6144, 2048};
    const cuuint32_t wb[3] = {64, 64, 3};
    const cuuint64_t od[4] = {64, 64, 16, 16}, ost[3] = {2048, 131072, 128};
    const cuuint32_t ob[4] = {64, 8, 16, 2};
    const cuuint64_t yd[2] = {2048, 1024}, yst[1] = {4096};
    const cuuint32_t yb[2] = {64, 16};
    const cuuint64_t sd[3] = {64, 1024, 32}, sst[2] = {4096, 128};
    const cuuint32_t sbx[3] = {64, 16, 4};
    CUtensorMap mxs = make_map(fn, x, 3, sd, sst, sbx);
    const cuuint64_t cd[3] = {3072, 64, 16}, cst[2] = {6144, 393216};
    const cuuint32_t cbx[3] = {64, 8, 2};
    CUtensorMap mcs = make_map(fn, wqkv, 3, cd, cst, cbx, CU_TENSOR_MAP_SWIZZLE_NONE);
    CUtensorMap mx = make_map(fn, x, 4, xd, xs, xb), mw = make_map(fn, wqkv, 3, wdm, wst, wb);
    CUtensorMap mwo = make_map(fn, wo, 4, od, ost, ob), mout = make_map(fn, d_out, 2, yd, yst, yb);
    const cuuint64_t gd[3] = {3584, 1024, 2}, gst[2] = {7168, (cuuint64_t)(wu < wg ? wg - wu : wu - wg)};
    const cuuint32_t gb[3] = {32, 128, 2};
    const cuuint64_t dd[2] = {1024, 3584}, dst[1] = {2048};
    const cuuint32_t db[2] = {64, 64};
    CUtensorMap mgu = make_map(fn, wu < wg ? wu : wg, 3, gd, gst, gb, CU_TENSOR_MAP_SWIZZLE_64B, CU_TENSOR_MAP_L2_PROMOTION_L2_128B);
    CUtensorMap mwd = make_map(fn, wd, 2, dd, dst, db, CU_TENSOR_MAP_SWIZZLE_128B, CU_TENSOR_MAP_L2_PROMOTION_L2_128B);
    fused_kernel<<<132, 512, SMEM_LAUNCH, cudaStreamPerThread>>>(by_sm, x, wqkv, wr, scr, wg, wu, wd, wo, (uint8_t*)d_out, roles, mw, mx, mwo, mxs, mcs, mout, mgu, mwd);
}
```

```cpp
#include <cuda_runtime.h>
#include <cuda.h>
#include <cuda_bf16.h>
#include <stdint.h>

namespace {

constexpr int STAGE = 57344;
constexpr int OFF_FW = 3 * STAGE;
constexpr int OFF_FA = OFF_FW + 49152;
constexpr int OFF_CS = OFF_FA + 6144;
constexpr int OFF_STAT = OFF_CS + 1232;
constexpr int OFF_ROWMAP = OFF_STAT + 2112;
constexpr int OFF_TAG = OFF_ROWMAP + 128;
constexpr int OFF_BAR = OFF_TAG + 8;
constexpr int OFF_F2X = 16384, OFF_HALO = 24576, OFF_O1 = 24576, OFF_O0 = 90112, NWO = 3, OFF_MEAN = 2 * STAGE, OFF_X1 = 2 * STAGE + 8192;
constexpr int OFF_WO0 = OFF_X1 + 16384, OFF_WO1 = STAGE, OFF_WO2 = OFF_FW;
static_assert(OFF_WO0 + 32768 == OFF_FW && OFF_WO1 + 32768 == OFF_O0 && OFF_O0 + 32768 == OFF_X1 && OFF_O1 + 32768 == STAGE, "alias");
__host__ __device__ constexpr uint32_t wo_next(uint32_t o, uint32_t base, int sh) { return o == base + (OFF_WO0 >> sh) ? base + (OFF_WO1 >> sh) : o == base + (OFF_WO1 >> sh) ? base + (OFF_WO2 >> sh) : base + (OFF_WO0 >> sh); }
constexpr int B_FULLA = 0, B_FULLB = 3, B_ROW = 6, B_FFULL = 11, B_F2DONE = 14, B_SW = 15, B_CS = 16, B_FDONE = 22, B_WOFULL = B_FDONE + 8, B_OFULL = B_WOFULL + 8,
              B_DONE = B_OFULL + 16;
constexpr int B_EMPTY = B_DONE + 16, B_XR = B_EMPTY + 3, B_G1DONE = B_XR + 1;
constexpr int B_UPD = B_G1DONE + 1, B_F2FULL = B_UPD + 1;
constexpr int B_AUX = B_F2FULL + 1, B_PART = B_AUX + 1, B_ATT = B_PART + 1, B_CSDONE = B_ATT + 1, B_AST = B_CSDONE + 1, NBAR = B_AST + 1;
constexpr int SMEM_BYTES = OFF_BAR + NBAR * 8;
static_assert(SMEM_BYTES <= 232448 && OFF_BAR % 8 == 0, "smem");
#define P_PART 13
#define F1_MASK (0x6a005a00u >> (14 - P_PART))
#define PF_CNT 0x2aaaaacu
#define N_S1 1
#define N_S2 3
#define ST_A 2
#define ST_B 5
#define T_H 0
#define T_O1 250
#define T_O 1800
#define T_S1 128
#define T_S2 950
#define N_GA 4
#define N_X 1
#define D_X 2
#define D_R 3
#define N_ROW 5
#define N_W 5
#define K_W1 5
#define K_W2 10
#define N_CS 3
#define N_F1 4
#define LAST 2
#define N_HA 4
#define N_A2 4
#define TAIL 1
#define POLL_NS 100
constexpr int SPIN_LIMIT = 1 << 18;

struct Scratch {
    uint8_t o[2048 * 1024 * 2];
    uint2 rec[2048];
    float cs[8][3072];
    uint32_t halo[128][512];
    uint32_t h[14336];
    float ypart[8][8][1024];
    uint2 sel[16];
    uint32_t hint[128][8];
    uint32_t epoch;
};
__device__ __align__(1024) Scratch g_scr;

#define TS(i) do {} while (0)
#define TS_END() do {} while (0)
constexpr int SMEM_LAUNCH = SMEM_BYTES;
#define TSC(c, i) do {} while (0)
#define NRETRY() do {} while (0)
__device__ __forceinline__ uint32_t smem_u32(const void* p) { return (uint32_t)__cvta_generic_to_shared(p); }
__device__ __forceinline__ void mbar_init(uint32_t bar, uint32_t cnt) { asm volatile("mbarrier.init.shared::cta.b64 [%0], %1;" ::"r"(bar), "r"(cnt) : "memory"); }
__device__ __forceinline__ void mbar_expect_tx(uint32_t bar, uint32_t bytes) { asm volatile("mbarrier.arrive.expect_tx.shared::cta.b64 _, [%0], %1;" ::"r"(bar), "r"(bytes) : "memory"); }
__device__ __forceinline__ void mbar_arrive(uint32_t bar) { asm volatile("mbarrier.arrive.shared::cta.b64 _, [%0];" ::"r"(bar) : "memory"); }
__device__ __forceinline__ void mbar_arrive_after(uint32_t bar, uint32_t lane, uint32_t dep) {
    asm volatile("{\n.reg .pred p;\n.reg .b32 t;\nsetp.eq.u32 p, %1, 0;\nmad.lo.u32 t, %1, %2, %0;\n@p mbarrier.arrive.shared::cta.b64 _, [t];\n}" ::"r"(bar), "r"(lane), "r"(dep) : "memory");
}
__device__ __forceinline__ void mbar_wait(uint32_t bar, uint32_t parity) {
    asm volatile("{\n.reg .pred P1;\nLAB_WAIT:\nmbarrier.try_wait.parity.shared::cta.b64 P1, [%0], %1;\n@!P1 bra LAB_WAIT;\n}" ::"r"(bar), "r"(parity) : "memory");
}
__device__ __forceinline__ void tma_3d(uint32_t dst, const CUtensorMap* m, uint32_t bar, int c0, int c1, int c2) {
    asm volatile("cp.async.bulk.tensor.3d.shared::cluster.global.mbarrier::complete_tx::bytes [%0], [%1, {%3, %4, %5}], [%2];" ::"r"(dst), "l"(m), "r"(bar), "r"(c0), "r"(c1), "r"(c2) : "memory");
}
__device__ __forceinline__ void tma_2d_once(uint32_t dst, const CUtensorMap* m, uint32_t bar, int c0, int c1) {
    asm volatile("cp.async.bulk.tensor.2d.shared::cluster.global.mbarrier::complete_tx::bytes.L2::cache_hint [%0], [%1, {%3, %4}], [%2], %5;" ::"r"(dst), "l"(m), "r"(bar), "r"(c0), "r"(c1), "l"(0x12F0000000000000ull) : "memory");
}
__device__ __forceinline__ void tma_3d_once(uint32_t dst, const CUtensorMap* m, uint32_t bar, int c0, int c1, int c2) {
    asm volatile("cp.async.bulk.tensor.3d.shared::cluster.global.mbarrier::complete_tx::bytes.L2::cache_hint [%0], [%1, {%3, %4, %5}], [%2], %6;" ::"r"(dst), "l"(m), "r"(bar), "r"(c0), "r"(c1), "r"(c2), "l"(0x12F0000000000000ull) : "memory");
}
__device__ __forceinline__ void tma_4d(uint32_t dst, const CUtensorMap* m, uint32_t bar, int c0, int c1, int c2, int c3) {
    asm volatile("cp.async.bulk.tensor.4d.shared::cluster.global.mbarrier::complete_tx::bytes [%0], [%1, {%3, %4, %5, %6}], [%2];" ::"r"(dst), "l"(m), "r"(bar), "r"(c0), "r"(c1), "r"(c2), "r"(c3) : "memory");
}
__device__ __forceinline__ void tma_store_2d(const CUtensorMap* m, uint32_t src, int c0, int c1) {
    asm volatile("cp.async.bulk.tensor.2d.global.shared::cta.bulk_group [%0, {%2, %3}], [%1];" ::"l"(m), "r"(src), "r"(c0), "r"(c1) : "memory");
}
__device__ __forceinline__ void bulk_g2s(uint32_t dst, const void* src, uint32_t bytes, uint32_t bar) {
    asm volatile("cp.async.bulk.shared::cluster.global.mbarrier::complete_tx::bytes [%0], [%1], %2, [%3];" ::"r"(dst), "l"(src), "r"(bytes), "r"(bar) : "memory");
}
__device__ __forceinline__ void bulk_prefetch(const void* p, uint32_t bytes) { asm volatile("cp.async.bulk.prefetch.L2.global [%0], %1;" ::"l"(p), "r"(bytes) : "memory"); }
__device__ __forceinline__ void prefetch_map(const CUtensorMap* m) { asm volatile("prefetch.tensormap [%0];" ::"l"(m) : "memory"); }
__device__ __forceinline__ void fence_async_smem() { asm volatile("fence.proxy.async.shared::cta;" ::: "memory"); }
__device__ __forceinline__ void wg_fence() { asm volatile("wgmma.fence.sync.aligned;" ::: "memory"); }
__device__ __forceinline__ void wg_commit() { asm volatile("wgmma.commit_group.sync.aligned;" ::: "memory"); }
template <int N> __device__ __forceinline__ void wg_wait() { asm volatile("wgmma.wait_group.sync.aligned %0;" ::"n"(N) : "memory"); }
__device__ __forceinline__ uint64_t mkdesc(uint32_t lo, uint32_t hi) { return ((uint64_t)hi << 32) | lo; }
__host__ __device__ constexpr uint32_t dhi(uint32_t sbo, uint32_t mode) { return (sbo >> 4) | (mode << 30); }
__host__ __device__ constexpr uint32_t dlo(uint32_t off, uint32_t lbo) { return (off >> 4) + ((lbo >> 4) << 16); }
__device__ __forceinline__ bool elect_one() {
    uint32_t e;
    asm volatile("{\n.reg .pred p;\nelect.sync _|p, 0xffffffff;\nselp.u32 %0, 1, 0, p;\n}" : "=r"(e));
    return e;
}
template <int R> __device__ __forceinline__ void reg_inc() { asm volatile("setmaxnreg.inc.sync.aligned.u32 %0;" ::"n"(R)); }
template <int R> __device__ __forceinline__ void reg_dec() { asm volatile("setmaxnreg.dec.sync.aligned.u32 %0;" ::"n"(R)); }
__device__ __forceinline__ void bar_sync(int id, int n) { asm volatile("bar.sync %0, %1;" ::"r"(id), "r"(n) : "memory"); }
__device__ __forceinline__ void bar_arrive(int id, int n) { asm volatile("bar.arrive %0, %1;" ::"r"(id), "r"(n) : "memory"); }
__device__ __forceinline__ uint32_t pack_bf16(float lo, float hi) { uint32_t r; asm("cvt.rn.bf16x2.f32 %0, %1, %2;" : "=r"(r) : "f"(hi), "f"(lo)); return r; }
__device__ __forceinline__ float bf_lo(uint32_t u) { return __uint_as_float(u << 16); }
__device__ __forceinline__ float bf_hi(uint32_t u) { return __uint_as_float(u & 0xffff0000u); }
__device__ __forceinline__ float bf16r(float v) { return bf_lo(pack_bf16(v, 0.f)); }
__device__ __forceinline__ uint32_t tagw(uint32_t w, uint32_t m, uint32_t tag) { uint32_t r; asm("lop3.b32 %0, %1, %2, %3, 0xb8;" : "=r"(r) : "r"(w), "r"(m), "r"(tag)); return r; }
__device__ __forceinline__ uint32_t tagf(float f, uint32_t tag) { return tagw(__float_as_uint(f), 1u, tag); }
__device__ __forceinline__ uint32_t movm(uint32_t a) { uint32_t d; asm volatile("movmatrix.sync.aligned.m8n8.trans.b16 %0, %1;" : "=r"(d) : "r"(a)); return d; }
__device__ __forceinline__ void mma16816(float (&c)[4], uint32_t a0, uint32_t a1, uint32_t a2, uint32_t a3, uint32_t b0, uint32_t b1) {
    asm volatile("mma.sync.aligned.m16n8k16.row.col.f32.bf16.bf16.f32 {%0,%1,%2,%3}, {%4,%5,%6,%7}, {%8,%9}, {%0,%1,%2,%3};"
                 : "+f"(c[0]), "+f"(c[1]), "+f"(c[2]), "+f"(c[3]) : "r"(a0), "r"(a1), "r"(a2), "r"(a3), "r"(b0), "r"(b1));
}
__device__ __forceinline__ void mma1688(float (&c)[4], uint32_t a0, uint32_t a1, uint32_t b0) {
    asm volatile("mma.sync.aligned.m16n8k8.row.col.f32.bf16.bf16.f32 {%0,%1,%2,%3}, {%4,%5}, {%6}, {%0,%1,%2,%3};"
                 : "+f"(c[0]), "+f"(c[1]), "+f"(c[2]), "+f"(c[3]) : "r"(a0), "r"(a1), "r"(b0));
}
__device__ __forceinline__ uint32_t ld_rlx(const void* p) { uint32_t v; asm volatile("ld.relaxed.gpu.global.u32 %0, [%1];" : "=r"(v) : "l"(p) : "memory"); return v; }
__device__ __forceinline__ uint2 ld_rlx2(const void* p) { uint2 v; asm volatile("ld.relaxed.gpu.global.v2.u32 {%0,%1}, [%2];" : "=r"(v.x), "=r"(v.y) : "l"(p) : "memory"); return v; }
__device__ __forceinline__ uint4 ld_rlx4(const void* p) { uint4 v; asm volatile("ld.relaxed.gpu.global.v4.u32 {%0,%1,%2,%3}, [%4];" : "=r"(v.x), "=r"(v.y), "=r"(v.z), "=r"(v.w) : "l"(p) : "memory"); return v; }
__device__ __forceinline__ void st_rlx(void* p, uint32_t v) { asm volatile("st.relaxed.gpu.global.u32 [%0], %1;" ::"l"(p), "r"(v) : "memory"); }
__device__ __forceinline__ void st_rlx2(void* p, uint32_t a, uint32_t b) { asm volatile("st.relaxed.gpu.global.v2.u32 [%0], {%1,%2};" ::"l"(p), "r"(a), "r"(b) : "memory"); }
__device__ __forceinline__ void st_rlx4(void* p, uint32_t a, uint32_t b, uint32_t c, uint32_t d) { asm volatile("st.relaxed.gpu.global.v4.u32 [%0], {%1,%2,%3,%4};" ::"l"(p), "r"(a), "r"(b), "r"(c), "r"(d) : "memory"); }
__device__ __forceinline__ uint4 ldg_nc(const void* p) { uint4 v; asm volatile("ld.global.nc.v4.u32 {%0,%1,%2,%3}, [%4];" : "=r"(v.x), "=r"(v.y), "=r"(v.z), "=r"(v.w) : "l"(p)); return v; }
__device__ __forceinline__ uint32_t mism(uint32_t a, uint32_t b, uint32_t tag) { uint32_t r; asm("lop3.b32 %0, %1, %2, %3, 0x7e;" : "=r"(r) : "r"(a), "r"(b), "r"(tag)); return r; }
__device__ __forceinline__ uint32_t mism(const uint4& v, uint32_t tag) { return mism(v.x, v.y, tag) | mism(v.z, v.w, tag); }
__device__ __forceinline__ void prefetch_l2(const void* p) { asm volatile("prefetch.global.L2 [%0];" ::"l"(p)); }
__device__ __forceinline__ void nap(int n) {
#pragma unroll 1
    for (int i = 0; i < n; i++) __nanosleep(100);
}
__device__ __forceinline__ uint32_t now() { uint32_t t; asm volatile("mov.u32 %0, %%globaltimer_lo;" : "=r"(t)); return t; }
__device__ __forceinline__ void until(uint32_t t) {
    while (t - now() - 1 < 16384u) __nanosleep(50);
}
__device__ __forceinline__ uint32_t opaque(uint32_t v) { return __shfl_xor_sync(0xffffffffu, v, 0); }
__device__ __forceinline__ void sts4(uint32_t a, uint32_t x, uint32_t y, uint32_t z, uint32_t w) { asm volatile("st.shared.v4.u32 [%0], {%1,%2,%3,%4};" ::"r"(a), "r"(x), "r"(y), "r"(z), "r"(w) : "memory"); }
__device__ __forceinline__ void sts2(uint32_t a, uint32_t x, uint32_t y) { asm volatile("st.shared.v2.u32 [%0], {%1,%2};" ::"r"(a), "r"(x), "r"(y) : "memory"); }
__device__ __forceinline__ uint4 lds4(uint32_t a) { uint4 v; asm volatile("ld.shared.v4.u32 {%0,%1,%2,%3}, [%4];" : "=r"(v.x), "=r"(v.y), "=r"(v.z), "=r"(v.w) : "r"(a) : "memory"); return v; }
__device__ __forceinline__ float4 lds4f(uint32_t a) { float4 v; asm volatile("ld.shared.v4.f32 {%0,%1,%2,%3}, [%4];" : "=f"(v.x), "=f"(v.y), "=f"(v.z), "=f"(v.w) : "r"(a) : "memory"); return v; }
__device__ __forceinline__ uint2 lds2(uint32_t a) { uint2 v; asm volatile("ld.shared.v2.u32 {%0,%1}, [%2];" : "=r"(v.x), "=r"(v.y) : "r"(a) : "memory"); return v; }
__device__ __forceinline__ float2 lds2f(uint32_t a) { float2 v; asm volatile("ld.shared.v2.f32 {%0,%1}, [%2];" : "=f"(v.x), "=f"(v.y) : "r"(a) : "memory"); return v; }
__device__ __forceinline__ uint32_t lds1(uint32_t a) { uint32_t v; asm volatile("ld.shared.u32 %0, [%1];" : "=r"(v) : "r"(a) : "memory"); return v; }
__device__ __forceinline__ float lds1f(uint32_t a) { return __uint_as_float(lds1(a)); }
__device__ __forceinline__ void sts1(uint32_t a, uint32_t v) { asm volatile("st.shared.u32 [%0], %1;" ::"r"(a), "r"(v) : "memory"); }
__device__ __forceinline__ uint32_t redux_max(uint32_t v) { uint32_t r; asm volatile("redux.sync.max.u32 %0, %1, 0xffffffff;" : "=r"(r) : "r"(v)); return r; }
__device__ __forceinline__ float ex2(float x) { float r; asm("ex2.approx.ftz.f32 %0, %1;" : "=f"(r) : "f"(x)); return r; }
__device__ __forceinline__ float rcp(float x) { float r; asm("rcp.approx.ftz.f32 %0, %1;" : "=f"(r) : "f"(x)); return r; }
__device__ __forceinline__ float sigmoidf(float v) { return rcp(1.f + ex2(v * -1.4426950408889634f)); }

template <int TA, int TB>
__device__ __forceinline__ void wgmma_n192(float (&d)[96], uint64_t da, uint64_t db, int acc = 1) {
    asm volatile("{\n.reg .pred p;\nsetp.ne.b32 p, %100, 0;\n"
        "wgmma.mma_async.sync.aligned.m64n192k16.f32.bf16.bf16 "
        "{%0, %1, %2, %3, %4, %5, %6, %7, %8, %9, %10, %11, %12, %13, %14, %15, "
        "%16, %17, %18, %19, %20, %21, %22, %23, %24, %25, %26, %27, %28, %29, %30, %31, "
        "%32, %33, %34, %35, %36, %37, %38, %39, %40, %41, %42, %43, %44, %45, %46, %47, "
        "%48, %49, %50, %51, %52, %53, %54, %55, %56, %57, %58, %59, %60, %61, %62, %63, "
        "%64, %65, %66, %67, %68, %69, %70, %71, %72, %73, %74, %75, %76, %77, %78, %79, "
        "%80, %81, %82, %83, %84, %85, %86, %87, %88, %89, %90, %91, %92, %93, %94, %95}, "
        "%96, %97, p, 1, 1, %98, %99;\n}\n"
        : "+f"(d[0]), "+f"(d[1]), "+f"(d[2]), "+f"(d[3]), "+f"(d[4]), "+f"(d[5]), "+f"(d[6]), "+f"(d[7]),
          "+f"(d[8]), "+f"(d[9]), "+f"(d[10]), "+f"(d[11]), "+f"(d[12]), "+f"(d[13]), "+f"(d[14]), "+f"(d[15]),
          "+f"(d[16]), "+f"(d[17]), "+f"(d[18]), "+f"(d[19]), "+f"(d[20]), "+f"(d[21]), "+f"(d[22]), "+f"(d[23]),
          "+f"(d[24]), "+f"(d[25]), "+f"(d[26]), "+f"(d[27]), "+f"(d[28]), "+f"(d[29]), "+f"(d[30]), "+f"(d[31]),
          "+f"(d[32]), "+f"(d[33]), "+f"(d[34]), "+f"(d[35]), "+f"(d[36]), "+f"(d[37]), "+f"(d[38]), "+f"(d[39]),
          "+f"(d[40]), "+f"(d[41]), "+f"(d[42]), "+f"(d[43]), "+f"(d[44]), "+f"(d[45]), "+f"(d[46]), "+f"(d[47]),
          "+f"(d[48]), "+f"(d[49]), "+f"(d[50]), "+f"(d[51]), "+f"(d[52]), "+f"(d[53]), "+f"(d[54]), "+f"(d[55]),
          "+f"(d[56]), "+f"(d[57]), "+f"(d[58]), "+f"(d[59]), "+f"(d[60]), "+f"(d[61]), "+f"(d[62]), "+f"(d[63]),
          "+f"(d[64]), "+f"(d[65]), "+f"(d[66]), "+f"(d[67]), "+f"(d[68]), "+f"(d[69]), "+f"(d[70]), "+f"(d[71]),
          "+f"(d[72]), "+f"(d[73]), "+f"(d[74]), "+f"(d[75]), "+f"(d[76]), "+f"(d[77]), "+f"(d[78]), "+f"(d[79]),
          "+f"(d[80]), "+f"(d[81]), "+f"(d[82]), "+f"(d[83]), "+f"(d[84]), "+f"(d[85]), "+f"(d[86]), "+f"(d[87]),
          "+f"(d[88]), "+f"(d[89]), "+f"(d[90]), "+f"(d[91]), "+f"(d[92]), "+f"(d[93]), "+f"(d[94]), "+f"(d[95])
        : "l"(da), "l"(db), "n"(TA), "n"(TB), "r"(acc));
}
template <int TA, int TB>
__device__ __forceinline__ void wgmma_n128(float (&d)[64], uint64_t da, uint64_t db, int acc = 1) {
    asm volatile("{\n.reg .pred p;\nsetp.ne.b32 p, %68, 0;\n"
        "wgmma.mma_async.sync.aligned.m64n128k16.f32.bf16.bf16 "
        "{%0, %1, %2, %3, %4, %5, %6, %7, %8, %9, %10, %11, %12, %13, %14, %15, "
        "%16, %17, %18, %19, %20, %21, %22, %23, %24, %25, %26, %27, %28, %29, %30, %31, "
        "%32, %33, %34, %35, %36, %37, %38, %39, %40, %41, %42, %43, %44, %45, %46, %47, "
        "%48, %49, %50, %51, %52, %53, %54, %55, %56, %57, %58, %59, %60, %61, %62, %63}, "
        "%64, %65, p, 1, 1, %66, %67;\n}\n"
        : "+f"(d[0]), "+f"(d[1]), "+f"(d[2]), "+f"(d[3]), "+f"(d[4]), "+f"(d[5]), "+f"(d[6]), "+f"(d[7]),
          "+f"(d[8]), "+f"(d[9]), "+f"(d[10]), "+f"(d[11]), "+f"(d[12]), "+f"(d[13]), "+f"(d[14]), "+f"(d[15]),
          "+f"(d[16]), "+f"(d[17]), "+f"(d[18]), "+f"(d[19]), "+f"(d[20]), "+f"(d[21]), "+f"(d[22]), "+f"(d[23]),
          "+f"(d[24]), "+f"(d[25]), "+f"(d[26]), "+f"(d[27]), "+f"(d[28]), "+f"(d[29]), "+f"(d[30]), "+f"(d[31]),
          "+f"(d[32]), "+f"(d[33]), "+f"(d[34]), "+f"(d[35]), "+f"(d[36]), "+f"(d[37]), "+f"(d[38]), "+f"(d[39]),
          "+f"(d[40]), "+f"(d[41]), "+f"(d[42]), "+f"(d[43]), "+f"(d[44]), "+f"(d[45]), "+f"(d[46]), "+f"(d[47]),
          "+f"(d[48]), "+f"(d[49]), "+f"(d[50]), "+f"(d[51]), "+f"(d[52]), "+f"(d[53]), "+f"(d[54]), "+f"(d[55]),
          "+f"(d[56]), "+f"(d[57]), "+f"(d[58]), "+f"(d[59]), "+f"(d[60]), "+f"(d[61]), "+f"(d[62]), "+f"(d[63])
        : "l"(da), "l"(db), "n"(TA), "n"(TB), "r"(acc));
}
template <int TB>
__device__ __forceinline__ void wgmma_rs_n128(float (&d)[64], uint32_t a0, uint32_t a1, uint32_t a2, uint32_t a3, uint64_t db) {
    asm volatile("{\n.reg .pred p;\nsetp.ne.b32 p, 1, 0;\n"
        "wgmma.mma_async.sync.aligned.m64n128k16.f32.bf16.bf16 "
        "{%0, %1, %2, %3, %4, %5, %6, %7, %8, %9, %10, %11, %12, %13, %14, %15, "
        "%16, %17, %18, %19, %20, %21, %22, %23, %24, %25, %26, %27, %28, %29, %30, %31, "
        "%32, %33, %34, %35, %36, %37, %38, %39, %40, %41, %42, %43, %44, %45, %46, %47, "
        "%48, %49, %50, %51, %52, %53, %54, %55, %56, %57, %58, %59, %60, %61, %62, %63}, "
        "{%64, %65, %66, %67}, %68, p, 1, 1, %69;\n}\n"
        : "+f"(d[0]), "+f"(d[1]), "+f"(d[2]), "+f"(d[3]), "+f"(d[4]), "+f"(d[5]), "+f"(d[6]), "+f"(d[7]),
          "+f"(d[8]), "+f"(d[9]), "+f"(d[10]), "+f"(d[11]), "+f"(d[12]), "+f"(d[13]), "+f"(d[14]), "+f"(d[15]),
          "+f"(d[16]), "+f"(d[17]), "+f"(d[18]), "+f"(d[19]), "+f"(d[20]), "+f"(d[21]), "+f"(d[22]), "+f"(d[23]),
          "+f"(d[24]), "+f"(d[25]), "+f"(d[26]), "+f"(d[27]), "+f"(d[28]), "+f"(d[29]), "+f"(d[30]), "+f"(d[31]),
          "+f"(d[32]), "+f"(d[33]), "+f"(d[34]), "+f"(d[35]), "+f"(d[36]), "+f"(d[37]), "+f"(d[38]), "+f"(d[39]),
          "+f"(d[40]), "+f"(d[41]), "+f"(d[42]), "+f"(d[43]), "+f"(d[44]), "+f"(d[45]), "+f"(d[46]), "+f"(d[47]),
          "+f"(d[48]), "+f"(d[49]), "+f"(d[50]), "+f"(d[51]), "+f"(d[52]), "+f"(d[53]), "+f"(d[54]), "+f"(d[55]),
          "+f"(d[56]), "+f"(d[57]), "+f"(d[58]), "+f"(d[59]), "+f"(d[60]), "+f"(d[61]), "+f"(d[62]), "+f"(d[63])
        : "r"(a0), "r"(a1), "r"(a2), "r"(a3), "l"(db), "n"(TB));
}
template <int TA, int TB>
__device__ __forceinline__ void wgmma_n8(float (&d)[4], uint64_t da, uint64_t db, int acc = 1) {
    asm volatile("{\n.reg .pred p;\nsetp.ne.b32 p, %8, 0;\n"
        "wgmma.mma_async.sync.aligned.m64n8k16.f32.bf16.bf16 "
        "{%0, %1, %2, %3}, "
        "%4, %5, p, 1, 1, %6, %7;\n}\n"
        : "+f"(d[0]), "+f"(d[1]), "+f"(d[2]), "+f"(d[3])
        : "l"(da), "l"(db), "n"(TA), "n"(TB), "r"(acc));
}

__device__ __forceinline__ uint32_t sub2(uint32_t a, uint32_t b) { uint32_t r; asm("sub.rn.bf16x2 %0, %1, %2;" : "=r"(r) : "r"(a), "r"(b)); return r; }

struct Roles { uint16_t v[132]; };

__global__ void __launch_bounds__(512, 1)
fused_kernel(int by_sm, const __nv_bfloat16* __restrict__ x, const __nv_bfloat16* __restrict__ wqkv, const __nv_bfloat16* __restrict__ wr,
             Scratch* const S, const char* __restrict__ wg, const char* __restrict__ wu, const char* __restrict__ wd, const char* __restrict__ wo, uint8_t* __restrict__ out,
             const __grid_constant__ Roles roles,
             const __grid_constant__ CUtensorMap mw, const __grid_constant__ CUtensorMap mx, const __grid_constant__ CUtensorMap mwo,
             const __grid_constant__ CUtensorMap mxs, const __grid_constant__ CUtensorMap mcs, const __grid_constant__ CUtensorMap mout, const __grid_constant__ CUtensorMap mgu, const __grid_constant__ CUtensorMap mwd) {
    extern __shared__ __align__(1024) uint8_t smem[];
    constexpr uint32_t sb = 1024, bars = sb + OFF_BAR, sd = sb >> 4;
    const int tid = threadIdx.x, lane = tid & 31;
    asm volatile("{\n.reg .pred p, q;\nsetp.lt.u32 p, %2, 16;\nsetp.lt.u32 q, %2, 24;\n@p prefetch.global.L2 [%0];\n@p prefetch.global.L2 [%0 + 128];\n@q prefetch.global.L2 [%1];\n}" ::
                 "l"((const char*)x + (blockIdx.x * 16 + tid - 32) % 2048 * 2048), "l"((const char*)wqkv + (blockIdx.x * 24 + tid - 32) * 128), "r"(tid - 32));
    const int warp = __shfl_sync(0xffffffffu, tid >> 5, 0);
    uint32_t smid;
    asm volatile("mov.u32 %0, %%smid;" : "=r"(smid));
    const int role = roles.v[by_sm ? smid : blockIdx.x], fb = role & 255, b = role >> 8, kc = fb >> 4, c2 = fb & 15;
    const int mt = b >> 4, nt = b & 15, hp = b & 1, cb = nt >> 1;
    const int par = mt >> 2, j0 = (mt & 3) * 256;
    uint8_t* const g_o = S->o;

    auto load_stage = [&](int p, uint32_t so, int bi) {
        const uint32_t fullA = bars + 8 * (B_FULLA + bi), fullB = bars + 8 * (B_FULLB + bi);
        mbar_expect_tx(fullA, 40960);
        tma_3d(sb + so + 16384, &mw, fullA, nt * 64, p * 64, 0);
        tma_4d(sb + so, &mx, fullA, par * 1024 + p * 64, 0, (j0 >> 5) + 4, 0);
        mbar_expect_tx(fullB, 16384);
        tma_4d(sb + so + 40960, &mx, fullB, par * 1024 + p * 64, 0, j0 >> 5, 0);
    };
    if (warp == 0 && fb < 128 && elect_one()) {
        mbar_init(bars + 8 * B_FULLA, 1); mbar_init(bars + 8 * B_FULLB, 1);
        load_stage(0, STAGE, 0);
    }
    if (fb >= 128) {
        const uint32_t epoch = ld_rlx(&S->epoch), tag = (epoch & 1) - 1;
        if (fb > 128) {
#pragma unroll 1
            for (int it = 0; it < 64 && warp == 0 && ld_rlx(&S->epoch) == epoch; it++) __nanosleep(500);
            TS_END();
            return;
        }
        if (tid < 8) st_rlx2(&S->sel[tid], ~tag, ~tag);
        uint4 ra, rb;
#pragma unroll 1
        for (int it = 0; it < SPIN_LIMIT; it++) {
            ra = ld_rlx4(&S->rec[tid * 2]); rb = ld_rlx4(&S->rec[1024 + tid * 2]);
            if (!__any_sync(0xffffffffu, (mism(ra.x, ra.z, tag) | mism(rb.x, rb.z, tag)) & 0x8000u)) break;
        }
        __syncwarp();
        TSC(tid == 0, 31);
        sts4(sb + 1024 + tid * 16, ra.y, rb.y, ra.w, rb.w);
        uint4 k = make_uint4(ra.x, ra.z, rb.x, rb.z);
        uint32_t cand;
#pragma unroll 1
        for (int pass = 0; pass < 2; pass++) {
            const uint32_t a0 = max(k.x, k.y), a1 = min(k.x, k.y), a2 = max(k.z, k.w), a3 = min(k.z, k.w), c1 = min(a0, a2), c2 = max(a1, a3);
            k = make_uint4(max(a0, a2), max(c1, c2), min(c1, c2), min(a1, a3));
#pragma unroll
            for (int r = 0; r < 8; r++) {
                const uint32_t m = redux_max(k.x);
                if (lane == r) cand = m;
                if (k.x == m) k = make_uint4(k.y, k.z, k.w, 0);
            }
            if (pass) break;
            if (lane < 8) sts1(sb + (warp * 8 + lane) * 4, cand);
            __syncthreads();
            if (warp) { TS_END(); return; }
            k = lds4(sb + lane * 16);
            TSC(TIMING == 12 && tid == 0 && k.x != 0x12345, 40);
        }
        if (lane < 8) st_rlx2(&S->sel[lane], cand, lds1(sb + 1024 + (~cand & 0x7ffu) * 4));
        TSC(tid == 0, 20);
        TS_END();
        return;
    }
    auto ffn_w = [&](int n, int s) {
        const uint32_t dst = sb + OFF_FW + s * 16384;
        if (n < 8) {
            mbar_expect_tx(bars + 8 * (B_FFULL + s), 16384);
            tma_3d_once(dst, &mgu, bars + 8 * (B_FFULL + s), fb * 32, n * 128, 0);
        } else {
            mbar_expect_tx(bars + 8 * B_F2FULL, 16384);
            tma_2d_once(dst, &mwd, bars + 8 * B_F2FULL, c2 * 64, kc * 448 + 64 + s * 128);
            tma_2d_once(dst + 8192, &mwd, bars + 8 * B_F2FULL, c2 * 64, kc * 448 + 128 + s * 128);
        }
    };
    if (warp == 1 && elect_one()) {
#pragma unroll
        for (int i = 0; i < B_FDONE; i++)
            if (i != B_FULLA && i != B_FULLB) mbar_init(bars + 8 * i, i >= B_FFULL && i < B_F2DONE ? 2 : 1);
    }
    if (warp == 4 && elect_one()) {
#pragma unroll
        for (int i = B_EMPTY; i < NBAR; i++) mbar_init(bars + 8 * i, i < B_UPD ? 2 : i < B_AUX ? 4 : i == B_AUX ? 7 : i == B_CSDONE ? 3 : 8);
    }
    if (warp >= 8 && elect_one()) {
#pragma unroll
        for (int i = 0; i < (B_EMPTY - B_FDONE) / 8; i++) mbar_init(bars + 8 * (B_FDONE + 8 * i - 8 + warp), 1);
    }
    uint32_t epoch;
    if (warp >> 2 == 2) epoch = ld_rlx(&S->epoch);
    __syncthreads();

    if (warp >= 12) {
        reg_dec<24>();
        if (warp > 12) {
            const int p = warp - 13;
            if (p == 1) {
                float sw = 0.f;
                mbar_wait(bars + 8 * (B_ROW + 4), 0);
#pragma unroll 1
                for (int i = 0; i < 16; i++) { const uint32_t q = lds1(sb + OFF_FA + i * 128 + lane * 4); sw += bf_lo(q) + bf_hi(q); }
#pragma unroll 1
                for (int o = 1; o < 32; o <<= 1) sw += __shfl_xor_sync(0xffffffffu, sw, o);
                if (lane == 0) { sts1(sb + OFF_TAG + 4, __float_as_uint(sw)); mbar_arrive(bars + 8 * B_SW); }
            } else {
#pragma unroll 1
                for (int q = 0; q < 4; q++) {
                    nap(p ? (q ? D_R : N_ROW) : (q ? D_X : N_X));
                    if (p == 0) {
                        const __nv_bfloat16* xp = x + (size_t)((j0 + nt * 16 + (lane >> 1)) * 2 + par) * 1024 + q * 256 + (lane & 1) * 64;
                        prefetch_l2(xp); prefetch_l2(xp + 128);
                    } else if (elect_one()) {
                        mbar_expect_tx(bars + 8 * (B_ROW + q), 8192);
                        tma_3d(sb + OFF_FW + q * 8192, &mxs, bars + 8 * (B_ROW + q), 0, j0 + nt * 16, par * 16 + q * 4);
                    }
                }
                if (p == 0) nap(N_CS);
            }
            const uint32_t stg = sb + OFF_FW + 32768 + p * 4096 + lane * 16;
            float c[8];
#pragma unroll
            for (int i = 0; i < 8; i++) c[i] = 0.f;
#pragma unroll 1
            for (int n = 0; n < 10; n++) {
                const uint32_t bo = (n & 1) * 2048, bar = bars + 8 * (B_CS + 2 * p + (n & 1));
                if (n >= 2) {
                    mbar_wait(bar, ~(n >> 1) & 1);
#pragma unroll 2
                    for (int i = 0; i < 4; i++) {
                        const uint4 v = lds4(stg + bo + i * 512);
                        c[0] += bf_lo(v.x); c[1] += bf_hi(v.x); c[2] += bf_lo(v.y); c[3] += bf_hi(v.y);
                        c[4] += bf_lo(v.z); c[5] += bf_hi(v.z); c[6] += bf_lo(v.w); c[7] += bf_hi(v.w);
                    }
                    asm volatile("" :: "f"(c[7]));
                    __syncwarp();
                }
                if (n < 8 && elect_one()) {
                    mbar_expect_tx(bar, 2048);
                    tma_3d(sb + OFF_FW + 32768 + p * 4096 + bo, &mcs, bar, p * 1024 + nt * 64, mt * 8, 2 * n);
                }
            }
            sts4(stg + lane * 16, __float_as_uint(c[0]), __float_as_uint(c[1]), __float_as_uint(c[2]), __float_as_uint(c[3]));
            sts4(stg + lane * 16 + 16, __float_as_uint(c[4]), __float_as_uint(c[5]), __float_as_uint(c[6]), __float_as_uint(c[7]));
            bar_sync(13, 128);
            const uint32_t tag = lds1(sb + OFF_TAG);
            float* gcs = &S->cs[0][p * 1024 + nt * 64];
            {
                const float2 a0 = lds2f(stg - lane * 8), a1 = lds2f(stg - lane * 8 + 256), a2 = lds2f(stg - lane * 8 + 512), a3 = lds2f(stg - lane * 8 + 768);
                st_rlx2(gcs + mt * 3072 + lane * 2, tagf((a0.x + a1.x) + (a2.x + a3.x), tag), __float_as_uint((a0.y + a1.y) + (a2.y + a3.y)));
            }
            fence_async_smem();
            __syncwarp();
            if (lane == 0) mbar_arrive(bars + 8 * B_CSDONE);
            TSC(warp == 13 && lane == 0, 19);
            {
                uint4 v[4];
                const float* src = gcs + (lane >> 4) * 4 * 3072 + (lane & 15) * 4;
#pragma unroll 1
                for (int it = 0; it < SPIN_LIMIT; it++) {
#pragma unroll
                    for (int m = 0; m < 4; m++) v[m] = ld_rlx4(src + m * 3072);
                    if (!__any_sync(0xffffffffu, (mism(v[0].x, v[1].x, tag) | mism(v[2].x, v[3].x, tag)) & 1)) break;
                }
                __syncwarp();
#pragma unroll
                for (int c = 0; c < 4; c++) {
                    const float a = (__uint_as_float((&v[0].x)[c]) + __uint_as_float((&v[1].x)[c])) + (__uint_as_float((&v[2].x)[c]) + __uint_as_float((&v[3].x)[c]));
                    (&v[0].x)[c] = __float_as_uint(a + __shfl_xor_sync(0xffffffffu, a, 16));
                }
                const uint32_t ca = sb + OFF_CS + p * 384 + ((lane & 15) >> 1) * 48 + (lane & 1) * 8;
#pragma unroll 1
                for (int r = 0; r < 3; r++) {
                    const uint32_t u0 = pack_bf16(__uint_as_float(v[0].x), __uint_as_float(v[0].y)), u1 = pack_bf16(__uint_as_float(v[0].z), __uint_as_float(v[0].w));
                    sts2(ca + r * 16, u0, u1);
                    v[0].x = __float_as_uint(__uint_as_float(v[0].x) - bf_lo(u0)); v[0].y = __float_as_uint(__uint_as_float(v[0].y) - bf_hi(u0));
                    v[0].z = __float_as_uint(__uint_as_float(v[0].z) - bf_lo(u1)); v[0].w = __float_as_uint(__uint_as_float(v[0].w) - bf_hi(u1));
                }
                if (lane < 20) sts1(sb + OFF_CS + 1152 + lane * 4, 0);
                fence_async_smem();
            }
            if (p == 1) { if (lane < 2) st_rlx4(&S->hint[b][lane * 4], ~tag, ~tag, ~tag, ~tag); }
            else { st_rlx4(&S->halo[b][p * 128 + lane * 4], ~tag, ~tag, ~tag, ~tag); st_rlx4(&S->halo[b][p * 128 + 128 + lane * 4], ~tag, ~tag, ~tag, ~tag); }
            __syncwarp();
            if (lane == 0) mbar_arrive(bars + 8 * B_AUX);
            TSC(warp == 13 && lane == 0, 21);
            mbar_wait(bars + 8 * B_PART, 0);
            mbar_wait(bars + 8 * (B_EMPTY + 2), 0);
            if (p == 0) {
                if (j0) {
                    nap(N_HA);
#pragma unroll 1
                    for (int it = 0; it < SPIN_LIMIT; it++) {
                        TSC(TIMING == 15 && lane == 0 && it < 8, 40 + it);
                        if (elect_one()) { mbar_expect_tx(bars + 8 * B_CS, 2048); bulk_g2s(sb + OFF_HALO, S->halo[b - 16], 2048, bars + 8 * B_CS); }
                        mbar_wait(bars + 8 * B_CS, it & 1);
                        const uint32_t a = sb + OFF_HALO + lane * 16;
                        if (!__any_sync(0xffffffffu, (mism(lds1(a), lds1(a + 512), tag) | mism(lds1(a + 1024), lds1(a + 1536), tag)) & 1)) break;
                    }
                } else {
#pragma unroll
                    for (int c = 0; c < 4; c++) sts4(sb + OFF_HALO + c * 512 + lane * 16, 0, 0, 0, 0);
                }
                __syncwarp();
                bar_arrive(3, 64);
                TSC(TIMING >= 11 && lane == 0, 34);
            } else {
                const int w = p - 1;
                const uint8_t* osrc = g_o + (size_t)((mt * 2 + hp) * 2 + w) * 131072;
                const bool far = w > hp && j0 && lane >= 16;
                const uint32_t* hsrc = &S->hint[b & 0x70][0] + ((lane & 15) - (far ? 16 : 0)) * 8;
                if (lane == 0 && !w) st_rlx(&S->hint[b][0], tagw(now(), 1u, tag));
                uint32_t hv;
#pragma unroll 1
                for (int it = 0; it < SPIN_LIMIT; it++) {
                    hv = ld_rlx(hsrc);
                    if (!__any_sync(0xffffffffu, (hv ^ tag) & 1)) break;
                }
                TSC(TIMING == 11 && lane == 0, 32 + w);
                const uint32_t tn = __shfl_sync(0xffffffffu, hv, 0) - 0x40000000u;
                hv = redux_max(hv - tn + (far ? T_H : 0)) + tn + T_O + w * T_O1;
                mbar_wait(bars + 8 * (w ? B_AST : B_G1DONE), 0);
                if (elect_one()) {
#pragma unroll 1
                    for (int st = 0; st < 8; st++) {
                        const uint32_t full = bars + 8 * (B_OFULL + 8 * w + st);
                        if (st >= 2) mbar_wait(full + 8 * (B_DONE - B_OFULL - 2), 0);
                        if (st < 3) until(hv + (st == 2 ? T_S2 : st * T_S1));
                        TSC(st == 0, 28 + w);
                        mbar_expect_tx(full, 16384);
                        bulk_g2s(sb + (w ? OFF_O1 : OFF_O0) + (st & 1) * 16384, osrc + st * 16384, 16384, full);
                    }
                }
            }
            TS_END();
            return;
        }
        if (elect_one()) {
            auto load_wo = [&](int s, uint32_t ws) {
                mbar_expect_tx(bars + 8 * (B_WOFULL + s), 32768);
                tma_4d(ws, &mwo, bars + 8 * (B_WOFULL + s), 0, s * 8, 0, cb * 2);
            };
            uint32_t so = 2 * STAGE, ph = 1, cnt = PF_CNT << 4;
            int bi = 1, q = 0;
            mbar_expect_tx(bars + 8 * (B_ROW + 4), 2048);
            bulk_g2s(sb + OFF_FA, wr, 2048, bars + 8 * (B_ROW + 4));
            if (smem_u32(smem) != sb) __trap();
            prefetch_map(&mxs); prefetch_map(&mcs);
            const char* pf = (b < 64 ? wg : wu) + (b & 63) * 7168;
#pragma unroll 1
            for (int p = 1; p < 16; p++) {
                if (p < 3) nap(p == 1 ? N_S1 : N_S2);
                mbar_wait(bars + 8 * (B_EMPTY + bi), ph);
                load_stage(p, so, bi);
                if (p >= 2 && p < 5) {
                    const int k0 = p == 2 ? 3 : p == 3 ? K_W1 : K_W2, n = ((p == 2 ? K_W1 : p == 3 ? K_W2 : 16) - k0) * 3072;
                    if (p == 2) nap(N_W);
                    bulk_prefetch((const char*)wqkv + k0 * 393216 + b * n, n);
                }
#pragma unroll 1
                for (int e = q + (cnt & 3); q < e; q++) {
                    if (q == 16) pf = wd + mt * 7 * 131072 + nt * 8192;
                    if (q == 23) pf = wo + b * 8192;
                    bulk_prefetch(pf, q < 16 ? 7168 : 8192);
                    pf += q < 16 ? 64 * 7168 : q < 23 ? 131072 : 1048576;
                }
                cnt >>= 2;
                so = so == 2 * STAGE ? 0 : so + STAGE;
                if (++bi == 3) { bi = 0; ph ^= 1; }
            }
            TS(27);
            uint32_t ws = sb + OFF_WO0;
#pragma unroll 1
            for (int i = 0; i < 8; i++) {
                if (i < 2) {
                    mbar_wait(bars + 8 * (B_EMPTY + 1 + i), 0);
                    mbar_expect_tx(bars + 8 * B_XR, 16384);
                    tma_4d(sb + (i ? 0 : OFF_X1), &mx, bars + 8 * B_XR, par * 1024 + cb * 128 + 64 - i * 64, 0, (j0 >> 5) + hp * 4, 0);
                }
                if (i == 1) {
                    mbar_expect_tx(bars + 8 * B_F2FULL, 8192);
                    tma_2d_once(sb + OFF_F2X, &mwd, bars + 8 * B_F2FULL, c2 * 64, kc * 448);
                }
                if (i) {
                    mbar_wait(bars + 8 * (i == 1 ? B_G1DONE : i == 2 ? B_F2DONE : B_DONE - NWO + i), 0);
                    if (i > 1) mbar_wait(bars + 8 * (i == 2 ? B_OFULL + 8 : B_DONE + 8 - NWO + i), 0);
                }
                load_wo(i, ws);
                if (i == 4) prefetch_map(&mout);
                ws = wo_next(ws, sb, 0);
            }
        }
        TS_END();
    } else if (warp >= 8) {
        reg_dec<40>();
        const int p = warp - 8;
        const bool f1 = fb < 112;
        const uint32_t tag = (epoch & 1) - 1;
        {
            const int ta = tid - 256;
            if (ta < 48) st_rlx4(&S->cs[mt][(ta >> 4) * 1024 + nt * 64 + (ta & 15) * 4], ~tag, ~tag, ~tag, ~tag);
        }
        float s1 = 0.f, s2 = 0.f, sr = 0.f, sw, sh = 0.f;
        {
            const uint32_t xa = sb + OFF_FW + p * 512 + lane * 16, wa = sb + OFF_FA + (((p * 4 + (lane >> 3)) ^ lane) & 7) * 16;
            TSC(TIMING == 12 && lane == 0, 50 + p);
            mbar_wait(bars + 8 * (B_ROW + 4), 0);
            {
                float c1 = 0.f, c2 = 0.f, cr = 0.f;
#pragma unroll 1
                for (int q = 0; q < 4; q++) {
                mbar_wait(bars + 8 * (B_ROW + q), 0);
                TSC(TIMING == 12 && tid == 256 + 96, 32 + q);
                TSC(tid == 256 && q == 3, 17);
#pragma unroll
                for (int i = 0; i < 4; i++) {
                    const uint4 u = lds4(xa + q * 8192 + i * 2048), w4 = lds4(wa + q * 512 + i * 128);
                    const float a0 = bf_lo(u.x), a1 = bf_hi(u.x), a2 = bf_lo(u.y), a3 = bf_hi(u.y), a4 = bf_lo(u.z), a5 = bf_hi(u.z), a6 = bf_lo(u.w), a7 = bf_hi(u.w);
                    s1 += a0 + a1; c1 += a4 + a5; s1 += a2 + a3; c1 += a6 + a7;
                    s2 = fmaf(a0, a0, s2); c2 = fmaf(a4, a4, c2); sr = fmaf(a0, bf_lo(w4.x), sr); cr = fmaf(a4, bf_lo(w4.z), cr);
                    s2 = fmaf(a1, a1, s2); c2 = fmaf(a5, a5, c2); sr = fmaf(a1, bf_hi(w4.x), sr); cr = fmaf(a5, bf_hi(w4.z), cr);
                    s2 = fmaf(a2, a2, s2); c2 = fmaf(a6, a6, c2); sr = fmaf(a2, bf_lo(w4.y), sr); cr = fmaf(a6, bf_lo(w4.w), cr);
                    s2 = fmaf(a3, a3, s2); c2 = fmaf(a7, a7, c2); sr = fmaf(a3, bf_hi(w4.y), sr); cr = fmaf(a7, bf_hi(w4.w), cr);
                }
                }
                s1 += c1; s2 += c2; sr += cr;
            }
            mbar_wait(bars + 8 * B_SW, 0);
            sw = lds1f(sb + OFF_TAG + 4);
#pragma unroll 1
            for (int pass = 0;; pass++) {
#pragma unroll
                for (int o = 1; o < 8; o <<= 1) {
                    s1 += __shfl_xor_sync(0xffffffffu, s1, o); s2 += __shfl_xor_sync(0xffffffffu, s2, o); sr += __shfl_xor_sync(0xffffffffu, sr, o);
                }
                s1 *= 1.f / 1024.f;
                s2 = fmaf(-s1, s1, s2 * (1.f / 1024.f));
                if (!__any_sync(0xffffffffu, !pass && s1 * s1 > 256.f * s2)) break;
                sh = bf16r(s1); s1 = 0.f; s2 = 0.f; sr = 0.f;
#pragma unroll 1
                for (uint32_t o = 0; o < 2048; o = opaque(o + ((o & 12) == 12 ? 116 : 4))) {
                    const uint32_t u = lds1(xa + (o >> 7) * 2048 + (o & 12)), q = lds1(wa + o);
                    const float a0 = bf_lo(u) - sh, a1 = bf_hi(u) - sh;
                    s1 += a0 + a1; s2 = fmaf(a0, a0, fmaf(a1, a1, s2)); sr = fmaf(a0, bf_lo(q), fmaf(a1, bf_hi(q), sr));
                }
            }
        }
        const int ta = opaque(tid) - 256, lane = ta & 31, g = lane >> 2, t = lane & 3;
        {
            if ((lane & 7) == 0) {
                const int s = b * 16 + p * 4 + (lane >> 3);
                const float mb = bf16r(sh + s1);
                float den;
                asm("sqrt.approx.f32 %0, %1;" : "=f"(den) : "f"(bf16r(bf16r(s2) + 1e-5f)));
                den = bf16r(den);
                uint32_t rb = pack_bf16(fmaf(sh - mb, sw, sr) * rcp(den), 0.f);
                if (rb == 0x8000u) rb = 0;
                uint32_t ord = (rb & 0x8000u) ? (~rb & 0xffffu) : (rb | 0x8000u);
                if ((rb & 0x7fffu) > 0x7f80u) ord = 0;
                st_rlx2(&S->rec[s], (ord << 16) | (tag & 0x8000u) | (0x47ffu - (s & 1023) * 2 - par), pack_bf16(mb, den));
            }
            TSC(TIMING == 12 && lane == 0, 36 + p);
            bar_sync(12, 128);
            if (p == 1) sts1(sb + OFF_ROWMAP + lane * 4, 0xffffffffu);
            if (p == 0) {
                if (lane == 0) {
                    sts1(sb + OFF_TAG, tag);
                }
                __syncwarp();
                bar_arrive(13, 128);
            }
            TSC(ta == 0, 18);
        }
        {
            uint2 r[3];
            nap(N_GA);
            const uint2* src = &S->rec[mt * 256 + ta];
            const int l2 = ta < 8 && j0 ? -8 : 0;
#pragma unroll 1
            for (int it = 0; it < SPIN_LIMIT; it++) {
                r[0] = ld_rlx2(src + l2); r[1] = ld_rlx2(src); r[2] = ld_rlx2(src + 128);
                if (!__any_sync(0xffffffffu, (mism(r[0].x, r[1].x, tag) | (r[2].x ^ tag)) & 0x8000u)) break;
            }
#pragma unroll
            for (int n = 0; n < 3; n++)
                if (n || ta < 8) sts2(sb + OFF_STAT + (n ? n * 1024 - 960 : 0) + ta * 8, (r[n].y << 16) ^ 0x80000000u, __float_as_uint(rcp(bf_hi(r[n].y))));
        }
        __syncwarp();
        if (lane == 0) mbar_arrive(bars + 8 * B_AUX);
        TSC(ta == 0, 30);
        if (p == 1) nap(N_F1);
        if (f1 && p < 2 && elect_one()) ffn_w(p, p);
        uint2 sel;
#pragma unroll 1
        for (int it = 0; it < SPIN_LIMIT; it++) {
            sel = ld_rlx2(&S->sel[lane & 7]);
            if (!__any_sync(0xffffffffu, (sel.x ^ tag) & 0x8000u)) break;
            __nanosleep(POLL_NS);
        }
        TSC(ta == 0, 26);
        if (b == 0 && ta == 0) st_rlx(&S->epoch, epoch + 1);
        {
            const __nv_bfloat16* xp = x + (~sel.x & 0x7ffu) * 1024 + (lane >> 3) * 8;
            const uint32_t mb = __byte_perm(sel.y, 0, 0x1010);
            if (p >= 2) nap(N_A2);
#pragma unroll 1
            for (int n = p; n < (f1 ? 8 : 0); n += 4) {
                uint4 v[4];
#pragma unroll
                for (int c = 0; c < 4; c++) v[c] = ldg_nc(xp + n * 128 + c * 32);
                const int s = n % 3;
                if (n >= 2) {
                    mbar_wait(bars + 8 * (n == 2 ? B_CSDONE : B_FDONE + n - 3), 0);
                    if (elect_one()) ffn_w(n & 7, s);
                }
#pragma unroll
                for (int c = 0; c < 4; c++) sts4(sb + OFF_FA + s * 2048 + c * 512 + lane * 16, sub2(v[c].x, mb), sub2(v[c].y, mb), sub2(v[c].z, mb), sub2(v[c].w, mb));
                fence_async_smem();
                __syncwarp();
                if (lane == 0) mbar_arrive(bars + 8 * (B_FFULL + s));
                TSC(TIMING == 12 && lane == 0, 41 + n);
            }
            if (p < 3) {
                mbar_wait(bars + 8 * B_CSDONE, 0);
                mbar_wait(bars + 8 * (f1 ? B_FDONE + 5 + p : B_PART), 0);
                if (elect_one()) ffn_w(8, p ? p - 1 : 2);
            }
        }
        const bool hw = f1 && (p == 0 || p == 3);
        if (hw) st_rlx4(&S->h[fb * 128 + (p & 1) * 64 + (lane & 15) * 4], ~tag, ~tag, ~tag, ~tag);
        st_rlx4(&S->ypart[kc][ta >> 4][c2 * 64 + (ta & 15) * 4], ~tag, ~tag, ~tag, ~tag);
        const float ri[2] = {rcp(bf_hi(__shfl_sync(0xffffffffu, sel.y, 2 * t))), rcp(bf_hi(__shfl_sync(0xffffffffu, sel.y, 2 * t + 1)))};
        mbar_wait(bars + 8 * B_PART, 0);
        if (hw) {
            const uint32_t pa = sb + OFF_FA + (ta & 63) * 16, go = wu < wg ? 1024 : 0;
            const float4 g0 = lds4f(pa + go), g1 = lds4f(pa + 2048 + go), u0 = lds4f(pa + (go ^ 1024)), u1 = lds4f(pa + 2048 + (go ^ 1024));
            float hv[4];
#pragma unroll
            for (int c = 0; c < 4; c++) {
                const float ga = bf16r(((&g0.x)[c] + (&g1.x)[c]) * ri[c & 1]), up = bf16r(((&u0.x)[c] + (&u1.x)[c]) * ri[c & 1]);
                hv[c] = bf16r(ga * sigmoidf(ga)) * up;
            }
#pragma unroll
            for (int hh = 0; hh < 2; hh++) {
                const float o = __shfl_xor_sync(0xffffffffu, (g & 1) ? hv[2 * hh] : hv[2 * hh + 1], 4);
                st_rlx(&S->h[(fb * 4 + (p & 1) * 2 + hh) * 32 + (2 * t + (g & 1)) * 4 + (g >> 1)],
                       tagw((g & 1) ? pack_bf16(o, hv[2 * hh + 1]) : pack_bf16(hv[2 * hh], o), g < 2, tag));
            }
            TSC(ta == 0, 22);
        }
        {
            uint4 hq[4];
            const uint32_t* hp4 = S->h + kc * 1792 + ta * 4;
#pragma unroll 1
            for (int it = 0; it < SPIN_LIMIT; it++) {
#pragma unroll
                for (int n = 0; n < 4; n++) hq[n] = ld_rlx4(hp4 + (n < 3 ? n * 512 : p < 2 ? 1536 : 0));
                if (!__any_sync(0xffffffffu, (mism(hq[0].x, hq[1].x, tag) | mism(hq[2].x, hq[3].x, tag)) & 1)) break;
            }
            mbar_wait(bars + 8 * B_G1DONE, 0);
            bar_sync(12, 128);
#pragma unroll
            for (int n = 0; n < 4; n++) sts4(sb + OFF_FA + ta * 16 + (n < 3 ? n * 2048 : p < 2 ? 6144 : 0), hq[n].x, hq[n].y, hq[n].z, hq[n].w);
            fence_async_smem();
            bar_sync(12, 128);
            TSC(ta == 0, 25);
            mbar_wait(bars + 8 * B_F2FULL, 0);
            mbar_wait(bars + 8 * B_AST, 0);
            float acc[4] = {0.f, 0.f, 0.f, 0.f};
            uint32_t da = sd + dlo(OFF_F2X, 8192), db = sd + dlo(OFF_FA, 128);
#pragma unroll 1
            for (int q = 0; q < 7; q++) {
                wg_fence();
#pragma unroll
                for (int j = 0; j < 4; j++) wgmma_n8<1, 0>(acc, mkdesc(da + j * 128, dhi(1024, 1)), mkdesc(db + j * 16, dhi(128, 0)));
                wg_commit();
                if (q == 2) mbar_wait(bars + 8 * B_ATT, 0);
                da = sd + dlo(OFF_FW, 8192) + q * 512; db += 64;
            }
            wg_wait<0>();
            if (ta == 0) mbar_arrive(bars + 8 * B_F2DONE);
#pragma unroll
            for (int c = 0; c < 4; c++) st_rlx(&S->ypart[kc][2 * t + (c & 1)][c2 * 64 + p * 16 + (c >> 1) * 8 + g], tagf(acc[c], tag));
            TSC(ta == 0, 23);
            bar_sync(12, 128);
        }
#pragma unroll 1
        for (int j = 2 * p; j < 2 * p + 2; j++) {
            const uint32_t kj = __shfl_sync(0xffffffffu, sel.x, j);
            const int row = 0x7ff - (kj & 0x7ffu), jj = (row >> 1) - j0 - hp * 128;
            float a0 = 0.f, a1 = 0.f, a2 = 0.f, a3 = 0.f, sig = 0.f;
            if ((row & 1) == par && jj >= 0 && jj < 128) {
                sig = bf16r(sigmoidf(__uint_as_float(((int)kj < 0 ? kj ^ 0x80000000u : ~kj) & 0xffff0000u)));
#pragma unroll 1
                for (int hh = 0; hh < 8; hh += 4) {
                    uint4 v[4];
#pragma unroll 1
                    for (int it = 0; it < SPIN_LIMIT; it++) {
#pragma unroll
                        for (int m = 0; m < 4; m++) v[m] = ld_rlx4(&S->ypart[hh + m][j][cb * 128 + lane * 4]);
                        if (!__any_sync(0xffffffffu, (mism(v[0], tag) | mism(v[1], tag) | mism(v[2], tag) | mism(v[3], tag)) & 1)) break;
                    }
#pragma unroll
                    for (int m = 0; m < 4; m++) { a0 += __uint_as_float(v[m].x); a1 += __uint_as_float(v[m].y); a2 += __uint_as_float(v[m].z); a3 += __uint_as_float(v[m].w); }
                }
                asm volatile("st.shared.u8 [%0], %1;" ::"r"(sb + OFF_ROWMAP + jj), "r"(j) : "memory");
            }
            sts2(sb + OFF_FA + (lane >> 1) * 128 + j * 16 + (lane & 1) * 8, pack_bf16(bf16r(a0) * sig, bf16r(a1) * sig), pack_bf16(bf16r(a2) * sig, bf16r(a3) * sig));
        }
        fence_async_smem();
        __syncwarp();
        if (lane == 0) mbar_arrive(bars + 8 * B_UPD);
        TSC(ta == 0, 24);
        TS_END();
    } else {
        reg_inc<224>();
        const int w = warp >> 2, wi = warp & 3, tw = (1 - w) * 4 + wi;
        const bool elect = (tid & 127) == 0;
        const uint32_t ln = opaque(lane), g = ln >> 2, t = ln & 3;
        uint32_t tag, ow[8][4];
        auto store_o = [&](int f0, int f1) {
            uint8_t* ob = g_o + (size_t)((mt * 2 + 1 - w) * 2 + 1 - (wi >> 1)) * 131072 + nt * 1024 + (wi & 1) * 512 + ln * 4;
#pragma unroll
            for (int f = f0; f < f1; f++)
#pragma unroll
                for (int i = 3; i >= 0; i--)
                    st_rlx(ob + f * 16384 + i * 128, ow[f][i]);
        };
        {
            float acc[2][96];
            const uint32_t sta = opaque(sb + OFF_STAT + tw * 256 + 64 + g * 8);
            {
                float fa[4] = {0.f, 0.f, 0.f, 0.f};
                uint32_t so = STAGE >> 4, bo = bars, ph = 0;
                const uint32_t dx0 = sd + dlo(w ? 40960 : 0, 16), dw0 = sd + dlo(16384, 8192);
                int p = 0;
                if (w) bar_arrive(1, 256);
                uint32_t fm = fb < 112 ? F1_MASK >> (16 * w) : 0u, fph = 0, fd = bars + 8 * (B_FDONE + w);
                int fs = w;
#pragma unroll 1
                for (; p < 16; p++) {
                    mbar_wait(bo + 8 * B_FULLA, ph);
                    if (w) mbar_wait(bo + 8 * B_FULLB, ph);
                    TSC(elect && p == 0, 1 + 8 * w);
                    TSC(TIMING == 9 && elect && p >= 9 && p < 14, 32 + (p - 9) * 6 + w * 3);
                    bar_sync(1 + w, 256);
                    TSC(TIMING == 1 && tid == 0, 32 + p);
                    if (p == 15) {
                        wg_fence();
                        wgmma_n192<0, 1>(acc[1], mkdesc(sd + dlo(OFF_MEAN + 1024, 0) + w * 128, dhi(128, 0)), mkdesc(sd + dlo(OFF_CS, 0), dhi(48, 0)));
                        wgmma_n192<0, 1>(acc[0], mkdesc(sd + dlo(OFF_MEAN, 0) + w * 128, dhi(128, 0)), mkdesc(sd + dlo(OFF_CS, 0), dhi(48, 0)));
                        wg_commit();
                    }
                    wg_fence();
#pragma unroll
                    for (int h = 1; h >= 0; h--) {
#pragma unroll
                        for (int k = 0; k < 4; k++) wgmma_n192<0, 1>(acc[h], mkdesc(dx0 + so + h * 512 + k * 2, dhi(1024, 1)), mkdesc(dw0 + so + k * 128, dhi(1024, 1)), k ? 1 : p);
                        wg_commit();
                    }
                    if (fm & 1) {
                        mbar_wait(bars + 8 * (B_FFULL + fs), fph);
                        TSC(TIMING == 9 && elect && p >= 9, 33 + (p - 9) * 6 + w * 3);
                        wg_fence();
#pragma unroll
                        for (int j = 0; j < 8; j++)
                            wgmma_n8<1, 0>(fa, mkdesc(sd + dlo(OFF_FW, 8192) + fs * 1024 + j * 64, dhi(512, 2)), mkdesc(sd + dlo(OFF_FA, 128) + fs * 128 + j * 16, dhi(128, 0)));
                        wg_commit();
                    }
                    bar_arrive(2 - w, 256);
                    if (p == 15) break;
                    wg_wait<0>();
                    TSC(TIMING == 9 && elect && p >= 9 && p < 14, 34 + (p - 9) * 6 + w * 3);
                    if (wi == 0 && elect_one()) { mbar_arrive(bo + 8 * B_EMPTY); if (fm & 1) mbar_arrive(fd); }
                    so = so == 2 * (STAGE >> 4) ? 0 : so + (STAGE >> 4);
                    bo += 8;
                    if (bo == bars + 24) { bo = bars; ph ^= 1; }
                    if (fm & 1) { fd += 16; fs += 2; if (fs >= 3) { fs -= 3; fph ^= 1; } }
                    fm >>= 1;
                    if (p == P_PART) {
                        if (fb < 112) sts4(sb + OFF_FA + tid * 16, __float_as_uint(fa[0]), __float_as_uint(fa[1]), __float_as_uint(fa[2]), __float_as_uint(fa[3]));
                        __syncwarp();
                        if (lane == 0) mbar_arrive(bars + 8 * B_PART);
                    }
                    if (p != 14) continue;
                    mbar_wait(bars + 8 * B_AUX, 0);
                    mbar_wait(bars + 8 * (B_EMPTY + 1), 0);
                    const uint32_t hm = __float_as_uint(0.5f * lds1f(sb + OFF_STAT + 64 + tw * 256 + ln * 8)) >> 16;
                    sts4(sb + OFF_MEAN + w * 2048 + wi * 256 + (ln >> 4) * 1024 + (ln & 15) * 16, hm * 0x10001u, hm, 0, 0);
                    fence_async_smem();
                }
            }
            TSC(TIMING != 14 && elect, 2 + 8 * w);

            tag = lds1(sb + OFF_TAG);
            mbar_wait(bars + 8 * (B_EMPTY + 2), 0);
            wg_wait<1>();
#pragma unroll
            for (int i = 0; i < 96; i++) asm volatile("" : "+f"(acc[1][i]) :: "memory");
            uint32_t pk[4][24];
            const uint32_t hm = tw == 7 ? ~ln & 1 : 0;
            auto np = [&](int i, int j) {
                const float* a = &acc[i >> 1][4 * j + 2 * (i & 1)];
                pk[i][j] = pack_bf16(a[0], a[1]);
                if (j >= 16) pk[i][j] = movm(pk[i][j]);
                if (i == 3 && j >= 8 && !(j & 1)) pk[i][j] = tagw(pk[i][j], hm, tag);
            };
            const uint32_t ha = sb + OFF_HALO + tw * 2048 + ln * 8;
#pragma unroll
            for (int j = 8; j < 24; j += 2) {
                np(3, j); np(3, j + 1);
                sts2(ha + 2048 + (j - 8) * 128, pk[3][j], pk[3][j + 1]);
                asm volatile("{\n.reg .pred p;\nsetp.eq.u32 p, %3, 7;\n@p st.relaxed.gpu.global.v2.u32 [%0], {%1,%2};\n}" ::"l"((char*)&S->halo[b][ln * 2] + (j - 8) * 128),
                             "r"(pk[3][j]), "r"(pk[3][j + 1]), "r"(tw) : "memory");
            }
            bar_arrive(4 + tw, 64);
            TSC(TIMING == 15 && ln == 0 && tw == 7, 39);
            TSC(TIMING == 8 && ln == 0 && wi == 1, 32 + 8 * w);
            const bool u0 = 2 * t > g, u1 = 2 * t + 1 > g;
            const uint32_t mU = (u0 ? 0xffffu : 0u) | (u1 ? 0xffff0000u : 0u);
            uint2 hl[8];
            float rk[4][2], fq[4][2];
            auto factors = [&]() {
                const uint32_t ka = sb + OFF_STAT + tw * 256 + 4 + t * 16, k0 = opaque(ka + (u0 ? 0 : 64)), k1 = opaque(ka + (u1 ? 8 : 72));
#pragma unroll
                for (int i = 0; i < 4; i++) {
                    const float rq = lds1f(sta + i * 64 + 4) * (0.17677669529663687f * 1.4426950408889634f);
                    rk[i][0] = lds1f(k0 + i * 64); rk[i][1] = lds1f(k1 + i * 64);
                    fq[i][0] = rq * rk[i][0]; fq[i][1] = rq * rk[i][1];
                }
            };
#pragma unroll
            for (int jj = 0; jj < 12; jj++) { const int j = (jj >> 2) * 8 + (jj & 3); np(2, j); if (j < 8) np(3, j); }
            factors();
            wg_wait<0>();
#pragma unroll
            for (int i = 0; i < 96; i++) asm volatile("" : "+f"(acc[0][i]) :: "memory");
            if (elect) mbar_arrive(bars + 8 * B_G1DONE);
            const float mask = tw == 0 && j0 == 0 ? -INFINITY : 0.f;
#pragma unroll
            for (int hd = 0; hd < 2; hd++) {
#pragma unroll
                for (int jj = 0; jj < 12; jj++) {
                    const int j = (jj >> 2) * 8 + hd * 4 + (jj & 3);
                    np(0, j); np(1, j);
                    if (j & 4)
                    { np(2, j); if (j < 8) np(3, j); }
                }
                if (hd == 0) mbar_wait(bars + 8 * B_G1DONE, 0);
                float s[2][3][4];
#pragma unroll
                for (int h = 1; h >= 0; h--)
#pragma unroll
                    for (int n = 2; n >= 0; n--) {
                        if (h == 0 && n == 0 && hd == 0) {
                            TSC(TIMING == 8 && ln == 0 && wi == 1 && s[1][0][0] + s[0][1][0] != 123.456f, 33 + 8 * w);
                            bar_sync(3 + tw, 64);
#pragma unroll
                            for (int c = 0; c < 8; c++) hl[c] = lds2(ha + c * 256);
                        }
                        const int kg = 2 * h - 1 + n;
                        s[h][n][0] = s[h][n][1] = kg < 0 ? mask : 0.f; s[h][n][2] = s[h][n][3] = 0.f;
#pragma unroll
                        for (int ks = 0; ks < 2; ks++) {
                            const int q = hd * 4 + 2 * ks;
                            const uint32_t* k = kg < 0 ? &hl[hd * 2 + ks].x : &pk[kg < 0 ? 0 : kg][8 + q];
                            mma16816(s[h][n], pk[2 * h][q], pk[2 * h + 1][q], pk[2 * h][q + 1], pk[2 * h + 1][q + 1], k[0], k[1]);
                        }
                    }
                uint32_t pp[4], pc[4];
#pragma unroll
                for (int i = 0; i < 4; i++) {
                    const float* sp = &s[i >> 1][i & 1][2 * (i & 1)];
                    const float* sc = &s[i >> 1][(i & 1) + 1][2 * (i & 1)];
                    float a0 = (u0 ? sp[0] : sc[0]) * fq[i][0], a1 = (u1 ? sp[1] : sc[1]) * fq[i][1];
                    float m = fmaxf(a0, a1);
                    m = fmaxf(m, __shfl_xor_sync(0xffffffffu, m, 1));
                    m = fmaxf(m, __shfl_xor_sync(0xffffffffu, m, 2));
                    a0 = ex2(a0 - m); a1 = ex2(a1 - m);
                    float sum = a0 + a1;
                    sum += __shfl_xor_sync(0xffffffffu, sum, 1);
                    sum += __shfl_xor_sync(0xffffffffu, sum, 2);
                    const float inv = rcp(sum);
                    const uint32_t pw = pack_bf16(a0 * rk[i][0] * inv, a1 * rk[i][1] * inv);
                    pp[i] = pw & mU; pc[i] = pw & ~mU;
                }
                TSC(TIMING == 8 && ln == 0 && wi == 1 && pp[0] + pp[3] != 0x12345, 34 + 2 * hd + 8 * w);
#pragma unroll
                for (int fh = 0; fh < 2; fh++)
#pragma unroll
                    for (int i = 0; i < 4; i++) {
                        const int v = 16 + hd * 4 + 2 * fh;
                        const uint32_t* vp = i ? &pk[i ? i - 1 : 0][v] : &hl[4 + hd * 2 + fh].x;
                        float o[4] = {0.f, 0.f, 0.f, 0.f};
                        if (i & 1) mma16816(o, vp[0], vp[1], pk[i][v], pk[i][v + 1], pp[i], pc[i]);
                        else { mma1688(o, pk[i][v], pk[i][v + 1], pc[i]); mma1688(o, vp[0], vp[1], pp[i]); }
                        const uint32_t tm = (ln & 7) == (nt & 3) * 2 + (i & 1);
                        ow[hd * 4 + 2 * fh][i] = tagw(pack_bf16(o[0], o[1]), tm, tag); ow[hd * 4 + 2 * fh + 1][i] = tagw(pack_bf16(o[2], o[3]), tm, tag);
                    }
                store_o(hd ? ST_A : 0, hd ? ST_B : ST_A);
                TSC(TIMING == 11 && !hd && ln == 0 && wi == 3, 45 + w);
                if (!hd) mbar_arrive_after(bars + 8 * B_AST, ln, hl[2].x ^ hl[3].x ^ hl[5].x ^ hl[6].x ^ hl[7].x);
                mbar_wait(bars + 8 * B_G1DONE, 0);
                if (hd && ln == 0) mbar_arrive(bars + 8 * B_ATT);
                TSC(TIMING != 14 && elect && hd == 0, 3 + 8 * w);
                TSC(TIMING == 8 && ln == 0 && wi == 1, 35 + 2 * hd + 8 * w);
            }
        }
        TSC(TIMING != 14 && elect, 4 + 8 * w);
        float acc2[64];
        TSC(TIMING != 14 && elect, 5 + 8 * w);
        {
            const uint32_t ring = sb + (w ? OFF_O1 : OFF_O0), da0 = (ring >> 4) + dlo(0, 1024);
            const uint32_t l2 = opaque(ln), chk = ring + wi * 256 + (l2 >> 3) * 1032 + ((l2 >> 2) & 1) * 132 + (l2 & 3) * 32;
            const uint32_t xs = sb + (wi & 1) * 8192 + (tw >> 1) * 2048, mad = xs + (l2 & 15) * 128;
            auto residual = [&](float* base) {
                const uint32_t sta = sb + OFF_STAT + (8 + hp * 128 + tw * 16 + g) * 8;
                const float2 s0 = lds2f(sta), s1 = lds2f(sta + 64);
                const float m0 = s0.x * s0.y, r0 = 1.f + s0.y, m1 = s1.x * s1.y, r1 = 1.f + s1.y;
                mbar_wait(bars + 8 * B_XR, 0);
#pragma unroll
                for (int j = 0; j < 16; j += 2) {
                    uint32_t xr[4];
                    asm volatile("ldmatrix.sync.aligned.m8n8.x4.shared.b16 {%0,%1,%2,%3}, [%4];" : "=r"(xr[0]), "=r"(xr[1]), "=r"(xr[2]), "=r"(xr[3])
                                 : "r"(mad + (j >> 3) * OFF_X1 + ((((j & 7) + (l2 >> 4)) ^ (l2 & 7)) << 4)) : "memory");
#pragma unroll
                    for (int c = 0; c < 4; c++) {
                        base[4 * j + 2 * c] = fmaf(bf_lo(xr[c]), c & 1 ? r1 : r0, c & 1 ? m1 : m0); base[4 * j + 2 * c + 1] = fmaf(bf_hi(xr[c]), c & 1 ? r1 : r0, c & 1 ? m1 : m0);
                        asm volatile("" : "+f"(base[4 * j + 2 * c]), "+f"(base[4 * j + 2 * c + 1]) :: "memory");
                    }
                }
            };
            residual(acc2);
            uint32_t db = sd + dlo(OFF_WO0, 16384);
#pragma unroll 1
            for (int s = 0; s < 8; s++) {
                const uint32_t ro = (s & 1) * 16384;
                mbar_wait(bars + 8 * (B_WOFULL + s), 0);
                TSC(TIMING == 11 && tid == 0 && s == 0, 43);
                mbar_wait(bars + 8 * (B_OFULL + s) + 64 * w, 0);
                TSC(TIMING == 11 && tid == 0 && s == 0, 44);
#pragma unroll 1
                for (int it = 0; __any_sync(0xffffffffu, (mism(lds1(chk + ro), lds1(chk + ro + 4096), tag) | mism(lds1(chk + ro + 8192), lds1(chk + ro + 12288), tag)) & 1) && it < SPIN_LIMIT; it++) {
                    NRETRY();
                    const uint32_t fo = wi * 256 + (l2 >> 4) * 1024 + (l2 & 15) * 16;
                    uint4 v[8];
#pragma unroll
                    for (int c = 0; c < 8; c++) v[c] = ld_rlx4(g_o + (size_t)(((mt * 2 + hp) * 2 + w) * 8 + s) * 16384 + fo + c * 2048);
#pragma unroll
                    for (int c = 0; c < 8; c++) sts4(ring + ro + fo + c * 2048, v[c].x, v[c].y, v[c].z, v[c].w);
                    fence_async_smem();
                    __syncwarp();
                }
                if (s == 0) mbar_wait(bars + 8 * B_ATT, 0);
                if (s <= 8 - LAST) bar_sync(1 + w, 256);
                TSC(elect && s == 0, 6 + 8 * w);
                TSC(TIMING == 2 && elect, 32 + 16 * w + s);
                wg_fence();
#pragma unroll
                for (int k = 0; k < 8; k++)
                    wgmma_n128<1, 1>(acc2, mkdesc(da0 + (ro >> 4) + k * 128, dhi(128, 0)), mkdesc(db + k * 128, dhi(1024, 1)));
                wg_commit();
                db = wo_next(db, sd + dlo(0, 16384), 4);
                if (s < 8 - LAST) {
                    bar_arrive(2 - w, 256);
                    if (s == 0) store_o(ST_B, 8);
                    wg_wait<0>();
                    if (elect) mbar_arrive(bars + 8 * (B_DONE + s) + 64 * w);
                }
            }
            mbar_wait(bars + 8 * B_UPD, 0);
            int sl0, sl1;
            asm volatile("ld.shared.s8 %0, [%1];" : "=r"(sl0) : "r"(sb + OFF_ROWMAP + tw * 16 + g) : "memory");
            asm volatile("ld.shared.s8 %0, [%1];" : "=r"(sl1) : "r"(sb + OFF_ROWMAP + tw * 16 + 8 + g) : "memory");
            const uint32_t e0 = (sl0 >> 1) == (int)t ? 0x3f80u << ((sl0 & 1) * 16) : 0u, e1 = (sl1 >> 1) == (int)t ? 0x3f80u << ((sl1 & 1) * 16) : 0u;
            if (__any_sync(0xffffffffu, lds1(sb + OFF_ROWMAP + (1 - w) * 64 + (l2 & 15) * 4) != 0xffffffffu)) {
                wg_fence();
                wgmma_rs_n128<1>(acc2, e0, e1, 0u, 0u, mkdesc(sd + dlo(OFF_FA, 0), dhi(128, 0)));
                wg_commit();
            }
            bar_arrive(2 - w, 256);
            wg_wait<0>();
#pragma unroll
            for (int i = 0; i < 64; i++) asm volatile("" : "+f"(acc2[i]) :: "memory");
            TSC(elect, 7 + 8 * w);
#pragma unroll
            for (int j = 0; j < 16; j += 2) {
                const int ch = (j & 7) + (l2 >> 4);
                asm volatile("stmatrix.sync.aligned.m8n8.x4.shared.b16 [%0], {%1,%2,%3,%4};" ::"r"(mad + (j >> 3) * OFF_X1 + ((ch ^ (l2 & 7)) << 4)),
                             "r"(pack_bf16(acc2[4 * j], acc2[4 * j + 1])), "r"(pack_bf16(acc2[4 * j + 2], acc2[4 * j + 3])),
                             "r"(pack_bf16(acc2[4 * j + 4], acc2[4 * j + 5])), "r"(pack_bf16(acc2[4 * j + 6], acc2[4 * j + 7])) : "memory");
                if (TAIL && (TAIL == 2 || w) && (j & 7) == 6) {
                    __syncwarp();
                    uint8_t* op = out + (size_t)(j0 + hp * 128 + tw * 16 + (l2 >> 3)) * 4096 + par * 2048 + cb * 256 + (j >> 3) * 128;
#pragma unroll
                    for (int c = 0; c < 4; c++) {
                        const uint4 v = lds4(xs + (j >> 3) * OFF_X1 + c * 512 + l2 * 16);
                        *(uint4*)(op + c * 4 * 4096 + (((l2 ^ (c * 4 + (l2 >> 3))) & 7) << 4)) = v;
                    }
                } else if ((j & 7) == 6) {
                    fence_async_smem();
                    __syncwarp();
                    if (ln == 0) tma_store_2d(&mout, xs + (j >> 3) * OFF_X1, par * 1024 + cb * 128 + (j >> 3) * 64, j0 + hp * 128 + tw * 16);
                }
            }
            if (ln == 0) asm volatile("cp.async.bulk.commit_group;\ncp.async.bulk.wait_group.read 0;" ::: "memory");
            TSC(elect, 8 + 8 * w);
            TS_END();
        }
    }
}

typedef CUresult (*EncodeFn)(CUtensorMap*, CUtensorMapDataType, cuuint32_t, void*, const cuuint64_t*, const cuuint64_t*, const cuuint32_t*,
                             const cuuint32_t*, CUtensorMapInterleave, CUtensorMapSwizzle, CUtensorMapL2promotion, CUtensorMapFloatOOBfill);

CUtensorMap make_map(EncodeFn fn, const void* base, int rank, const cuuint64_t* dims, const cuuint64_t* strides, const cuuint32_t* box,
                     CUtensorMapSwizzle swz = CU_TENSOR_MAP_SWIZZLE_128B, CUtensorMapL2promotion pro = CU_TENSOR_MAP_L2_PROMOTION_L2_256B) {
    CUtensorMap m;
    cuuint32_t es[5] = {1, 1, 1, 1, 1};
    fn(&m, CU_TENSOR_MAP_DATA_TYPE_BFLOAT16, rank, (void*)base, dims, strides, box, es, CU_TENSOR_MAP_INTERLEAVE_NONE,
       swz, pro, CU_TENSOR_MAP_FLOAT_OOB_FILL_NONE);
    return m;
}

}

extern "C" void kernel_launch(void* const* d_in, const int* in_sizes, int n_in, void* d_out, int out_size) {
    (void)in_sizes; (void)n_in; (void)out_size;
    const __nv_bfloat16* x = (const __nv_bfloat16*)d_in[0];
    const __nv_bfloat16* wqkv = (const __nv_bfloat16*)d_in[1];
    const char* wo = (const char*)d_in[2];
    const __nv_bfloat16* wr = (const __nv_bfloat16*)d_in[4];
    const char* wg = (const char*)d_in[5];
    const char* wu = (const char*)d_in[6];
    const char* wd = (const char*)d_in[7];
    static EncodeFn fn = nullptr;
    static int by_sm = 0;
    static Scratch* scr = nullptr;
    if (!fn) {
        void* p = nullptr; cudaDriverEntryPointQueryResult q;
        cudaGetDriverEntryPoint("cuTensorMapEncodeTiled", &p, cudaEnableDefault, &q);
        fn = (EncodeFn)p;
        cudaFuncSetAttribute(fused_kernel, cudaFuncAttributeMaxDynamicSharedMemorySize, SMEM_LAUNCH);
        cudaGetSymbolAddress((void**)&scr, g_scr);
        int dev = 0, sms = 0;
        cudaGetDevice(&dev);
        cudaDeviceGetAttribute(&sms, cudaDevAttrMultiProcessorCount, dev);
        by_sm = sms == 132;
    }
    Roles roles;
    for (int i = 0; i < 132; i++) {
        const int T = i >> 1, T8 = T < 32 ? T : T + 1 + (T - 32) / 7, fb = (T < 60 ? (~T8 & 7) * 8 + (T8 >> 3) : T < 62 ? T + 4 : T - 2) * 2 + (i & 1);
        roles.v[i] = fb | ((fb & ~31) | (fb & 1) << 4 | (fb & 31) >> 1) << 8;
    }
    const cuuint64_t xd[4] = {2048, 16, 32, 2}, xs[3] = {4096, 131072, 65536};
    const cuuint32_t xb[4] = {64, 16, 4, 2};
    const cuuint64_t wdm[3] = {1024, 1024, 3}, wst[2] = {6144, 2048};
    const cuuint32_t wb[3] = {64, 64, 3};
    const cuuint64_t od[4] = {64, 64, 16, 16}, ost[3] = {2048, 131072, 128};
    const cuuint32_t ob[4] = {64, 8, 16, 2};
    const cuuint64_t yd[2] = {2048, 1024}, yst[1] = {4096};
    const cuuint32_t yb[2] = {64, 16};
    const cuuint64_t sd[3] = {64, 1024, 32}, sst[2] = {4096, 128};
    const cuuint32_t sbx[3] = {64, 16, 4};
    CUtensorMap mxs = make_map(fn, x, 3, sd, sst, sbx);
    const cuuint64_t cd[3] = {3072, 64, 16}, cst[2] = {6144, 393216};
    const cuuint32_t cbx[3] = {64, 8, 2};
    CUtensorMap mcs = make_map(fn, wqkv, 3, cd, cst, cbx, CU_TENSOR_MAP_SWIZZLE_NONE);
    CUtensorMap mx = make_map(fn, x, 4, xd, xs, xb), mw = make_map(fn, wqkv, 3, wdm, wst, wb);
    CUtensorMap mwo = make_map(fn, wo, 4, od, ost, ob), mout = make_map(fn, d_out, 2, yd, yst, yb);
    const cuuint64_t gd[3] = {3584, 1024, 2}, gst[2] = {7168, (cuuint64_t)(wu < wg ? wg - wu : wu - wg)};
    const cuuint32_t gb[3] = {32, 128, 2};
    const cuuint64_t dd[2] = {1024, 3584}, dst[1] = {2048};
    const cuuint32_t db[2] = {64, 64};
    CUtensorMap mgu = make_map(fn, wu < wg ? wu : wg, 3, gd, gst, gb, CU_TENSOR_MAP_SWIZZLE_64B, CU_TENSOR_MAP_L2_PROMOTION_L2_128B);
    CUtensorMap mwd = make_map(fn, wd, 2, dd, dst, db, CU_TENSOR_MAP_SWIZZLE_128B, CU_TENSOR_MAP_L2_PROMOTION_L2_128B);
    fused_kernel<<<132, 512, SMEM_LAUNCH, cudaStreamPerThread>>>(by_sm, x, wqkv, wr, scr, wg, wu, wd, wo, (uint8_t*)d_out, roles, mw, mx, mwo, mxs, mcs, mout, mgu, mwd);
}
```

```cpp
#include <cuda_runtime.h>
#include <cuda.h>
#include <cuda_bf16.h>
#include <stdint.h>

namespace {

constexpr int STAGE = 57344;
constexpr int OFF_FW = 3 * STAGE;
constexpr int OFF_FA = OFF_FW + 49152;
constexpr int OFF_CS = OFF_FA + 6144;
constexpr int OFF_STAT = OFF_CS + 1232;
constexpr int OFF_ROWMAP = OFF_STAT + 2112;
constexpr int OFF_TAG = OFF_ROWMAP + 128;
constexpr int OFF_BAR = OFF_TAG + 8;
constexpr int OFF_F2X = 16384, OFF_HALO = 24576, OFF_O1 = 24576, OFF_O0 = 90112, NWO = 3, OFF_MEAN = 2 * STAGE, OFF_X1 = 2 * STAGE + 8192;
constexpr int OFF_WO0 = OFF_X1 + 16384, OFF_WO1 = STAGE, OFF_WO2 = OFF_FW;
static_assert(OFF_WO0 + 32768 == OFF_FW && OFF_WO1 + 32768 == OFF_O0 && OFF_O0 + 32768 == OFF_X1 && OFF_O1 + 32768 == STAGE, "alias");
__host__ __device__ constexpr uint32_t wo_next(uint32_t o, uint32_t base, int sh) { return o == base + (OFF_WO0 >> sh) ? base + (OFF_WO1 >> sh) : o == base + (OFF_WO1 >> sh) ? base + (OFF_WO2 >> sh) : base + (OFF_WO0 >> sh); }
constexpr int B_FULLA = 0, B_FULLB = 3, B_ROW = 6, B_FFULL = 11, B_F2DONE = 14, B_SW = 15, B_CS = 16, B_FDONE = 22, B_WOFULL = B_FDONE + 8, B_OFULL = B_WOFULL + 8,
              B_DONE = B_OFULL + 16;
constexpr int B_EMPTY = B_DONE + 16, B_XR = B_EMPTY + 3, B_G1DONE = B_XR + 1;
constexpr int B_UPD = B_G1DONE + 1, B_F2FULL = B_UPD + 1;
constexpr int B_AUX = B_F2FULL + 1, B_PART = B_AUX + 1, B_ATT = B_PART + 1, B_CSDONE = B_ATT + 1, B_AST = B_CSDONE + 1, NBAR = B_AST + 1;
constexpr int SMEM_BYTES = OFF_BAR + NBAR * 8;
static_assert(SMEM_BYTES <= 232448 && OFF_BAR % 8 == 0, "smem");
#define P_PART 13
#define F1_MASK (0x6a005a00u >> (14 - P_PART))
#define PF_CNT 0x2aaaaacu
#define N_S1 1
#define N_S2 3
#define ST_A 2
#define ST_B 5
#define T_H 0
#define T_O1 250
#define T_O 1800
#define T_S1 128
#define T_S2 950
#define N_GA 4
#define N_X 1
#define D_X 2
#define D_R 3
#define N_ROW 5
#define N_W 5
#define K_W1 5
#define K_W2 10
#define N_CS 3
#define N_F1 4
#define LAST 2
#define N_HA 4
#define N_A2 4
#define TAIL 1
#define N_H 0
#define N_C2 0
#define N_HI 5
#define POLL_NS 100
constexpr int SPIN_LIMIT = 1 << 18;

struct Scratch {
    uint8_t o[2048 * 1024 * 2];
    uint2 rec[2048];
    float cs[8][3072];
    uint32_t halo[128][512];
    uint32_t h[14336];
    float ypart[8][8][1024];
    uint2 sel[16];
    uint32_t hint[128][8];
    uint32_t epoch;
};
__device__ __align__(1024) Scratch g_scr;

#define TS(i) do {} while (0)
#define TS_END() do {} while (0)
constexpr int SMEM_LAUNCH = SMEM_BYTES;
#define TSC(c, i) do {} while (0)
#define NRETRY() do {} while (0)
__device__ __forceinline__ uint32_t smem_u32(const void* p) { return (uint32_t)__cvta_generic_to_shared(p); }
__device__ __forceinline__ void mbar_init(uint32_t bar, uint32_t cnt) { asm volatile("mbarrier.init.shared::cta.b64 [%0], %1;" ::"r"(bar), "r"(cnt) : "memory"); }
__device__ __forceinline__ void mbar_expect_tx(uint32_t bar, uint32_t bytes) { asm volatile("mbarrier.arrive.expect_tx.shared::cta.b64 _, [%0], %1;" ::"r"(bar), "r"(bytes) : "memory"); }
__device__ __forceinline__ void mbar_arrive(uint32_t bar) { asm volatile("mbarrier.arrive.shared::cta.b64 _, [%0];" ::"r"(bar) : "memory"); }
__device__ __forceinline__ void mbar_arrive_after(uint32_t bar, uint32_t lane, uint32_t dep) {
    asm volatile("{\n.reg .pred p;\n.reg .b32 t;\nsetp.eq.u32 p, %1, 0;\nmad.lo.u32 t, %1, %2, %0;\n@p mbarrier.arrive.shared::cta.b64 _, [t];\n}" ::"r"(bar), "r"(lane), "r"(dep) : "memory");
}
__device__ __forceinline__ void mbar_wait(uint32_t bar, uint32_t parity) {
    asm volatile("{\n.reg .pred P1;\nLAB_WAIT:\nmbarrier.try_wait.parity.shared::cta.b64 P1, [%0], %1;\n@!P1 bra LAB_WAIT;\n}" ::"r"(bar), "r"(parity) : "memory");
}
__device__ __forceinline__ void tma_3d(uint32_t dst, const CUtensorMap* m, uint32_t bar, int c0, int c1, int c2) {
    asm volatile("cp.async.bulk.tensor.3d.shared::cluster.global.mbarrier::complete_tx::bytes [%0], [%1, {%3, %4, %5}], [%2];" ::"r"(dst), "l"(m), "r"(bar), "r"(c0), "r"(c1), "r"(c2) : "memory");
}
__device__ __forceinline__ void tma_2d_once(uint32_t dst, const CUtensorMap* m, uint32_t bar, int c0, int c1) {
    asm volatile("cp.async.bulk.tensor.2d.shared::cluster.global.mbarrier::complete_tx::bytes.L2::cache_hint [%0], [%1, {%3, %4}], [%2], %5;" ::"r"(dst), "l"(m), "r"(bar), "r"(c0), "r"(c1), "l"(0x12F0000000000000ull) : "memory");
}
__device__ __forceinline__ void tma_3d_once(uint32_t dst, const CUtensorMap* m, uint32_t bar, int c0, int c1, int c2) {
    asm volatile("cp.async.bulk.tensor.3d.shared::cluster.global.mbarrier::complete_tx::bytes.L2::cache_hint [%0], [%1, {%3, %4, %5}], [%2], %6;" ::"r"(dst), "l"(m), "r"(bar), "r"(c0), "r"(c1), "r"(c2), "l"(0x12F0000000000000ull) : "memory");
}
__device__ __forceinline__ void tma_4d(uint32_t dst, const CUtensorMap* m, uint32_t bar, int c0, int c1, int c2, int c3) {
    asm volatile("cp.async.bulk.tensor.4d.shared::cluster.global.mbarrier::complete_tx::bytes [%0], [%1, {%3, %4, %5, %6}], [%2];" ::"r"(dst), "l"(m), "r"(bar), "r"(c0), "r"(c1), "r"(c2), "r"(c3) : "memory");
}
__device__ __forceinline__ void tma_store_2d(const CUtensorMap* m, uint32_t src, int c0, int c1) {
    asm volatile("cp.async.bulk.tensor.2d.global.shared::cta.bulk_group [%0, {%2, %3}], [%1];" ::"l"(m), "r"(src), "r"(c0), "r"(c1) : "memory");
}
__device__ __forceinline__ void bulk_g2s(uint32_t dst, const void* src, uint32_t bytes, uint32_t bar) {
    asm volatile("cp.async.bulk.shared::cluster.global.mbarrier::complete_tx::bytes [%0], [%1], %2, [%3];" ::"r"(dst), "l"(src), "r"(bytes), "r"(bar) : "memory");
}
__device__ __forceinline__ void bulk_prefetch(const void* p, uint32_t bytes) { asm volatile("cp.async.bulk.prefetch.L2.global [%0], %1;" ::"l"(p), "r"(bytes) : "memory"); }
__device__ __forceinline__ void prefetch_map(const CUtensorMap* m) { asm volatile("prefetch.tensormap [%0];" ::"l"(m) : "memory"); }
__device__ __forceinline__ void fence_async_smem() { asm volatile("fence.proxy.async.shared::cta;" ::: "memory"); }
__device__ __forceinline__ void wg_fence() { asm volatile("wgmma.fence.sync.aligned;" ::: "memory"); }
__device__ __forceinline__ void wg_commit() { asm volatile("wgmma.commit_group.sync.aligned;" ::: "memory"); }
template <int N> __device__ __forceinline__ void wg_wait() { asm volatile("wgmma.wait_group.sync.aligned %0;" ::"n"(N) : "memory"); }
__device__ __forceinline__ uint64_t mkdesc(uint32_t lo, uint32_t hi) { return ((uint64_t)hi << 32) | lo; }
__host__ __device__ constexpr uint32_t dhi(uint32_t sbo, uint32_t mode) { return (sbo >> 4) | (mode << 30); }
__host__ __device__ constexpr uint32_t dlo(uint32_t off, uint32_t lbo) { return (off >> 4) + ((lbo >> 4) << 16); }
__device__ __forceinline__ bool elect_one() {
    uint32_t e;
    asm volatile("{\n.reg .pred p;\nelect.sync _|p, 0xffffffff;\nselp.u32 %0, 1, 0, p;\n}" : "=r"(e));
    return e;
}
template <int R> __device__ __forceinline__ void reg_inc() { asm volatile("setmaxnreg.inc.sync.aligned.u32 %0;" ::"n"(R)); }
template <int R> __device__ __forceinline__ void reg_dec() { asm volatile("setmaxnreg.dec.sync.aligned.u32 %0;" ::"n"(R)); }
__device__ __forceinline__ void bar_sync(int id, int n) { asm volatile("bar.sync %0, %1;" ::"r"(id), "r"(n) : "memory"); }
__device__ __forceinline__ void bar_arrive(int id, int n) { asm volatile("bar.arrive %0, %1;" ::"r"(id), "r"(n) : "memory"); }
__device__ __forceinline__ uint32_t pack_bf16(float lo, float hi) { uint32_t r; asm("cvt.rn.bf16x2.f32 %0, %1, %2;" : "=r"(r) : "f"(hi), "f"(lo)); return r; }
__device__ __forceinline__ float bf_lo(uint32_t u) { return __uint_as_float(u << 16); }
__device__ __forceinline__ float bf_hi(uint32_t u) { return __uint_as_float(u & 0xffff0000u); }
__device__ __forceinline__ float bf16r(float v) { return bf_lo(pack_bf16(v, 0.f)); }
__device__ __forceinline__ uint32_t tagw(uint32_t w, uint32_t m, uint32_t tag) { uint32_t r; asm("lop3.b32 %0, %1, %2, %3, 0xb8;" : "=r"(r) : "r"(w), "r"(m), "r"(tag)); return r; }
__device__ __forceinline__ uint32_t tagf(float f, uint32_t tag) { return tagw(__float_as_uint(f), 1u, tag); }
__device__ __forceinline__ uint32_t movm(uint32_t a) { uint32_t d; asm volatile("movmatrix.sync.aligned.m8n8.trans.b16 %0, %1;" : "=r"(d) : "r"(a)); return d; }
__device__ __forceinline__ void mma16816(float (&c)[4], uint32_t a0, uint32_t a1, uint32_t a2, uint32_t a3, uint32_t b0, uint32_t b1) {
    asm volatile("mma.sync.aligned.m16n8k16.row.col.f32.bf16.bf16.f32 {%0,%1,%2,%3}, {%4,%5,%6,%7}, {%8,%9}, {%0,%1,%2,%3};"
                 : "+f"(c[0]), "+f"(c[1]), "+f"(c[2]), "+f"(c[3]) : "r"(a0), "r"(a1), "r"(a2), "r"(a3), "r"(b0), "r"(b1));
}
__device__ __forceinline__ void mma1688(float (&c)[4], uint32_t a0, uint32_t a1, uint32_t b0) {
    asm volatile("mma.sync.aligned.m16n8k8.row.col.f32.bf16.bf16.f32 {%0,%1,%2,%3}, {%4,%5}, {%6}, {%0,%1,%2,%3};"
                 : "+f"(c[0]), "+f"(c[1]), "+f"(c[2]), "+f"(c[3]) : "r"(a0), "r"(a1), "r"(b0));
}
__device__ __forceinline__ uint32_t ld_rlx(const void* p) { uint32_t v; asm volatile("ld.relaxed.gpu.global.u32 %0, [%1];" : "=r"(v) : "l"(p) : "memory"); return v; }
__device__ __forceinline__ uint2 ld_rlx2(const void* p) { uint2 v; asm volatile("ld.relaxed.gpu.global.v2.u32 {%0,%1}, [%2];" : "=r"(v.x), "=r"(v.y) : "l"(p) : "memory"); return v; }
__device__ __forceinline__ uint4 ld_rlx4(const void* p) { uint4 v; asm volatile("ld.relaxed.gpu.global.v4.u32 {%0,%1,%2,%3}, [%4];" : "=r"(v.x), "=r"(v.y), "=r"(v.z), "=r"(v.w) : "l"(p) : "memory"); return v; }
__device__ __forceinline__ void st_rlx(void* p, uint32_t v) { asm volatile("st.relaxed.gpu.global.u32 [%0], %1;" ::"l"(p), "r"(v) : "memory"); }
__device__ __forceinline__ void st_rlx2(void* p, uint32_t a, uint32_t b) { asm volatile("st.relaxed.gpu.global.v2.u32 [%0], {%1,%2};" ::"l"(p), "r"(a), "r"(b) : "memory"); }
__device__ __forceinline__ void st_rlx4(void* p, uint32_t a, uint32_t b, uint32_t c, uint32_t d) { asm volatile("st.relaxed.gpu.global.v4.u32 [%0], {%1,%2,%3,%4};" ::"l"(p), "r"(a), "r"(b), "r"(c), "r"(d) : "memory"); }
__device__ __forceinline__ uint4 ldg_nc(const void* p) { uint4 v; asm volatile("ld.global.nc.v4.u32 {%0,%1,%2,%3}, [%4];" : "=r"(v.x), "=r"(v.y), "=r"(v.z), "=r"(v.w) : "l"(p)); return v; }
__device__ __forceinline__ uint32_t mism(uint32_t a, uint32_t b, uint32_t tag) { uint32_t r; asm("lop3.b32 %0, %1, %2, %3, 0x7e;" : "=r"(r) : "r"(a), "r"(b), "r"(tag)); return r; }
__device__ __forceinline__ uint32_t mism(const uint4& v, uint32_t tag) { return mism(v.x, v.y, tag) | mism(v.z, v.w, tag); }
__device__ __forceinline__ void prefetch_l2(const void* p) { asm volatile("prefetch.global.L2 [%0];" ::"l"(p)); }
__device__ __forceinline__ void nap(int n) {
#pragma unroll 1
    for (int i = 0; i < n; i++) __nanosleep(100);
}
__device__ __forceinline__ uint32_t now() { uint32_t t; asm volatile("mov.u32 %0, %%globaltimer_lo;" : "=r"(t)); return t; }
__device__ __forceinline__ void until(uint32_t t) {
    while (t - now() - 1 < 16384u) __nanosleep(50);
}
__device__ __forceinline__ uint32_t opaque(uint32_t v) { return __shfl_xor_sync(0xffffffffu, v, 0); }
__device__ __forceinline__ void sts4(uint32_t a, uint32_t x, uint32_t y, uint32_t z, uint32_t w) { asm volatile("st.shared.v4.u32 [%0], {%1,%2,%3,%4};" ::"r"(a), "r"(x), "r"(y), "r"(z), "r"(w) : "memory"); }
__device__ __forceinline__ void sts2(uint32_t a, uint32_t x, uint32_t y) { asm volatile("st.shared.v2.u32 [%0], {%1,%2};" ::"r"(a), "r"(x), "r"(y) : "memory"); }
__device__ __forceinline__ uint4 lds4(uint32_t a) { uint4 v; asm volatile("ld.shared.v4.u32 {%0,%1,%2,%3}, [%4];" : "=r"(v.x), "=r"(v.y), "=r"(v.z), "=r"(v.w) : "r"(a) : "memory"); return v; }
__device__ __forceinline__ float4 lds4f(uint32_t a) { float4 v; asm volatile("ld.shared.v4.f32 {%0,%1,%2,%3}, [%4];" : "=f"(v.x), "=f"(v.y), "=f"(v.z), "=f"(v.w) : "r"(a) : "memory"); return v; }
__device__ __forceinline__ uint2 lds2(uint32_t a) { uint2 v; asm volatile("ld.shared.v2.u32 {%0,%1}, [%2];" : "=r"(v.x), "=r"(v.y) : "r"(a) : "memory"); return v; }
__device__ __forceinline__ float2 lds2f(uint32_t a) { float2 v; asm volatile("ld.shared.v2.f32 {%0,%1}, [%2];" : "=f"(v.x), "=f"(v.y) : "r"(a) : "memory"); return v; }
__device__ __forceinline__ uint32_t lds1(uint32_t a) { uint32_t v; asm volatile("ld.shared.u32 %0, [%1];" : "=r"(v) : "r"(a) : "memory"); return v; }
__device__ __forceinline__ float lds1f(uint32_t a) { return __uint_as_float(lds1(a)); }
__device__ __forceinline__ void sts1(uint32_t a, uint32_t v) { asm volatile("st.shared.u32 [%0], %1;" ::"r"(a), "r"(v) : "memory"); }
__device__ __forceinline__ uint32_t redux_max(uint32_t v) { uint32_t r; asm volatile("redux.sync.max.u32 %0, %1, 0xffffffff;" : "=r"(r) : "r"(v)); return r; }
__device__ __forceinline__ float ex2(float x) { float r; asm("ex2.approx.ftz.f32 %0, %1;" : "=f"(r) : "f"(x)); return r; }
__device__ __forceinline__ float rcp(float x) { float r; asm("rcp.approx.ftz.f32 %0, %1;" : "=f"(r) : "f"(x)); return r; }
__device__ __forceinline__ float sigmoidf(float v) { return rcp(1.f + ex2(v * -1.4426950408889634f)); }

template <int TA, int TB>
__device__ __forceinline__ void wgmma_n192(float (&d)[96], uint64_t da, uint64_t db, int acc = 1) {
    asm volatile("{\n.reg .pred p;\nsetp.ne.b32 p, %100, 0;\n"
        "wgmma.mma_async.sync.aligned.m64n192k16.f32.bf16.bf16 "
        "{%0, %1, %2, %3, %4, %5, %6, %7, %8, %9, %10, %11, %12, %13, %14, %15, "
        "%16, %17, %18, %19, %20, %21, %22, %23, %24, %25, %26, %27, %28, %29, %30, %31, "
        "%32, %33, %34, %35, %36, %37, %38, %39, %40, %41, %42, %43, %44, %45, %46, %47, "
        "%48, %49, %50, %51, %52, %53, %54, %55, %56, %57, %58, %59, %60, %61, %62, %63, "
        "%64, %65, %66, %67, %68, %69, %70, %71, %72, %73, %74, %75, %76, %77, %78, %79, "
        "%80, %81, %82, %83, %84, %85, %86, %87, %88, %89, %90, %91, %92, %93, %94, %95}, "
        "%96, %97, p, 1, 1, %98, %99;\n}\n"
        : "+f"(d[0]), "+f"(d[1]), "+f"(d[2]), "+f"(d[3]), "+f"(d[4]), "+f"(d[5]), "+f"(d[6]), "+f"(d[7]),
          "+f"(d[8]), "+f"(d[9]), "+f"(d[10]), "+f"(d[11]), "+f"(d[12]), "+f"(d[13]), "+f"(d[14]), "+f"(d[15]),
          "+f"(d[16]), "+f"(d[17]), "+f"(d[18]), "+f"(d[19]), "+f"(d[20]), "+f"(d[21]), "+f"(d[22]), "+f"(d[23]),
          "+f"(d[24]), "+f"(d[25]), "+f"(d[26]), "+f"(d[27]), "+f"(d[28]), "+f"(d[29]), "+f"(d[30]), "+f"(d[31]),
          "+f"(d[32]), "+f"(d[33]), "+f"(d[34]), "+f"(d[35]), "+f"(d[36]), "+f"(d[37]), "+f"(d[38]), "+f"(d[39]),
          "+f"(d[40]), "+f"(d[41]), "+f"(d[42]), "+f"(d[43]), "+f"(d[44]), "+f"(d[45]), "+f"(d[46]), "+f"(d[47]),
          "+f"(d[48]), "+f"(d[49]), "+f"(d[50]), "+f"(d[51]), "+f"(d[52]), "+f"(d[53]), "+f"(d[54]), "+f"(d[55]),
          "+f"(d[56]), "+f"(d[57]), "+f"(d[58]), "+f"(d[59]), "+f"(d[60]), "+f"(d[61]), "+f"(d[62]), "+f"(d[63]),
          "+f"(d[64]), "+f"(d[65]), "+f"(d[66]), "+f"(d[67]), "+f"(d[68]), "+f"(d[69]), "+f"(d[70]), "+f"(d[71]),
          "+f"(d[72]), "+f"(d[73]), "+f"(d[74]), "+f"(d[75]), "+f"(d[76]), "+f"(d[77]), "+f"(d[78]), "+f"(d[79]),
          "+f"(d[80]), "+f"(d[81]), "+f"(d[82]), "+f"(d[83]), "+f"(d[84]), "+f"(d[85]), "+f"(d[86]), "+f"(d[87]),
          "+f"(d[88]), "+f"(d[89]), "+f"(d[90]), "+f"(d[91]), "+f"(d[92]), "+f"(d[93]), "+f"(d[94]), "+f"(d[95])
        : "l"(da), "l"(db), "n"(TA), "n"(TB), "r"(acc));
}
template <int TA, int TB>
__device__ __forceinline__ void wgmma_n128(float (&d)[64], uint64_t da, uint64_t db, int acc = 1) {
    asm volatile("{\n.reg .pred p;\nsetp.ne.b32 p, %68, 0;\n"
        "wgmma.mma_async.sync.aligned.m64n128k16.f32.bf16.bf16 "
        "{%0, %1, %2, %3, %4, %5, %6, %7, %8, %9, %10, %11, %12, %13, %14, %15, "
        "%16, %17, %18, %19, %20, %21, %22, %23, %24, %25, %26, %27, %28, %29, %30, %31, "
        "%32, %33, %34, %35, %36, %37, %38, %39, %40, %41, %42, %43, %44, %45, %46, %47, "
        "%48, %49, %50, %51, %52, %53, %54, %55, %56, %57, %58, %59, %60, %61, %62, %63}, "
        "%64, %65, p, 1, 1, %66, %67;\n}\n"
        : "+f"(d[0]), "+f"(d[1]), "+f"(d[2]), "+f"(d[3]), "+f"(d[4]), "+f"(d[5]), "+f"(d[6]), "+f"(d[7]),
          "+f"(d[8]), "+f"(d[9]), "+f"(d[10]), "+f"(d[11]), "+f"(d[12]), "+f"(d[13]), "+f"(d[14]), "+f"(d[15]),
          "+f"(d[16]), "+f"(d[17]), "+f"(d[18]), "+f"(d[19]), "+f"(d[20]), "+f"(d[21]), "+f"(d[22]), "+f"(d[23]),
          "+f"(d[24]), "+f"(d[25]), "+f"(d[26]), "+f"(d[27]), "+f"(d[28]), "+f"(d[29]), "+f"(d[30]), "+f"(d[31]),
          "+f"(d[32]), "+f"(d[33]), "+f"(d[34]), "+f"(d[35]), "+f"(d[36]), "+f"(d[37]), "+f"(d[38]), "+f"(d[39]),
          "+f"(d[40]), "+f"(d[41]), "+f"(d[42]), "+f"(d[43]), "+f"(d[44]), "+f"(d[45]), "+f"(d[46]), "+f"(d[47]),
          "+f"(d[48]), "+f"(d[49]), "+f"(d[50]), "+f"(d[51]), "+f"(d[52]), "+f"(d[53]), "+f"(d[54]), "+f"(d[55]),
          "+f"(d[56]), "+f"(d[57]), "+f"(d[58]), "+f"(d[59]), "+f"(d[60]), "+f"(d[61]), "+f"(d[62]), "+f"(d[63])
        : "l"(da), "l"(db), "n"(TA), "n"(TB), "r"(acc));
}
template <int TB>
__device__ __forceinline__ void wgmma_rs_n128(float (&d)[64], uint32_t a0, uint32_t a1, uint32_t a2, uint32_t a3, uint64_t db) {
    asm volatile("{\n.reg .pred p;\nsetp.ne.b32 p, 1, 0;\n"
        "wgmma.mma_async.sync.aligned.m64n128k16.f32.bf16.bf16 "
        "{%0, %1, %2, %3, %4, %5, %6, %7, %8, %9, %10, %11, %12, %13, %14, %15, "
        "%16, %17, %18, %19, %20, %21, %22, %23, %24, %25, %26, %27, %28, %29, %30, %31, "
        "%32, %33, %34, %35, %36, %37, %38, %39, %40, %41, %42, %43, %44, %45, %46, %47, "
        "%48, %49, %50, %51, %52, %53, %54, %55, %56, %57, %58, %59, %60, %61, %62, %63}, "
        "{%64, %65, %66, %67}, %68, p, 1, 1, %69;\n}\n"
        : "+f"(d[0]), "+f"(d[1]), "+f"(d[2]), "+f"(d[3]), "+f"(d[4]), "+f"(d[5]), "+f"(d[6]), "+f"(d[7]),
          "+f"(d[8]), "+f"(d[9]), "+f"(d[10]), "+f"(d[11]), "+f"(d[12]), "+f"(d[13]), "+f"(d[14]), "+f"(d[15]),
          "+f"(d[16]), "+f"(d[17]), "+f"(d[18]), "+f"(d[19]), "+f"(d[20]), "+f"(d[21]), "+f"(d[22]), "+f"(d[23]),
          "+f"(d[24]), "+f"(d[25]), "+f"(d[26]), "+f"(d[27]), "+f"(d[28]), "+f"(d[29]), "+f"(d[30]), "+f"(d[31]),
          "+f"(d[32]), "+f"(d[33]), "+f"(d[34]), "+f"(d[35]), "+f"(d[36]), "+f"(d[37]), "+f"(d[38]), "+f"(d[39]),
          "+f"(d[40]), "+f"(d[41]), "+f"(d[42]), "+f"(d[43]), "+f"(d[44]), "+f"(d[45]), "+f"(d[46]), "+f"(d[47]),
          "+f"(d[48]), "+f"(d[49]), "+f"(d[50]), "+f"(d[51]), "+f"(d[52]), "+f"(d[53]), "+f"(d[54]), "+f"(d[55]),
          "+f"(d[56]), "+f"(d[57]), "+f"(d[58]), "+f"(d[59]), "+f"(d[60]), "+f"(d[61]), "+f"(d[62]), "+f"(d[63])
        : "r"(a0), "r"(a1), "r"(a2), "r"(a3), "l"(db), "n"(TB));
}
template <int TA, int TB>
__device__ __forceinline__ void wgmma_n8(float (&d)[4], uint64_t da, uint64_t db, int acc = 1) {
    asm volatile("{\n.reg .pred p;\nsetp.ne.b32 p, %8, 0;\n"
        "wgmma.mma_async.sync.aligned.m64n8k16.f32.bf16.bf16 "
        "{%0, %1, %2, %3}, "
        "%4, %5, p, 1, 1, %6, %7;\n}\n"
        : "+f"(d[0]), "+f"(d[1]), "+f"(d[2]), "+f"(d[3])
        : "l"(da), "l"(db), "n"(TA), "n"(TB), "r"(acc));
}

__device__ __forceinline__ uint32_t sub2(uint32_t a, uint32_t b) { uint32_t r; asm("sub.rn.bf16x2 %0, %1, %2;" : "=r"(r) : "r"(a), "r"(b)); return r; }

struct Roles { uint16_t v[132]; };

__global__ void __launch_bounds__(512, 1)
fused_kernel(int by_sm, const __nv_bfloat16* __restrict__ x, const __nv_bfloat16* __restrict__ wqkv, const __nv_bfloat16* __restrict__ wr,
             Scratch* const S, const char* __restrict__ wg, const char* __restrict__ wu, const char* __restrict__ wd, const char* __restrict__ wo, uint8_t* __restrict__ out,
             const __grid_constant__ Roles roles,
             const __grid_constant__ CUtensorMap mw, const __grid_constant__ CUtensorMap mx, const __grid_constant__ CUtensorMap mwo,
             const __grid_constant__ CUtensorMap mxs, const __grid_constant__ CUtensorMap mcs, const __grid_constant__ CUtensorMap mout, const __grid_constant__ CUtensorMap mgu, const __grid_constant__ CUtensorMap mwd) {
    extern __shared__ __align__(1024) uint8_t smem[];
    constexpr uint32_t sb = 1024, bars = sb + OFF_BAR, sd = sb >> 4;
    const int tid = threadIdx.x, lane = tid & 31;
    asm volatile("{\n.reg .pred p, q;\nsetp.lt.u32 p, %2, 16;\nsetp.lt.u32 q, %2, 24;\n@p prefetch.global.L2 [%0];\n@p prefetch.global.L2 [%0 + 128];\n@q prefetch.global.L2 [%1];\n}" ::
                 "l"((const char*)x + (blockIdx.x * 16 + tid - 32) % 2048 * 2048), "l"((const char*)wqkv + (blockIdx.x * 24 + tid - 32) * 128), "r"(tid - 32));
    const int warp = __shfl_sync(0xffffffffu, tid >> 5, 0);
    uint32_t smid;
    asm volatile("mov.u32 %0, %%smid;" : "=r"(smid));
    const int role = roles.v[by_sm ? smid : blockIdx.x], fb = role & 255, b = role >> 8, kc = fb >> 4, c2 = fb & 15;
    const int mt = b >> 4, nt = b & 15, hp = b & 1, cb = nt >> 1;
    const int par = mt >> 2, j0 = (mt & 3) * 256;
    uint8_t* const g_o = S->o;

    auto load_stage = [&](int p, uint32_t so, int bi) {
        const uint32_t fullA = bars + 8 * (B_FULLA + bi), fullB = bars + 8 * (B_FULLB + bi);
        mbar_expect_tx(fullA, 40960);
        tma_3d(sb + so + 16384, &mw, fullA, nt * 64, p * 64, 0);
        tma_4d(sb + so, &mx, fullA, par * 1024 + p * 64, 0, (j0 >> 5) + 4, 0);
        mbar_expect_tx(fullB, 16384);
        tma_4d(sb + so + 40960, &mx, fullB, par * 1024 + p * 64, 0, j0 >> 5, 0);
    };
    if (warp == 0 && fb < 128 && elect_one()) {
        mbar_init(bars + 8 * B_FULLA, 1); mbar_init(bars + 8 * B_FULLB, 1);
        load_stage(0, STAGE, 0);
    }
    if (fb >= 128) {
        const uint32_t epoch = ld_rlx(&S->epoch), tag = (epoch & 1) - 1;
        if (fb > 128) {
#pragma unroll 1
            for (int it = 0; it < 64 && warp == 0 && ld_rlx(&S->epoch) == epoch; it++) __nanosleep(500);
            TS_END();
            return;
        }
        if (tid < 8) st_rlx2(&S->sel[tid], ~tag, ~tag);
        uint4 ra, rb;
#pragma unroll 1
        for (int it = 0; it < SPIN_LIMIT; it++) {
            ra = ld_rlx4(&S->rec[tid * 2]); rb = ld_rlx4(&S->rec[1024 + tid * 2]);
            if (!__any_sync(0xffffffffu, (mism(ra.x, ra.z, tag) | mism(rb.x, rb.z, tag)) & 0x8000u)) break;
        }
        __syncwarp();
        TSC(tid == 0, 31);
        sts4(sb + 1024 + tid * 16, ra.y, rb.y, ra.w, rb.w);
        uint4 k = make_uint4(ra.x, ra.z, rb.x, rb.z);
        uint32_t cand;
#pragma unroll 1
        for (int pass = 0; pass < 2; pass++) {
            const uint32_t a0 = max(k.x, k.y), a1 = min(k.x, k.y), a2 = max(k.z, k.w), a3 = min(k.z, k.w), c1 = min(a0, a2), c2 = max(a1, a3);
            k = make_uint4(max(a0, a2), max(c1, c2), min(c1, c2), min(a1, a3));
#pragma unroll
            for (int r = 0; r < 8; r++) {
                const uint32_t m = redux_max(k.x);
                if (lane == r) cand = m;
                if (k.x == m) k = make_uint4(k.y, k.z, k.w, 0);
            }
            if (pass) break;
            if (lane < 8) sts1(sb + (warp * 8 + lane) * 4, cand);
            __syncthreads();
            if (warp) { TS_END(); return; }
            k = lds4(sb + lane * 16);
            TSC(TIMING == 12 && tid == 0 && k.x != 0x12345, 40);
        }
        if (lane < 8) st_rlx2(&S->sel[lane], cand, lds1(sb + 1024 + (~cand & 0x7ffu) * 4));
        TSC(tid == 0, 20);
        TS_END();
        return;
    }
    auto ffn_w = [&](int n, int s) {
        const uint32_t dst = sb + OFF_FW + s * 16384;
        if (n < 8) {
            mbar_expect_tx(bars + 8 * (B_FFULL + s), 16384);
            tma_3d_once(dst, &mgu, bars + 8 * (B_FFULL + s), fb * 32, n * 128, 0);
        } else {
            mbar_expect_tx(bars + 8 * B_F2FULL, 16384);
            tma_2d_once(dst, &mwd, bars + 8 * B_F2FULL, c2 * 64, kc * 448 + 64 + s * 128);
            tma_2d_once(dst + 8192, &mwd, bars + 8 * B_F2FULL, c2 * 64, kc * 448 + 128 + s * 128);
        }
    };
    if (warp == 1 && elect_one()) {
#pragma unroll
        for (int i = 0; i < B_FDONE; i++)
            if (i != B_FULLA && i != B_FULLB) mbar_init(bars + 8 * i, i >= B_FFULL && i < B_F2DONE ? 2 : 1);
    }
    if (warp == 4 && elect_one()) {
#pragma unroll
        for (int i = B_EMPTY; i < NBAR; i++) mbar_init(bars + 8 * i, i < B_UPD ? 2 : i < B_AUX ? 4 : i == B_AUX ? 7 : i == B_CSDONE ? 3 : 8);
    }
    if (warp >= 8 && elect_one()) {
#pragma unroll
        for (int i = 0; i < (B_EMPTY - B_FDONE) / 8; i++) mbar_init(bars + 8 * (B_FDONE + 8 * i - 8 + warp), 1);
    }
    uint32_t epoch;
    if (warp >> 2 == 2) epoch = ld_rlx(&S->epoch);
    __syncthreads();

    if (warp >= 12) {
        reg_dec<24>();
        if (warp > 12) {
            const int p = warp - 13;
            if (p == 1) {
                float sw = 0.f;
                mbar_wait(bars + 8 * (B_ROW + 4), 0);
#pragma unroll 1
                for (int i = 0; i < 16; i++) { const uint32_t q = lds1(sb + OFF_FA + i * 128 + lane * 4); sw += bf_lo(q) + bf_hi(q); }
#pragma unroll 1
                for (int o = 1; o < 32; o <<= 1) sw += __shfl_xor_sync(0xffffffffu, sw, o);
                if (lane == 0) { sts1(sb + OFF_TAG + 4, __float_as_uint(sw)); mbar_arrive(bars + 8 * B_SW); }
            } else {
#pragma unroll 1
                for (int q = 0; q < 4; q++) {
                    nap(p ? (q ? D_R : N_ROW) : (q ? D_X : N_X));
                    if (p == 0) {
                        const __nv_bfloat16* xp = x + (size_t)((j0 + nt * 16 + (lane >> 1)) * 2 + par) * 1024 + q * 256 + (lane & 1) * 64;
                        if (q) prefetch_l2(xp);
                        prefetch_l2(xp + 128);
                    } else if (elect_one()) {
                        mbar_expect_tx(bars + 8 * (B_ROW + q), 8192);
                        tma_3d(sb + OFF_FW + q * 8192, &mxs, bars + 8 * (B_ROW + q), 0, j0 + nt * 16, par * 16 + q * 4);
                    }
                }
                if (p == 0) nap(N_CS);
            }
            const uint32_t stg = sb + OFF_FW + 32768 + p * 4096 + lane * 16;
            float c[8];
#pragma unroll
            for (int i = 0; i < 8; i++) c[i] = 0.f;
#pragma unroll 1
            for (int n = 0; n < 10; n++) {
                const uint32_t bo = (n & 1) * 2048, bar = bars + 8 * (B_CS + 2 * p + (n & 1));
                if (n >= 2) {
                    mbar_wait(bar, ~(n >> 1) & 1);
#pragma unroll 2
                    for (int i = 0; i < 4; i++) {
                        const uint4 v = lds4(stg + bo + i * 512);
                        c[0] += bf_lo(v.x); c[1] += bf_hi(v.x); c[2] += bf_lo(v.y); c[3] += bf_hi(v.y);
                        c[4] += bf_lo(v.z); c[5] += bf_hi(v.z); c[6] += bf_lo(v.w); c[7] += bf_hi(v.w);
                    }
                    asm volatile("" :: "f"(c[7]));
                    __syncwarp();
                }
                if (n < 8 && elect_one()) {
                    mbar_expect_tx(bar, 2048);
                    tma_3d(sb + OFF_FW + 32768 + p * 4096 + bo, &mcs, bar, p * 1024 + nt * 64, mt * 8, 2 * n);
                }
            }
            sts4(stg + lane * 16, __float_as_uint(c[0]), __float_as_uint(c[1]), __float_as_uint(c[2]), __float_as_uint(c[3]));
            sts4(stg + lane * 16 + 16, __float_as_uint(c[4]), __float_as_uint(c[5]), __float_as_uint(c[6]), __float_as_uint(c[7]));
            bar_sync(13, 128);
            const uint32_t tag = lds1(sb + OFF_TAG);
            float* gcs = &S->cs[0][p * 1024 + nt * 64];
            {
                const float2 a0 = lds2f(stg - lane * 8), a1 = lds2f(stg - lane * 8 + 256), a2 = lds2f(stg - lane * 8 + 512), a3 = lds2f(stg - lane * 8 + 768);
                st_rlx2(gcs + mt * 3072 + lane * 2, tagf((a0.x + a1.x) + (a2.x + a3.x), tag), __float_as_uint((a0.y + a1.y) + (a2.y + a3.y)));
            }
            fence_async_smem();
            __syncwarp();
            if (lane == 0) mbar_arrive(bars + 8 * B_CSDONE);
            TSC(warp == 13 && lane == 0, 19);
            {
                uint4 v[4];
                const float* src = gcs + (lane >> 4) * 4 * 3072 + (lane & 15) * 4;
                nap(N_C2);
#pragma unroll 1
                for (int it = 0; it < SPIN_LIMIT; it++) {
#pragma unroll
                    for (int m = 0; m < 4; m++) v[m] = ld_rlx4(src + m * 3072);
                    if (!__any_sync(0xffffffffu, (mism(v[0].x, v[1].x, tag) | mism(v[2].x, v[3].x, tag)) & 1)) break;
                }
                __syncwarp();
#pragma unroll
                for (int c = 0; c < 4; c++) {
                    const float a = (__uint_as_float((&v[0].x)[c]) + __uint_as_float((&v[1].x)[c])) + (__uint_as_float((&v[2].x)[c]) + __uint_as_float((&v[3].x)[c]));
                    (&v[0].x)[c] = __float_as_uint(a + __shfl_xor_sync(0xffffffffu, a, 16));
                }
                const uint32_t ca = sb + OFF_CS + p * 384 + ((lane & 15) >> 1) * 48 + (lane & 1) * 8;
#pragma unroll 1
                for (int r = 0; r < 3; r++) {
                    const uint32_t u0 = pack_bf16(__uint_as_float(v[0].x), __uint_as_float(v[0].y)), u1 = pack_bf16(__uint_as_float(v[0].z), __uint_as_float(v[0].w));
                    sts2(ca + r * 16, u0, u1);
                    v[0].x = __float_as_uint(__uint_as_float(v[0].x) - bf_lo(u0)); v[0].y = __float_as_uint(__uint_as_float(v[0].y) - bf_hi(u0));
                    v[0].z = __float_as_uint(__uint_as_float(v[0].z) - bf_lo(u1)); v[0].w = __float_as_uint(__uint_as_float(v[0].w) - bf_hi(u1));
                }
                if (lane < 20) sts1(sb + OFF_CS + 1152 + lane * 4, 0);
                fence_async_smem();
            }
            if (p == 1) { if (lane < 2) st_rlx4(&S->hint[b][lane * 4], ~tag, ~tag, ~tag, ~tag); }
            else { st_rlx4(&S->halo[b][p * 128 + lane * 4], ~tag, ~tag, ~tag, ~tag); st_rlx4(&S->halo[b][p * 128 + 128 + lane * 4], ~tag, ~tag, ~tag, ~tag); }
            __syncwarp();
            if (lane == 0) mbar_arrive(bars + 8 * B_AUX);
            TSC(warp == 13 && lane == 0, 21);
            mbar_wait(bars + 8 * B_PART, 0);
            mbar_wait(bars + 8 * (B_EMPTY + 2), 0);
            if (p == 0) {
                if (j0) {
                    nap(N_HA);
#pragma unroll 1
                    for (int it = 0; it < SPIN_LIMIT; it++) {
                        TSC(TIMING == 15 && lane == 0 && it < 8, 40 + it);
                        if (elect_one()) { mbar_expect_tx(bars + 8 * B_CS, 2048); bulk_g2s(sb + OFF_HALO, S->halo[b - 16], 2048, bars + 8 * B_CS); }
                        mbar_wait(bars + 8 * B_CS, it & 1);
                        const uint32_t a = sb + OFF_HALO + lane * 16;
                        if (!__any_sync(0xffffffffu, (mism(lds1(a), lds1(a + 512), tag) | mism(lds1(a + 1024), lds1(a + 1536), tag)) & 1)) break;
                    }
                } else {
#pragma unroll
                    for (int c = 0; c < 4; c++) sts4(sb + OFF_HALO + c * 512 + lane * 16, 0, 0, 0, 0);
                }
                __syncwarp();
                bar_arrive(3, 64);
                TSC(TIMING >= 11 && lane == 0, 34);
            } else {
                const int w = p - 1;
                const uint8_t* osrc = g_o + (size_t)((mt * 2 + hp) * 2 + w) * 131072;
                const bool far = w > hp && j0 && lane >= 16;
                const uint32_t* hsrc = &S->hint[b & 0x70][0] + ((lane & 15) - (far ? 16 : 0)) * 8;
                if (lane == 0 && !w) st_rlx(&S->hint[b][0], tagw(now(), 1u, tag));
                uint32_t hv;
                nap(N_HI);
#pragma unroll 1
                for (int it = 0; it < SPIN_LIMIT; it++) {
                    hv = ld_rlx(hsrc);
                    if (!__any_sync(0xffffffffu, (hv ^ tag) & 1)) break;
                }
                TSC(TIMING == 11 && lane == 0, 32 + w);
                const uint32_t tn = __shfl_sync(0xffffffffu, hv, 0) - 0x40000000u;
                hv = redux_max(hv - tn + (far ? T_H : 0)) + tn + T_O + w * T_O1;
                mbar_wait(bars + 8 * (w ? B_AST : B_G1DONE), 0);
                if (elect_one()) {
#pragma unroll 1
                    for (int st = 0; st < 8; st++) {
                        const uint32_t full = bars + 8 * (B_OFULL + 8 * w + st);
                        if (st >= 2) mbar_wait(full + 8 * (B_DONE - B_OFULL - 2), 0);
                        if (st < 3) until(hv + (st == 2 ? T_S2 : st * T_S1));
                        TSC(st == 0, 28 + w);
                        mbar_expect_tx(full, 16384);
                        bulk_g2s(sb + (w ? OFF_O1 : OFF_O0) + (st & 1) * 16384, osrc + st * 16384, 16384, full);
                    }
                }
            }
            TS_END();
            return;
        }
        if (elect_one()) {
            auto load_wo = [&](int s, uint32_t ws) {
                mbar_expect_tx(bars + 8 * (B_WOFULL + s), 32768);
                tma_4d(ws, &mwo, bars + 8 * (B_WOFULL + s), 0, s * 8, 0, cb * 2);
            };
            uint32_t so = 2 * STAGE, ph = 1, cnt = PF_CNT << 4;
            int bi = 1, q = 0;
            mbar_expect_tx(bars + 8 * (B_ROW + 4), 2048);
            bulk_g2s(sb + OFF_FA, wr, 2048, bars + 8 * (B_ROW + 4));
            if (smem_u32(smem) != sb) __trap();
            prefetch_map(&mxs); prefetch_map(&mcs);
            const char* pf = (b < 64 ? wg : wu) + (b & 63) * 7168;
#pragma unroll 1
            for (int p = 1; p < 16; p++) {
                if (p < 3) nap(p == 1 ? N_S1 : N_S2);
                mbar_wait(bars + 8 * (B_EMPTY + bi), ph);
                load_stage(p, so, bi);
                if (p >= 2 && p < 5) {
                    const int k0 = p == 2 ? 3 : p == 3 ? K_W1 : K_W2, n = ((p == 2 ? K_W1 : p == 3 ? K_W2 : 16) - k0) * 3072;
                    if (p == 2) nap(N_W);
                    bulk_prefetch((const char*)wqkv + k0 * 393216 + b * n, n);
                }
#pragma unroll 1
                for (int e = q + (cnt & 3); q < e; q++) {
                    if (q == 16) pf = wd + mt * 7 * 131072 + nt * 8192;
                    if (q == 23) pf = wo + b * 8192;
                    bulk_prefetch(pf, q < 16 ? 7168 : 8192);
                    pf += q < 16 ? 64 * 7168 : q < 23 ? 131072 : 1048576;
                }
                cnt >>= 2;
                so = so == 2 * STAGE ? 0 : so + STAGE;
                if (++bi == 3) { bi = 0; ph ^= 1; }
            }
            TS(27);
            uint32_t ws = sb + OFF_WO0;
#pragma unroll 1
            for (int i = 0; i < 8; i++) {
                if (i < 2) {
                    mbar_wait(bars + 8 * (B_EMPTY + 1 + i), 0);
                    mbar_expect_tx(bars + 8 * B_XR, 16384);
                    tma_4d(sb + (i ? 0 : OFF_X1), &mx, bars + 8 * B_XR, par * 1024 + cb * 128 + 64 - i * 64, 0, (j0 >> 5) + hp * 4, 0);
                }
                if (i == 1) {
                    mbar_expect_tx(bars + 8 * B_F2FULL, 8192);
                    tma_2d_once(sb + OFF_F2X, &mwd, bars + 8 * B_F2FULL, c2 * 64, kc * 448);
                }
                if (i) {
                    mbar_wait(bars + 8 * (i == 1 ? B_G1DONE : i == 2 ? B_F2DONE : B_DONE - NWO + i), 0);
                    if (i > 1) mbar_wait(bars + 8 * (i == 2 ? B_OFULL + 8 : B_DONE + 8 - NWO + i), 0);
                }
                load_wo(i, ws);
                if (i == 4) prefetch_map(&mout);
                ws = wo_next(ws, sb, 0);
            }
        }
        TS_END();
    } else if (warp >= 8) {
        reg_dec<40>();
        const int p = warp - 8;
        const bool f1 = fb < 112;
        const uint32_t tag = (epoch & 1) - 1;
        {
            const int ta = tid - 256;
            if (ta < 48) st_rlx4(&S->cs[mt][(ta >> 4) * 1024 + nt * 64 + (ta & 15) * 4], ~tag, ~tag, ~tag, ~tag);
        }
        float s1 = 0.f, s2 = 0.f, sr = 0.f, sw, sh = 0.f;
        {
            const uint32_t xa = sb + OFF_FW + p * 512 + lane * 16, wa = sb + OFF_FA + (((p * 4 + (lane >> 3)) ^ lane) & 7) * 16;
            TSC(TIMING == 12 && lane == 0, 50 + p);
            mbar_wait(bars + 8 * (B_ROW + 4), 0);
            {
                float c1 = 0.f, c2 = 0.f, cr = 0.f;
#pragma unroll 1
                for (int q = 0; q < 4; q++) {
                mbar_wait(bars + 8 * (B_ROW + q), 0);
                TSC(TIMING == 12 && tid == 256 + 96, 32 + q);
                TSC(tid == 256 && q == 3, 17);
#pragma unroll
                for (int i = 0; i < 4; i++) {
                    const uint4 u = lds4(xa + q * 8192 + i * 2048), w4 = lds4(wa + q * 512 + i * 128);
                    const float a0 = bf_lo(u.x), a1 = bf_hi(u.x), a2 = bf_lo(u.y), a3 = bf_hi(u.y), a4 = bf_lo(u.z), a5 = bf_hi(u.z), a6 = bf_lo(u.w), a7 = bf_hi(u.w);
                    s1 += a0 + a1; c1 += a4 + a5; s1 += a2 + a3; c1 += a6 + a7;
                    s2 = fmaf(a0, a0, s2); c2 = fmaf(a4, a4, c2); sr = fmaf(a0, bf_lo(w4.x), sr); cr = fmaf(a4, bf_lo(w4.z), cr);
                    s2 = fmaf(a1, a1, s2); c2 = fmaf(a5, a5, c2); sr = fmaf(a1, bf_hi(w4.x), sr); cr = fmaf(a5, bf_hi(w4.z), cr);
                    s2 = fmaf(a2, a2, s2); c2 = fmaf(a6, a6, c2); sr = fmaf(a2, bf_lo(w4.y), sr); cr = fmaf(a6, bf_lo(w4.w), cr);
                    s2 = fmaf(a3, a3, s2); c2 = fmaf(a7, a7, c2); sr = fmaf(a3, bf_hi(w4.y), sr); cr = fmaf(a7, bf_hi(w4.w), cr);
                }
                }
                s1 += c1; s2 += c2; sr += cr;
            }
            mbar_wait(bars + 8 * B_SW, 0);
            sw = lds1f(sb + OFF_TAG + 4);
#pragma unroll 1
            for (int pass = 0;; pass++) {
#pragma unroll
                for (int o = 1; o < 8; o <<= 1) {
                    s1 += __shfl_xor_sync(0xffffffffu, s1, o); s2 += __shfl_xor_sync(0xffffffffu, s2, o); sr += __shfl_xor_sync(0xffffffffu, sr, o);
                }
                s1 *= 1.f / 1024.f;
                s2 = fmaf(-s1, s1, s2 * (1.f / 1024.f));
                if (!__any_sync(0xffffffffu, !pass && s1 * s1 > 256.f * s2)) break;
                sh = bf16r(s1); s1 = 0.f; s2 = 0.f; sr = 0.f;
#pragma unroll 1
                for (uint32_t o = 0; o < 2048; o = opaque(o + ((o & 12) == 12 ? 116 : 4))) {
                    const uint32_t u = lds1(xa + (o >> 7) * 2048 + (o & 12)), q = lds1(wa + o);
                    const float a0 = bf_lo(u) - sh, a1 = bf_hi(u) - sh;
                    s1 += a0 + a1; s2 = fmaf(a0, a0, fmaf(a1, a1, s2)); sr = fmaf(a0, bf_lo(q), fmaf(a1, bf_hi(q), sr));
                }
            }
        }
        const int ta = opaque(tid) - 256, lane = ta & 31, g = lane >> 2, t = lane & 3;
        {
            if ((lane & 7) == 0) {
                const int s = b * 16 + p * 4 + (lane >> 3);
                const float mb = bf16r(sh + s1);
                float den;
                asm("sqrt.approx.f32 %0, %1;" : "=f"(den) : "f"(bf16r(bf16r(s2) + 1e-5f)));
                den = bf16r(den);
                uint32_t rb = pack_bf16(fmaf(sh - mb, sw, sr) * rcp(den), 0.f);
                if (rb == 0x8000u) rb = 0;
                uint32_t ord = (rb & 0x8000u) ? (~rb & 0xffffu) : (rb | 0x8000u);
                if ((rb & 0x7fffu) > 0x7f80u) ord = 0;
                st_rlx2(&S->rec[s], (ord << 16) | (tag & 0x8000u) | (0x47ffu - (s & 1023) * 2 - par), pack_bf16(mb, den));
            }
            TSC(TIMING == 12 && lane == 0, 36 + p);
            bar_sync(12, 128);
            if (p == 1) sts1(sb + OFF_ROWMAP + lane * 4, 0xffffffffu);
            if (p == 0) {
                if (lane == 0) {
                    sts1(sb + OFF_TAG, tag);
                }
                __syncwarp();
                bar_arrive(13, 128);
            }
            TSC(ta == 0, 18);
        }
        {
            uint2 r[3];
            nap(N_GA);
            const uint2* src = &S->rec[mt * 256 + ta];
            const int l2 = ta < 8 && j0 ? -8 : 0;
#pragma unroll 1
            for (int it = 0; it < SPIN_LIMIT; it++) {
                r[0] = ld_rlx2(src + l2); r[1] = ld_rlx2(src); r[2] = ld_rlx2(src + 128);
                if (!__any_sync(0xffffffffu, (mism(r[0].x, r[1].x, tag) | (r[2].x ^ tag)) & 0x8000u)) break;
            }
#pragma unroll
            for (int n = 0; n < 3; n++)
                if (n || ta < 8) sts2(sb + OFF_STAT + (n ? n * 1024 - 960 : 0) + ta * 8, (r[n].y << 16) ^ 0x80000000u, __float_as_uint(rcp(bf_hi(r[n].y))));
        }
        __syncwarp();
        if (lane == 0) mbar_arrive(bars + 8 * B_AUX);
        TSC(ta == 0, 30);
        if (p == 1) nap(N_F1);
        if (f1 && p < 2 && elect_one()) ffn_w(p, p);
        uint2 sel;
#pragma unroll 1
        for (int it = 0; it < SPIN_LIMIT; it++) {
            sel = ld_rlx2(&S->sel[lane & 7]);
            if (!__any_sync(0xffffffffu, (sel.x ^ tag) & 0x8000u)) break;
            __nanosleep(POLL_NS);
        }
        TSC(ta == 0, 26);
        if (b == 0 && ta == 0) st_rlx(&S->epoch, epoch + 1);
        {
            const __nv_bfloat16* xp = x + (~sel.x & 0x7ffu) * 1024 + (lane >> 3) * 8;
            const uint32_t mb = __byte_perm(sel.y, 0, 0x1010);
            if (p >= 2) nap(N_A2);
#pragma unroll 1
            for (int n = p; n < (f1 ? 8 : 0); n += 4) {
                uint4 v[4];
#pragma unroll
                for (int c = 0; c < 4; c++) v[c] = ldg_nc(xp + n * 128 + c * 32);
                const int s = n % 3;
                if (n >= 2) {
                    mbar_wait(bars + 8 * (n == 2 ? B_CSDONE : B_FDONE + n - 3), 0);
                    if (elect_one()) ffn_w(n & 7, s);
                }
#pragma unroll
                for (int c = 0; c < 4; c++) sts4(sb + OFF_FA + s * 2048 + c * 512 + lane * 16, sub2(v[c].x, mb), sub2(v[c].y, mb), sub2(v[c].z, mb), sub2(v[c].w, mb));
                fence_async_smem();
                __syncwarp();
                if (lane == 0) mbar_arrive(bars + 8 * (B_FFULL + s));
                TSC(TIMING == 12 && lane == 0, 41 + n);
            }
            if (p < 3) {
                mbar_wait(bars + 8 * B_CSDONE, 0);
                mbar_wait(bars + 8 * (f1 ? B_FDONE + 5 + p : B_PART), 0);
                if (elect_one()) ffn_w(8, p ? p - 1 : 2);
            }
        }
        const bool hw = f1 && (p == 0 || p == 3);
        if (hw) st_rlx4(&S->h[fb * 128 + (p & 1) * 64 + (lane & 15) * 4], ~tag, ~tag, ~tag, ~tag);
        st_rlx4(&S->ypart[kc][ta >> 4][c2 * 64 + (ta & 15) * 4], ~tag, ~tag, ~tag, ~tag);
        const float ri[2] = {rcp(bf_hi(__shfl_sync(0xffffffffu, sel.y, 2 * t))), rcp(bf_hi(__shfl_sync(0xffffffffu, sel.y, 2 * t + 1)))};
        mbar_wait(bars + 8 * B_PART, 0);
        if (hw) {
            const uint32_t pa = sb + OFF_FA + (ta & 63) * 16, go = wu < wg ? 1024 : 0;
            const float4 g0 = lds4f(pa + go), g1 = lds4f(pa + 2048 + go), u0 = lds4f(pa + (go ^ 1024)), u1 = lds4f(pa + 2048 + (go ^ 1024));
            float hv[4];
#pragma unroll
            for (int c = 0; c < 4; c++) {
                const float ga = bf16r(((&g0.x)[c] + (&g1.x)[c]) * ri[c & 1]), up = bf16r(((&u0.x)[c] + (&u1.x)[c]) * ri[c & 1]);
                hv[c] = bf16r(ga * sigmoidf(ga)) * up;
            }
#pragma unroll
            for (int hh = 0; hh < 2; hh++) {
                const float o = __shfl_xor_sync(0xffffffffu, (g & 1) ? hv[2 * hh] : hv[2 * hh + 1], 4);
                st_rlx(&S->h[(fb * 4 + (p & 1) * 2 + hh) * 32 + (2 * t + (g & 1)) * 4 + (g >> 1)],
                       tagw((g & 1) ? pack_bf16(o, hv[2 * hh + 1]) : pack_bf16(hv[2 * hh], o), g < 2, tag));
            }
            TSC(ta == 0, 22);
        }
        {
            uint4 hq[4];
            const uint32_t* hp4 = S->h + kc * 1792 + ta * 4;
            nap(f1 ? N_H : N_H + (N_H ? 5 : 0));
#pragma unroll 1
            for (int it = 0; it < SPIN_LIMIT; it++) {
#pragma unroll
                for (int n = 0; n < 4; n++) hq[n] = ld_rlx4(hp4 + (n < 3 ? n * 512 : p < 2 ? 1536 : 0));
                if (!__any_sync(0xffffffffu, (mism(hq[0].x, hq[1].x, tag) | mism(hq[2].x, hq[3].x, tag)) & 1)) break;
            }
            mbar_wait(bars + 8 * B_G1DONE, 0);
            bar_sync(12, 128);
#pragma unroll
            for (int n = 0; n < 4; n++) sts4(sb + OFF_FA + ta * 16 + (n < 3 ? n * 2048 : p < 2 ? 6144 : 0), hq[n].x, hq[n].y, hq[n].z, hq[n].w);
            fence_async_smem();
            bar_sync(12, 128);
            TSC(ta == 0, 25);
            mbar_wait(bars + 8 * B_F2FULL, 0);
            mbar_wait(bars + 8 * B_AST, 0);
            float acc[4] = {0.f, 0.f, 0.f, 0.f};
            uint32_t da = sd + dlo(OFF_F2X, 8192), db = sd + dlo(OFF_FA, 128);
#pragma unroll 1
            for (int q = 0; q < 7; q++) {
                wg_fence();
#pragma unroll
                for (int j = 0; j < 4; j++) wgmma_n8<1, 0>(acc, mkdesc(da + j * 128, dhi(1024, 1)), mkdesc(db + j * 16, dhi(128, 0)));
                wg_commit();
                if (q == 2) mbar_wait(bars + 8 * B_ATT, 0);
                da = sd + dlo(OFF_FW, 8192) + q * 512; db += 64;
            }
            wg_wait<0>();
            if (ta == 0) mbar_arrive(bars + 8 * B_F2DONE);
#pragma unroll
            for (int c = 0; c < 4; c++) st_rlx(&S->ypart[kc][2 * t + (c & 1)][c2 * 64 + p * 16 + (c >> 1) * 8 + g], tagf(acc[c], tag));
            TSC(ta == 0, 23);
            bar_sync(12, 128);
        }
#pragma unroll 1
        for (int j = 2 * p; j < 2 * p + 2; j++) {
            const uint32_t kj = __shfl_sync(0xffffffffu, sel.x, j);
            const int row = 0x7ff - (kj & 0x7ffu), jj = (row >> 1) - j0 - hp * 128;
            float a0 = 0.f, a1 = 0.f, a2 = 0.f, a3 = 0.f, sig = 0.f;
            if ((row & 1) == par && jj >= 0 && jj < 128) {
                sig = bf16r(sigmoidf(__uint_as_float(((int)kj < 0 ? kj ^ 0x80000000u : ~kj) & 0xffff0000u)));
#pragma unroll 1
                for (int hh = 0; hh < 8; hh += 4) {
                    uint4 v[4];
#pragma unroll 1
                    for (int it = 0; it < SPIN_LIMIT; it++) {
#pragma unroll
                        for (int m = 0; m < 4; m++) v[m] = ld_rlx4(&S->ypart[hh + m][j][cb * 128 + lane * 4]);
                        if (!__any_sync(0xffffffffu, (mism(v[0], tag) | mism(v[1], tag) | mism(v[2], tag) | mism(v[3], tag)) & 1)) break;
                    }
#pragma unroll
                    for (int m = 0; m < 4; m++) { a0 += __uint_as_float(v[m].x); a1 += __uint_as_float(v[m].y); a2 += __uint_as_float(v[m].z); a3 += __uint_as_float(v[m].w); }
                }
                asm volatile("st.shared.u8 [%0], %1;" ::"r"(sb + OFF_ROWMAP + jj), "r"(j) : "memory");
            }
            sts2(sb + OFF_FA + (lane >> 1) * 128 + j * 16 + (lane & 1) * 8, pack_bf16(bf16r(a0) * sig, bf16r(a1) * sig), pack_bf16(bf16r(a2) * sig, bf16r(a3) * sig));
        }
        fence_async_smem();
        __syncwarp();
        if (lane == 0) mbar_arrive(bars + 8 * B_UPD);
        TSC(ta == 0, 24);
        TS_END();
    } else {
        reg_inc<224>();
        const int w = warp >> 2, wi = warp & 3, tw = (1 - w) * 4 + wi;
        const bool elect = (tid & 127) == 0;
        const uint32_t ln = opaque(lane), g = ln >> 2, t = ln & 3;
        uint32_t tag, ow[8][4];
        auto store_o = [&](int f0, int f1) {
            uint8_t* ob = g_o + (size_t)((mt * 2 + 1 - w) * 2 + 1 - (wi >> 1)) * 131072 + nt * 1024 + (wi & 1) * 512 + ln * 4;
#pragma unroll
            for (int f = f0; f < f1; f++)
#pragma unroll
                for (int i = 3; i >= 0; i--)
                    st_rlx(ob + f * 16384 + i * 128, ow[f][i]);
        };
        {
            float acc[2][96];
            const uint32_t sta = opaque(sb + OFF_STAT + tw * 256 + 64 + g * 8);
            {
                float fa[4] = {0.f, 0.f, 0.f, 0.f};
                uint32_t so = STAGE >> 4, bo = bars, ph = 0;
                const uint32_t dx0 = sd + dlo(w ? 40960 : 0, 16), dw0 = sd + dlo(16384, 8192);
                int p = 0;
                if (w) bar_arrive(1, 256);
                uint32_t fm = fb < 112 ? F1_MASK >> (16 * w) : 0u, fph = 0, fd = bars + 8 * (B_FDONE + w);
                int fs = w;
#pragma unroll 1
                for (; p < 16; p++) {
                    mbar_wait(bo + 8 * B_FULLA, ph);
                    if (w) mbar_wait(bo + 8 * B_FULLB, ph);
                    TSC(elect && p == 0, 1 + 8 * w);
                    TSC(TIMING == 9 && elect && p >= 9 && p < 14, 32 + (p - 9) * 6 + w * 3);
                    bar_sync(1 + w, 256);
                    TSC(TIMING == 1 && tid == 0, 32 + p);
                    if (p == 15) {
                        wg_fence();
                        wgmma_n192<0, 1>(acc[1], mkdesc(sd + dlo(OFF_MEAN + 1024, 0) + w * 128, dhi(128, 0)), mkdesc(sd + dlo(OFF_CS, 0), dhi(48, 0)));
                        wgmma_n192<0, 1>(acc[0], mkdesc(sd + dlo(OFF_MEAN, 0) + w * 128, dhi(128, 0)), mkdesc(sd + dlo(OFF_CS, 0), dhi(48, 0)));
                        wg_commit();
                    }
                    wg_fence();
#pragma unroll
                    for (int h = 1; h >= 0; h--) {
#pragma unroll
                        for (int k = 0; k < 4; k++) wgmma_n192<0, 1>(acc[h], mkdesc(dx0 + so + h * 512 + k * 2, dhi(1024, 1)), mkdesc(dw0 + so + k * 128, dhi(1024, 1)), k ? 1 : p);
                        wg_commit();
                    }
                    if (fm & 1) {
                        mbar_wait(bars + 8 * (B_FFULL + fs), fph);
                        TSC(TIMING == 9 && elect && p >= 9, 33 + (p - 9) * 6 + w * 3);
                        wg_fence();
#pragma unroll
                        for (int j = 0; j < 8; j++)
                            wgmma_n8<1, 0>(fa, mkdesc(sd + dlo(OFF_FW, 8192) + fs * 1024 + j * 64, dhi(512, 2)), mkdesc(sd + dlo(OFF_FA, 128) + fs * 128 + j * 16, dhi(128, 0)));
                        wg_commit();
                    }
                    bar_arrive(2 - w, 256);
                    if (p == 15) break;
                    wg_wait<0>();
                    TSC(TIMING == 9 && elect && p >= 9 && p < 14, 34 + (p - 9) * 6 + w * 3);
                    if (wi == 0 && elect_one()) { mbar_arrive(bo + 8 * B_EMPTY); if (fm & 1) mbar_arrive(fd); }
                    so = so == 2 * (STAGE >> 4) ? 0 : so + (STAGE >> 4);
                    bo += 8;
                    if (bo == bars + 24) { bo = bars; ph ^= 1; }
                    if (fm & 1) { fd += 16; fs += 2; if (fs >= 3) { fs -= 3; fph ^= 1; } }
                    fm >>= 1;
                    if (p == P_PART) {
                        if (fb < 112) sts4(sb + OFF_FA + tid * 16, __float_as_uint(fa[0]), __float_as_uint(fa[1]), __float_as_uint(fa[2]), __float_as_uint(fa[3]));
                        __syncwarp();
                        if (lane == 0) mbar_arrive(bars + 8 * B_PART);
                    }
                    if (p != 14) continue;
                    mbar_wait(bars + 8 * B_AUX, 0);
                    mbar_wait(bars + 8 * (B_EMPTY + 1), 0);
                    const uint32_t hm = __float_as_uint(0.5f * lds1f(sb + OFF_STAT + 64 + tw * 256 + ln * 8)) >> 16;
                    sts4(sb + OFF_MEAN + w * 2048 + wi * 256 + (ln >> 4) * 1024 + (ln & 15) * 16, hm * 0x10001u, hm, 0, 0);
                    fence_async_smem();
                }
            }
            TSC(TIMING != 14 && elect, 2 + 8 * w);

            tag = lds1(sb + OFF_TAG);
            mbar_wait(bars + 8 * (B_EMPTY + 2), 0);
            wg_wait<1>();
#pragma unroll
            for (int i = 0; i < 96; i++) asm volatile("" : "+f"(acc[1][i]) :: "memory");
            uint32_t pk[4][24];
            const uint32_t hm = tw == 7 ? ~ln & 1 : 0;
            auto np = [&](int i, int j) {
                const float* a = &acc[i >> 1][4 * j + 2 * (i & 1)];
                pk[i][j] = pack_bf16(a[0], a[1]);
                if (j >= 16) pk[i][j] = movm(pk[i][j]);
                if (i == 3 && j >= 8 && !(j & 1)) pk[i][j] = tagw(pk[i][j], hm, tag);
            };
            const uint32_t ha = sb + OFF_HALO + tw * 2048 + ln * 8;
#pragma unroll
            for (int j = 8; j < 24; j += 2) {
                np(3, j); np(3, j + 1);
                sts2(ha + 2048 + (j - 8) * 128, pk[3][j], pk[3][j + 1]);
                asm volatile("{\n.reg .pred p;\nsetp.eq.u32 p, %3, 7;\n@p st.relaxed.gpu.global.v2.u32 [%0], {%1,%2};\n}" ::"l"((char*)&S->halo[b][ln * 2] + (j - 8) * 128),
                             "r"(pk[3][j]), "r"(pk[3][j + 1]), "r"(tw) : "memory");
            }
            bar_arrive(4 + tw, 64);
            TSC(TIMING == 15 && ln == 0 && tw == 7, 39);
            TSC(TIMING == 8 && ln == 0 && wi == 1, 32 + 8 * w);
            const bool u0 = 2 * t > g, u1 = 2 * t + 1 > g;
            const uint32_t mU = (u0 ? 0xffffu : 0u) | (u1 ? 0xffff0000u : 0u);
            uint2 hl[8];
            float rk[4][2], fq[4][2];
            auto factors = [&]() {
                const uint32_t ka = sb + OFF_STAT + tw * 256 + 4 + t * 16, k0 = opaque(ka + (u0 ? 0 : 64)), k1 = opaque(ka + (u1 ? 8 : 72));
#pragma unroll
                for (int i = 0; i < 4; i++) {
                    const float rq = lds1f(sta + i * 64 + 4) * (0.17677669529663687f * 1.4426950408889634f);
                    rk[i][0] = lds1f(k0 + i * 64); rk[i][1] = lds1f(k1 + i * 64);
                    fq[i][0] = rq * rk[i][0]; fq[i][1] = rq * rk[i][1];
                }
            };
#pragma unroll
            for (int jj = 0; jj < 12; jj++) { const int j = (jj >> 2) * 8 + (jj & 3); np(2, j); if (j < 8) np(3, j); }
            factors();
            wg_wait<0>();
#pragma unroll
            for (int i = 0; i < 96; i++) asm volatile("" : "+f"(acc[0][i]) :: "memory");
            if (elect) mbar_arrive(bars + 8 * B_G1DONE);
            const float mask = tw == 0 && j0 == 0 ? -INFINITY : 0.f;
#pragma unroll
            for (int hd = 0; hd < 2; hd++) {
#pragma unroll
                for (int jj = 0; jj < 12; jj++) {
                    const int j = (jj >> 2) * 8 + hd * 4 + (jj & 3);
                    np(0, j); np(1, j);
                    if (j & 4)
                    { np(2, j); if (j < 8) np(3, j); }
                }
                if (hd == 0) mbar_wait(bars + 8 * B_G1DONE, 0);
                float s[2][3][4];
#pragma unroll
                for (int h = 1; h >= 0; h--)
#pragma unroll
                    for (int n = 2; n >= 0; n--) {
                        if (h == 0 && n == 0 && hd == 0) {
                            TSC(TIMING == 8 && ln == 0 && wi == 1 && s[1][0][0] + s[0][1][0] != 123.456f, 33 + 8 * w);
                            bar_sync(3 + tw, 64);
#pragma unroll
                            for (int c = 0; c < 8; c++) hl[c] = lds2(ha + c * 256);
                        }
                        const int kg = 2 * h - 1 + n;
                        s[h][n][0] = s[h][n][1] = kg < 0 ? mask : 0.f; s[h][n][2] = s[h][n][3] = 0.f;
#pragma unroll
                        for (int ks = 0; ks < 2; ks++) {
                            const int q = hd * 4 + 2 * ks;
                            const uint32_t* k = kg < 0 ? &hl[hd * 2 + ks].x : &pk[kg < 0 ? 0 : kg][8 + q];
                            mma16816(s[h][n], pk[2 * h][q], pk[2 * h + 1][q], pk[2 * h][q + 1], pk[2 * h + 1][q + 1], k[0], k[1]);
                        }
                    }
                uint32_t pp[4], pc[4];
#pragma unroll
                for (int i = 0; i < 4; i++) {
                    const float* sp = &s[i >> 1][i & 1][2 * (i & 1)];
                    const float* sc = &s[i >> 1][(i & 1) + 1][2 * (i & 1)];
                    float a0 = (u0 ? sp[0] : sc[0]) * fq[i][0], a1 = (u1 ? sp[1] : sc[1]) * fq[i][1];
                    float m = fmaxf(a0, a1);
                    m = fmaxf(m, __shfl_xor_sync(0xffffffffu, m, 1));
                    m = fmaxf(m, __shfl_xor_sync(0xffffffffu, m, 2));
                    a0 = ex2(a0 - m); a1 = ex2(a1 - m);
                    float sum = a0 + a1;
                    sum += __shfl_xor_sync(0xffffffffu, sum, 1);
                    sum += __shfl_xor_sync(0xffffffffu, sum, 2);
                    const float inv = rcp(sum);
                    const uint32_t pw = pack_bf16(a0 * rk[i][0] * inv, a1 * rk[i][1] * inv);
                    pp[i] = pw & mU; pc[i] = pw & ~mU;
                }
                TSC(TIMING == 8 && ln == 0 && wi == 1 && pp[0] + pp[3] != 0x12345, 34 + 2 * hd + 8 * w);
#pragma unroll
                for (int fh = 0; fh < 2; fh++)
#pragma unroll
                    for (int i = 0; i < 4; i++) {
                        const int v = 16 + hd * 4 + 2 * fh;
                        const uint32_t* vp = i ? &pk[i ? i - 1 : 0][v] : &hl[4 + hd * 2 + fh].x;
                        float o[4] = {0.f, 0.f, 0.f, 0.f};
                        if (i & 1) mma16816(o, vp[0], vp[1], pk[i][v], pk[i][v + 1], pp[i], pc[i]);
                        else { mma1688(o, pk[i][v], pk[i][v + 1], pc[i]); mma1688(o, vp[0], vp[1], pp[i]); }
                        const uint32_t tm = (ln & 7) == (nt & 3) * 2 + (i & 1);
                        ow[hd * 4 + 2 * fh][i] = tagw(pack_bf16(o[0], o[1]), tm, tag); ow[hd * 4 + 2 * fh + 1][i] = tagw(pack_bf16(o[2], o[3]), tm, tag);
                    }
                store_o(hd ? ST_A : 0, hd ? ST_B : ST_A);
                TSC(TIMING == 11 && !hd && ln == 0 && wi == 3, 45 + w);
                if (!hd) mbar_arrive_after(bars + 8 * B_AST, ln, hl[2].x ^ hl[3].x ^ hl[5].x ^ hl[6].x ^ hl[7].x);
                mbar_wait(bars + 8 * B_G1DONE, 0);
                if (hd && ln == 0) mbar_arrive(bars + 8 * B_ATT);
                TSC(TIMING != 14 && elect && hd == 0, 3 + 8 * w);
                TSC(TIMING == 8 && ln == 0 && wi == 1, 35 + 2 * hd + 8 * w);
            }
        }
        TSC(TIMING != 14 && elect, 4 + 8 * w);
        float acc2[64];
        TSC(TIMING != 14 && elect, 5 + 8 * w);
        {
            const uint32_t ring = sb + (w ? OFF_O1 : OFF_O0), da0 = (ring >> 4) + dlo(0, 1024);
            const uint32_t l2 = opaque(ln), chk = ring + wi * 256 + (l2 >> 3) * 1032 + ((l2 >> 2) & 1) * 132 + (l2 & 3) * 32;
            const uint32_t xs = sb + (wi & 1) * 8192 + (tw >> 1) * 2048, mad = xs + (l2 & 15) * 128;
            auto residual = [&](float* base) {
                const uint32_t sta = sb + OFF_STAT + (8 + hp * 128 + tw * 16 + g) * 8;
                const float2 s0 = lds2f(sta), s1 = lds2f(sta + 64);
                const float m0 = s0.x * s0.y, r0 = 1.f + s0.y, m1 = s1.x * s1.y, r1 = 1.f + s1.y;
                mbar_wait(bars + 8 * B_XR, 0);
#pragma unroll
                for (int j = 0; j < 16; j += 2) {
                    uint32_t xr[4];
                    asm volatile("ldmatrix.sync.aligned.m8n8.x4.shared.b16 {%0,%1,%2,%3}, [%4];" : "=r"(xr[0]), "=r"(xr[1]), "=r"(xr[2]), "=r"(xr[3])
                                 : "r"(mad + (j >> 3) * OFF_X1 + ((((j & 7) + (l2 >> 4)) ^ (l2 & 7)) << 4)) : "memory");
#pragma unroll
                    for (int c = 0; c < 4; c++) {
                        base[4 * j + 2 * c] = fmaf(bf_lo(xr[c]), c & 1 ? r1 : r0, c & 1 ? m1 : m0); base[4 * j + 2 * c + 1] = fmaf(bf_hi(xr[c]), c & 1 ? r1 : r0, c & 1 ? m1 : m0);
                        asm volatile("" : "+f"(base[4 * j + 2 * c]), "+f"(base[4 * j + 2 * c + 1]) :: "memory");
                    }
                }
            };
            residual(acc2);
            uint32_t db = sd + dlo(OFF_WO0, 16384);
#pragma unroll 1
            for (int s = 0; s < 8; s++) {
                const uint32_t ro = (s & 1) * 16384;
                mbar_wait(bars + 8 * (B_WOFULL + s), 0);
                TSC(TIMING == 11 && tid == 0 && s == 0, 43);
                mbar_wait(bars + 8 * (B_OFULL + s) + 64 * w, 0);
                TSC(TIMING == 11 && tid == 0 && s == 0, 44);
#pragma unroll 1
                for (int it = 0; __any_sync(0xffffffffu, (mism(lds1(chk + ro), lds1(chk + ro + 4096), tag) | mism(lds1(chk + ro + 8192), lds1(chk + ro + 12288), tag)) & 1) && it < SPIN_LIMIT; it++) {
                    NRETRY();
                    const uint32_t fo = wi * 256 + (l2 >> 4) * 1024 + (l2 & 15) * 16;
                    uint4 v[8];
#pragma unroll
                    for (int c = 0; c < 8; c++) v[c] = ld_rlx4(g_o + (size_t)(((mt * 2 + hp) * 2 + w) * 8 + s) * 16384 + fo + c * 2048);
#pragma unroll
                    for (int c = 0; c < 8; c++) sts4(ring + ro + fo + c * 2048, v[c].x, v[c].y, v[c].z, v[c].w);
                    fence_async_smem();
                    __syncwarp();
                }
                if (s == 0) mbar_wait(bars + 8 * B_ATT, 0);
                if (s <= 8 - LAST) bar_sync(1 + w, 256);
                TSC(elect && s == 0, 6 + 8 * w);
                TSC(TIMING == 2 && elect, 32 + 16 * w + s);
                wg_fence();
#pragma unroll
                for (int k = 0; k < 8; k++)
                    wgmma_n128<1, 1>(acc2, mkdesc(da0 + (ro >> 4) + k * 128, dhi(128, 0)), mkdesc(db + k * 128, dhi(1024, 1)));
                wg_commit();
                db = wo_next(db, sd + dlo(0, 16384), 4);
                if (s < 8 - LAST) {
                    bar_arrive(2 - w, 256);
                    if (s == 0) store_o(ST_B, 8);
                    wg_wait<0>();
                    if (elect) mbar_arrive(bars + 8 * (B_DONE + s) + 64 * w);
                }
            }
            mbar_wait(bars + 8 * B_UPD, 0);
            int sl0, sl1;
            asm volatile("ld.shared.s8 %0, [%1];" : "=r"(sl0) : "r"(sb + OFF_ROWMAP + tw * 16 + g) : "memory");
            asm volatile("ld.shared.s8 %0, [%1];" : "=r"(sl1) : "r"(sb + OFF_ROWMAP + tw * 16 + 8 + g) : "memory");
            const uint32_t e0 = (sl0 >> 1) == (int)t ? 0x3f80u << ((sl0 & 1) * 16) : 0u, e1 = (sl1 >> 1) == (int)t ? 0x3f80u << ((sl1 & 1) * 16) : 0u;
            if (__any_sync(0xffffffffu, lds1(sb + OFF_ROWMAP + (1 - w) * 64 + (l2 & 15) * 4) != 0xffffffffu)) {
                wg_fence();
                wgmma_rs_n128<1>(acc2, e0, e1, 0u, 0u, mkdesc(sd + dlo(OFF_FA, 0), dhi(128, 0)));
                wg_commit();
            }
            bar_arrive(2 - w, 256);
            wg_wait<0>();
#pragma unroll
            for (int i = 0; i < 64; i++) asm volatile("" : "+f"(acc2[i]) :: "memory");
            TSC(elect, 7 + 8 * w);
#pragma unroll
            for (int j = 0; j < 16; j += 2) {
                const int ch = (j & 7) + (l2 >> 4);
                asm volatile("stmatrix.sync.aligned.m8n8.x4.shared.b16 [%0], {%1,%2,%3,%4};" ::"r"(mad + (j >> 3) * OFF_X1 + ((ch ^ (l2 & 7)) << 4)),
                             "r"(pack_bf16(acc2[4 * j], acc2[4 * j + 1])), "r"(pack_bf16(acc2[4 * j + 2], acc2[4 * j + 3])),
                             "r"(pack_bf16(acc2[4 * j + 4], acc2[4 * j + 5])), "r"(pack_bf16(acc2[4 * j + 6], acc2[4 * j + 7])) : "memory");
                if (TAIL && (TAIL == 2 || w) && (j & 7) == 6) {
                    __syncwarp();
                    uint8_t* op = out + (size_t)(j0 + hp * 128 + tw * 16 + (l2 >> 3)) * 4096 + par * 2048 + cb * 256 + (j >> 3) * 128;
#pragma unroll
                    for (int c = 0; c < 4; c++) {
                        const uint4 v = lds4(xs + (j >> 3) * OFF_X1 + c * 512 + l2 * 16);
                        *(uint4*)(op + c * 4 * 4096 + (((l2 ^ (c * 4 + (l2 >> 3))) & 7) << 4)) = v;
                    }
                } else if ((j & 7) == 6) {
                    fence_async_smem();
                    __syncwarp();
                    if (ln == 0) tma_store_2d(&mout, xs + (j >> 3) * OFF_X1, par * 1024 + cb * 128 + (j >> 3) * 64, j0 + hp * 128 + tw * 16);
                }
            }
            if (ln == 0) asm volatile("cp.async.bulk.commit_group;\ncp.async.bulk.wait_group.read 0;" ::: "memory");
            TSC(elect, 8 + 8 * w);
            TS_END();
        }
    }
}

typedef CUresult (*EncodeFn)(CUtensorMap*, CUtensorMapDataType, cuuint32_t, void*, const cuuint64_t*, const cuuint64_t*, const cuuint32_t*,
                             const cuuint32_t*, CUtensorMapInterleave, CUtensorMapSwizzle, CUtensorMapL2promotion, CUtensorMapFloatOOBfill);

CUtensorMap make_map(EncodeFn fn, const void* base, int rank, const cuuint64_t* dims, const cuuint64_t* strides, const cuuint32_t* box,
                     CUtensorMapSwizzle swz = CU_TENSOR_MAP_SWIZZLE_128B, CUtensorMapL2promotion pro = CU_TENSOR_MAP_L2_PROMOTION_L2_256B) {
    CUtensorMap m;
    cuuint32_t es[5] = {1, 1, 1, 1, 1};
    fn(&m, CU_TENSOR_MAP_DATA_TYPE_BFLOAT16, rank, (void*)base, dims, strides, box, es, CU_TENSOR_MAP_INTERLEAVE_NONE,
       swz, pro, CU_TENSOR_MAP_FLOAT_OOB_FILL_NONE);
    return m;
}

}

extern "C" void kernel_launch(void* const* d_in, const int* in_sizes, int n_in, void* d_out, int out_size) {
    (void)in_sizes; (void)n_in; (void)out_size;
    const __nv_bfloat16* x = (const __nv_bfloat16*)d_in[0];
    const __nv_bfloat16* wqkv = (const __nv_bfloat16*)d_in[1];
    const char* wo = (const char*)d_in[2];
    const __nv_bfloat16* wr = (const __nv_bfloat16*)d_in[4];
    const char* wg = (const char*)d_in[5];
    const char* wu = (const char*)d_in[6];
    const char* wd = (const char*)d_in[7];
    static EncodeFn fn = nullptr;
    static int by_sm = 0;
    static Scratch* scr = nullptr;
    if (!fn) {
        void* p = nullptr; cudaDriverEntryPointQueryResult q;
        cudaGetDriverEntryPoint("cuTensorMapEncodeTiled", &p, cudaEnableDefault, &q);
        fn = (EncodeFn)p;
        cudaFuncSetAttribute(fused_kernel, cudaFuncAttributeMaxDynamicSharedMemorySize, SMEM_LAUNCH);
        cudaGetSymbolAddress((void**)&scr, g_scr);
        int dev = 0, sms = 0;
        cudaGetDevice(&dev);
        cudaDeviceGetAttribute(&sms, cudaDevAttrMultiProcessorCount, dev);
        by_sm = sms == 132;
    }
    Roles roles;
    for (int i = 0; i < 132; i++) {
        const int T = i >> 1, T8 = T < 32 ? T : T + 1 + (T - 32) / 7, fb = (T < 60 ? (~T8 & 7) * 8 + (T8 >> 3) : T < 62 ? T + 4 : T - 2) * 2 + (i & 1);
        roles.v[i] = fb | ((fb & ~31) | (fb & 1) << 4 | (fb & 31) >> 1) << 8;
    }
    const cuuint64_t xd[4] = {2048, 16, 32, 2}, xs[3] = {4096, 131072, 65536};
    const cuuint32_t xb[4] = {64, 16, 4, 2};
    const cuuint64_t wdm[3] = {1024, 1024, 3}, wst[2] = {6144, 2048};
    const cuuint32_t wb[3] = {64, 64, 3};
    const cuuint64_t od[4] = {64, 64, 16, 16}, ost[3] = {2048, 131072, 128};
    const cuuint32_t ob[4] = {64, 8, 16, 2};
    const cuuint64_t yd[2] = {2048, 1024}, yst[1] = {4096};
    const cuuint32_t yb[2] = {64, 16};
    const cuuint64_t sd[3] = {64, 1024, 32}, sst[2] = {4096, 128};
    const cuuint32_t sbx[3] = {64, 16, 4};
    CUtensorMap mxs = make_map(fn, x, 3, sd, sst, sbx);
    const cuuint64_t cd[3] = {3072, 64, 16}, cst[2] = {6144, 393216};
    const cuuint32_t cbx[3] = {64, 8, 2};
    CUtensorMap mcs = make_map(fn, wqkv, 3, cd, cst, cbx, CU_TENSOR_MAP_SWIZZLE_NONE);
    CUtensorMap mx = make_map(fn, x, 4, xd, xs, xb), mw = make_map(fn, wqkv, 3, wdm, wst, wb);
    CUtensorMap mwo = make_map(fn, wo, 4, od, ost, ob), mout = make_map(fn, d_out, 2, yd, yst, yb);
    const cuuint64_t gd[3] = {3584, 1024, 2}, gst[2] = {7168, (cuuint64_t)(wu < wg ? wg - wu : wu - wg)};
    const cuuint32_t gb[3] = {32, 128, 2};
    const cuuint64_t dd[2] = {1024, 3584}, dst[1] = {2048};
    const cuuint32_t db[2] = {64, 64};
    CUtensorMap mgu = make_map(fn, wu < wg ? wu : wg, 3, gd, gst, gb, CU_TENSOR_MAP_SWIZZLE_64B, CU_TENSOR_MAP_L2_PROMOTION_L2_128B);
    CUtensorMap mwd = make_map(fn, wd, 2, dd, dst, db, CU_TENSOR_MAP_SWIZZLE_128B, CU_TENSOR_MAP_L2_PROMOTION_L2_128B);
    fused_kernel<<<132, 512, SMEM_LAUNCH, cudaStreamPerThread>>>(by_sm, x, wqkv, wr, scr, wg, wu, wd, wo, (uint8_t*)d_out, roles, mw, mx, mwo, mxs, mcs, mout, mgu, mwd);
}
```
